```python
import torch

def _softmax(x, axis=-1):
    return torch.softmax(x, dim=axis)

def _gelu(x):
    return torch.nn.functional.gelu(x, approximate='tanh')

def _silu(x):
    return torch.nn.functional.silu(x)

def _sigmoid(x):
    return torch.sigmoid(x)

def _layernorm(x, axis=-1, eps=1e-05):
    m = x.mean(dim=axis, keepdim=True)
    v = x.var(dim=axis, keepdim=True, unbiased=False)
    return (x - m) / torch.sqrt(v + eps)

def _scatter_add(tgt, idx, src, axis=0):
    return tgt.clone().index_add_(axis, idx, src)

def _segment_sum(src, seg, n):
    out = torch.zeros((n,) + src.shape[1:], dtype=src.dtype)
    return out.index_add_(0, seg, src)

def _pad(x, pw):
    flat = tuple((v for pair in reversed(pw) for v in pair))
    return torch.nn.functional.pad(x, flat)
kernel_name = 'gated_mix__grouped_kv_mqa__mixer_gmlp__prompt'

def setup_inputs():

    _w = lambda a: (lambda t: t.to(torch.bfloat16) if t.is_floating_point() else t)(torch.as_tensor(a))

    def _A_setup():
        B, S, D, H = (1, 2048, 512, 32)
        Dh = D // H
        return {'x': _w((lambda *s: torch.randn(*s, dtype=torch.bfloat16) * 0.05)(B, S, D)), 'wq': _w((lambda *s: torch.randn(*s, dtype=torch.bfloat16) * 1.6)(D, H * Dh)), 'wk': _w((lambda *s: torch.randn(*s, dtype=torch.bfloat16) * 1.6)(D, Dh)), 'wv': _w((lambda *s: torch.randn(*s, dtype=torch.bfloat16) * 0.2)(D, Dh)), 'wo': _w((lambda *s: torch.randn(*s, dtype=torch.bfloat16) * 0.2)(H * Dh, D))}
    _A_in = _A_setup()

    def _B_setup():
        B, S, D, F = (1, 2048, 512, 1376)
        Fh = F // 2
        return {'x': _w((lambda *s: torch.randn(*s, dtype=torch.bfloat16) * 0.05)(B, S, D)), 'w_in': _w((lambda *s: torch.randn(*s, dtype=torch.bfloat16) * 0.8)(D, 2 * Fh)), 'w_sp': _w(0.01 * (lambda *s: torch.randn(*s, dtype=torch.bfloat16) * 0.8)(S, S)), 'b_sp': _w(1.0 + 0.01 * (lambda *s: torch.randn(*s, dtype=torch.bfloat16) * 0.05)(S)), 'w_out': _w((lambda *s: torch.randn(*s, dtype=torch.bfloat16) * 0.05)(Fh, D))}
    _B_in = _B_setup()
    return {'A_x': _A_in['x'], 'A_wq': _A_in['wq'], 'A_wk': _A_in['wk'], 'A_wv': _A_in['wv'], 'A_wo': _A_in['wo'], 'B_x': _B_in['x'], 'B_w_in': _B_in['w_in'], 'B_w_sp': _B_in['w_sp'], 'B_b_sp': _B_in['b_sp'], 'B_w_out': _B_in['w_out'], 'gate_w': _w((lambda *s: torch.randn(*s, dtype=torch.bfloat16) * 0.05)(512) * 16.0)}

def reference(A_x, A_wq, A_wk, A_wv, A_wo, B_x, B_w_in, B_w_sp, B_b_sp, B_w_out, gate_w):

    def _A_ref(x, wq, wk, wv, wo):
        B, S, D = x.shape
        H = 32
        Dh = D // H
        q = (lambda x, *d: x.permute(*d))((x @ wq).reshape(B, S, H, Dh), 0, 2, 1, 3)
        k = x @ wk
        v = x @ wv
        scores = torch.einsum('bhqd,bkd->bhqk', q, k) * Dh ** (-0.5)
        p = _softmax(scores, axis=-1)
        o = torch.einsum('bhqk,bkd->bhqd', p, v)
        return (lambda x, *d: x.permute(*d))(o, 0, 2, 1, 3).reshape(B, S, H * Dh) @ wo

    def _B_ref(x, w_in, w_sp, b_sp, w_out):
        B, S, D = x.shape
        F = w_in.shape[-1]
        Fh = F // 2
        z = _gelu(torch.einsum('bsd,df->bsf', x, w_in))
        z1 = z[..., :Fh].clone()
        z2 = _layernorm(z[..., Fh:], axis=-1)
        g = torch.einsum('ts,bsf->btf', w_sp, z2) + b_sp[None, :, None]
        return torch.einsum('bsf,fd->bsd', z1 * g, w_out)
    x = A_x
    g = _sigmoid((x * gate_w).sum(-1, keepdims=True))
    a = _A_ref(x, A_wq, A_wk, A_wv, A_wo)
    b = _B_ref(x, B_w_in, B_w_sp, B_b_sp, B_w_out)
    return g * a + (1 - g) * b
```

```cpp
#include <cuda_runtime.h>
#include <cuda.h>
#include <cuda_bf16.h>
#include <cuda_fp16.h>
#include <stdint.h>

namespace {

constexpr int NCTA = 128;
constexpr int NTHREADS = 640;
constexpr int NP = 40;
constexpr int NM = 64 - NP;
constexpr int SPIN_LIMIT = 1 << 18;

constexpr uint32_t SM_K = 0;
constexpr uint32_t SM_ONES = 98304;
constexpr uint32_t KV_BYTES = 131328;
constexpr uint32_t SM_BAR = 131328;
constexpr uint32_t SM_RING = 132096;
constexpr uint32_t RSTAGE = 27648;
constexpr uint32_t WSLOT = 20480;
constexpr uint32_t SM_Q = 215040;
constexpr uint32_t SM_G = 231424;
constexpr uint32_t SM_MISC = 231936;
constexpr uint32_t SMEM_BYTES = 232448;

constexpr int B_XFULL = 0, B_XEMPTY = 8, B_WFULL = 16, B_WEMPTY = 32, B_KVFULL = 44, B_OFULL = 52, B_RFULL = 60,
              B_REMPTY = 63, B_KFB = 66, B_KSTAT = 67, B_DEC = 68, B_WOFULL = 69, B_EPOCH = 70, B_COUNT = 71;
constexpr int M_EPOCH = 0, M_KN2 = 1, M_VOK = 2, M_FAST = 3, M_RED = 4;

__device__ uint4 g_kimg[KV_BYTES / 16];
__device__ uint4 g_kbf[65536 / 16];
__device__ float g_kvstat[NCTA * 16];
__device__ float2 g_lnstat[16 * 8 * 128];
__device__ uint4 g_z2n[8 * 32 * 11264 / 16];
__device__ uint4 g_z1[NCTA * 11 * 128];
__device__ uint4 g_u[16 * 11 * 1024];
__device__ uint4 g_o[16 * 8 * 1024];
__device__ float4 g_part[NCTA * 2 * 3 * 128];
__device__ unsigned g_ticket;
__device__ unsigned g_kvcnt[32];
__device__ unsigned g_statcnt[32 * 32];
__device__ unsigned g_zflag[8 * 32];
__device__ unsigned g_ucnt[16 * 32];
__device__ unsigned g_ocnt[16 * 32];
#define TS(k) do { } while (0)

__device__ __forceinline__ void mbar_init(uint32_t a, uint32_t c) { asm volatile("mbarrier.init.shared::cta.b64 [%0], %1;" ::"r"(a), "r"(c) : "memory"); }
__device__ __forceinline__ void mbar_expect(uint32_t a, uint32_t b) { asm volatile("mbarrier.arrive.expect_tx.shared::cta.b64 _, [%0], %1;" ::"r"(a), "r"(b) : "memory"); }
__device__ __forceinline__ void mbar_arrive(uint32_t a) { asm volatile("mbarrier.arrive.shared::cta.b64 _, [%0];" ::"r"(a) : "memory"); }
__device__ __forceinline__ void mbar_arrive_both(uint32_t a) {
  asm volatile("{\n.reg .b32 ra;\nmapa.shared::cluster.u32 ra, %0, 0;\nmbarrier.arrive.release.cluster.shared::cluster.b64 _, [ra];\n"
               "mapa.shared::cluster.u32 ra, %0, 1;\nmbarrier.arrive.release.cluster.shared::cluster.b64 _, [ra];\n}" ::"r"(a) : "memory");
}
__device__ __forceinline__ void mbar_wait(uint32_t a, uint32_t ph) {
  uint32_t ok;
#pragma unroll 1
  for (int n = 0; n < SPIN_LIMIT; n++) {
    asm volatile("{\n.reg .pred p;\nmbarrier.try_wait.parity.shared::cta.b64 p, [%1], %2;\nselp.u32 %0, 1, 0, p;\n}" : "=r"(ok) : "r"(a), "r"(ph) : "memory");
    if (ok) break;
  }
}
__device__ __forceinline__ void mbar_wait_cl(uint32_t a, uint32_t ph) {
  uint32_t ok;
#pragma unroll 1
  for (int n = 0; n < SPIN_LIMIT; n++) {
    asm volatile("{\n.reg .pred p;\nmbarrier.try_wait.parity.acquire.cluster.shared::cta.b64 p, [%1], %2;\nselp.u32 %0, 1, 0, p;\n}" : "=r"(ok) : "r"(a), "r"(ph) : "memory");
    if (ok) break;
  }
}
__device__ __forceinline__ void tma2d(uint32_t dst, const CUtensorMap* tm, int c0, int c1, uint32_t bar) {
  asm volatile("cp.async.bulk.tensor.2d.shared::cluster.global.mbarrier::complete_tx::bytes [%0], [%1, {%3, %4}], [%2];"
               ::"r"(dst), "l"(tm), "r"(bar), "r"(c0), "r"(c1) : "memory");
}
__device__ __forceinline__ void tma2d_mc(uint32_t dst, const CUtensorMap* tm, int c0, int c1, uint32_t bar) {
  asm volatile("cp.async.bulk.tensor.2d.shared::cluster.global.mbarrier::complete_tx::bytes.multicast::cluster [%0], [%1, {%3, %4}], [%2], %5;"
               ::"r"(dst), "l"(tm), "r"(bar), "r"(c0), "r"(c1), "h"((uint16_t)3) : "memory");
}
__device__ __forceinline__ void bulk(uint32_t dst, const void* src, uint32_t bytes, uint32_t bar) {
  asm volatile("cp.async.bulk.shared::cluster.global.mbarrier::complete_tx::bytes [%0], [%1], %2, [%3];"
               ::"r"(dst), "l"(src), "r"(bytes), "r"(bar) : "memory");
}
__device__ __forceinline__ void bulk_mc(uint32_t dst, const void* src, uint32_t bytes, uint32_t bar) {
  asm volatile("cp.async.bulk.shared::cluster.global.mbarrier::complete_tx::bytes.multicast::cluster [%0], [%1], %2, [%3], %4;"
               ::"r"(dst), "l"(src), "r"(bytes), "r"(bar), "h"((uint16_t)3) : "memory");
}
__device__ __forceinline__ void l2_prefetch(const void* src, uint32_t bytes) { asm volatile("cp.async.bulk.prefetch.L2.global [%0], %1;" ::"l"(src), "r"(bytes) : "memory"); }
__device__ __forceinline__ void fence_async() { asm volatile("fence.proxy.async;" ::: "memory"); }
__device__ __forceinline__ void bar_sync(int id, int n) { asm volatile("bar.sync %0, %1;" ::"r"(id), "r"(n) : "memory"); }
__device__ __forceinline__ void bar_arrive(int id, int n) { asm volatile("bar.arrive %0, %1;" ::"r"(id), "r"(n) : "memory"); }
__device__ __forceinline__ void red_release(unsigned* p) { asm volatile("red.release.gpu.global.add.u32 [%0], 1;" ::"l"(p) : "memory"); }
__device__ __forceinline__ void st_release(unsigned* p, unsigned v) { asm volatile("st.release.gpu.global.u32 [%0], %1;" ::"l"(p), "r"(v) : "memory"); }
__device__ __forceinline__ unsigned ld_acquire(const unsigned* p) { unsigned v; asm volatile("ld.acquire.gpu.global.u32 %0, [%1];" : "=r"(v) : "l"(p) : "memory"); return v; }
__device__ __forceinline__ void wait_ge(const unsigned* p, unsigned target) {
#pragma unroll 1
  for (int n = 0; n < SPIN_LIMIT; n++) {
    if ((int)(ld_acquire(p) - target) >= 0) break;
    __nanosleep(20);
  }
}
__device__ __forceinline__ void wg_fence() { asm volatile("wgmma.fence.sync.aligned;" ::: "memory"); }
__device__ __forceinline__ void wg_commit() { asm volatile("wgmma.commit_group.sync.aligned;" ::: "memory"); }
template <int N> __device__ __forceinline__ void wg_wait() { asm volatile("wgmma.wait_group.sync.aligned %0;" ::"n"(N) : "memory"); }
template <int n> __device__ __forceinline__ void regfence(float (&d)[n]) {
#pragma unroll
  for (int i = 0; i < n; i++) asm volatile("" : "+f"(d[i])::"memory");
}
__device__ __forceinline__ uint64_t mkdesc(uint32_t addr, uint32_t lbo, uint32_t sbo, int swz) {
  return (uint64_t)((addr & 0x3FFFF) >> 4) | ((uint64_t)(lbo >> 4) << 16) | ((uint64_t)(sbo >> 4) << 32) | ((uint64_t)swz << 62);
}
__device__ __forceinline__ uint32_t pack_bf16(float lo, float hi) { uint32_t r; asm("cvt.rn.bf16x2.f32 %0, %1, %2;" : "=r"(r) : "f"(hi), "f"(lo)); return r; }
__device__ __forceinline__ uint32_t pack_f16(float lo, float hi) { uint32_t r; asm("cvt.rn.f16x2.f32 %0, %1, %2;" : "=r"(r) : "f"(hi), "f"(lo)); return r; }
__device__ __forceinline__ float bf_lo(uint32_t v) { return __uint_as_float(v << 16); }
__device__ __forceinline__ float bf_hi(uint32_t v) { return __uint_as_float(v & 0xFFFF0000u); }
__device__ __forceinline__ float ex2(float x) { float r; asm("ex2.approx.ftz.f32 %0, %1;" : "=f"(r) : "f"(x)); return r; }
__device__ __forceinline__ float gelu_tanh(float x) {
  float u = x * fmaf(x * x, 0.0356774081f, 0.7978845608f), t;
  asm("tanh.approx.f32 %0, %1;" : "=f"(t) : "f"(u));
  float h = 0.5f * x;
  return fmaf(h, t, h);
}
__device__ __forceinline__ void sts32(uint32_t a, uint32_t v) { asm volatile("st.shared.u32 [%0], %1;" ::"r"(a), "r"(v) : "memory"); }
__device__ __forceinline__ void sts16(uint32_t a, uint16_t v) { asm volatile("st.shared.u16 [%0], %1;" ::"r"(a), "h"(v) : "memory"); }
__device__ __forceinline__ void sts128(uint32_t a, uint32_t x, uint32_t y, uint32_t z, uint32_t w) { asm volatile("st.shared.v4.u32 [%0], {%1,%2,%3,%4};" ::"r"(a), "r"(x), "r"(y), "r"(z), "r"(w) : "memory"); }
__device__ __forceinline__ uint32_t lds32(uint32_t a) { uint32_t v; asm volatile("ld.shared.u32 %0, [%1];" : "=r"(v) : "r"(a) : "memory"); return v; }
__device__ __forceinline__ float ldsf(uint32_t a) { return __uint_as_float(lds32(a)); }
__device__ __forceinline__ uint4 lds128(uint32_t a) { uint4 v; asm volatile("ld.shared.v4.u32 {%0,%1,%2,%3}, [%4];" : "=r"(v.x), "=r"(v.y), "=r"(v.z), "=r"(v.w) : "r"(a) : "memory"); return v; }

template<int OFF, int TOT> __device__ __forceinline__ void wg_ss_n88(float (&d)[TOT], uint64_t da, uint64_t db) {
  asm volatile("wgmma.mma_async.sync.aligned.m64n88k16.f32.bf16.bf16 {%0, %1, %2, %3, %4, %5, %6, %7, %8, %9, %10, %11, %12, %13, %14, %15, %16, %17, %18, %19, %20, %21, %22, %23, %24, %25, %26, %27, %28, %29, %30, %31, %32, %33, %34, %35, %36, %37, %38, %39, %40, %41, %42, %43}, %44, %45, 1, 1, 1, 0, 1;"
    : "+f"(d[OFF+0]), "+f"(d[OFF+1]), "+f"(d[OFF+2]), "+f"(d[OFF+3]), "+f"(d[OFF+4]), "+f"(d[OFF+5]), "+f"(d[OFF+6]), "+f"(d[OFF+7]),
      "+f"(d[OFF+8]), "+f"(d[OFF+9]), "+f"(d[OFF+10]), "+f"(d[OFF+11]), "+f"(d[OFF+12]), "+f"(d[OFF+13]), "+f"(d[OFF+14]), "+f"(d[OFF+15]),
      "+f"(d[OFF+16]), "+f"(d[OFF+17]), "+f"(d[OFF+18]), "+f"(d[OFF+19]), "+f"(d[OFF+20]), "+f"(d[OFF+21]), "+f"(d[OFF+22]), "+f"(d[OFF+23]),
      "+f"(d[OFF+24]), "+f"(d[OFF+25]), "+f"(d[OFF+26]), "+f"(d[OFF+27]), "+f"(d[OFF+28]), "+f"(d[OFF+29]), "+f"(d[OFF+30]), "+f"(d[OFF+31]),
      "+f"(d[OFF+32]), "+f"(d[OFF+33]), "+f"(d[OFF+34]), "+f"(d[OFF+35]), "+f"(d[OFF+36]), "+f"(d[OFF+37]), "+f"(d[OFF+38]), "+f"(d[OFF+39]),
      "+f"(d[OFF+40]), "+f"(d[OFF+41]), "+f"(d[OFF+42]), "+f"(d[OFF+43])
    : "l"(da), "l"(db));
}
template<int OFF, int TOT> __device__ __forceinline__ void wg_ss_n64(float (&d)[TOT], uint64_t da, uint64_t db) {
  asm volatile("wgmma.mma_async.sync.aligned.m64n64k16.f32.bf16.bf16 {%0, %1, %2, %3, %4, %5, %6, %7, %8, %9, %10, %11, %12, %13, %14, %15, %16, %17, %18, %19, %20, %21, %22, %23, %24, %25, %26, %27, %28, %29, %30, %31}, %32, %33, 1, 1, 1, 0, 1;"
    : "+f"(d[OFF+0]), "+f"(d[OFF+1]), "+f"(d[OFF+2]), "+f"(d[OFF+3]), "+f"(d[OFF+4]), "+f"(d[OFF+5]), "+f"(d[OFF+6]), "+f"(d[OFF+7]),
      "+f"(d[OFF+8]), "+f"(d[OFF+9]), "+f"(d[OFF+10]), "+f"(d[OFF+11]), "+f"(d[OFF+12]), "+f"(d[OFF+13]), "+f"(d[OFF+14]), "+f"(d[OFF+15]),
      "+f"(d[OFF+16]), "+f"(d[OFF+17]), "+f"(d[OFF+18]), "+f"(d[OFF+19]), "+f"(d[OFF+20]), "+f"(d[OFF+21]), "+f"(d[OFF+22]), "+f"(d[OFF+23]),
      "+f"(d[OFF+24]), "+f"(d[OFF+25]), "+f"(d[OFF+26]), "+f"(d[OFF+27]), "+f"(d[OFF+28]), "+f"(d[OFF+29]), "+f"(d[OFF+30]), "+f"(d[OFF+31])
    : "l"(da), "l"(db));
}
template<int OFF, int TOT> __device__ __forceinline__ void wg_ss_n32t(float (&d)[TOT], uint64_t da, uint64_t db) {
  asm volatile("wgmma.mma_async.sync.aligned.m64n32k16.f32.bf16.bf16 {%0, %1, %2, %3, %4, %5, %6, %7, %8, %9, %10, %11, %12, %13, %14, %15}, %16, %17, 1, 1, 1, 1, 0;"
    : "+f"(d[OFF+0]), "+f"(d[OFF+1]), "+f"(d[OFF+2]), "+f"(d[OFF+3]), "+f"(d[OFF+4]), "+f"(d[OFF+5]), "+f"(d[OFF+6]), "+f"(d[OFF+7]),
      "+f"(d[OFF+8]), "+f"(d[OFF+9]), "+f"(d[OFF+10]), "+f"(d[OFF+11]), "+f"(d[OFF+12]), "+f"(d[OFF+13]), "+f"(d[OFF+14]), "+f"(d[OFF+15])
    : "l"(da), "l"(db));
}
template<int SCD, int OFF, int TOT> __device__ __forceinline__ void wg_qk_n16(float (&d)[TOT], uint32_t a0, uint32_t a1, uint32_t a2, uint32_t a3, uint64_t db) {
  asm volatile("wgmma.mma_async.sync.aligned.m64n16k16.f32.f16.f16 {%0, %1, %2, %3, %4, %5, %6, %7}, {%8,%9,%10,%11}, %12, %13, 1, 1, 0;"
    : "+f"(d[OFF+0]), "+f"(d[OFF+1]), "+f"(d[OFF+2]), "+f"(d[OFF+3]), "+f"(d[OFF+4]), "+f"(d[OFF+5]), "+f"(d[OFF+6]), "+f"(d[OFF+7])
    : "r"(a0), "r"(a1), "r"(a2), "r"(a3), "l"(db), "n"(SCD));
}
template<int SCD, int OFF, int TOT> __device__ __forceinline__ void wg_qk_n24(float (&d)[TOT], uint32_t a0, uint32_t a1, uint32_t a2, uint32_t a3, uint64_t db) {
  asm volatile("wgmma.mma_async.sync.aligned.m64n24k16.f32.f16.f16 {%0, %1, %2, %3, %4, %5, %6, %7, %8, %9, %10, %11}, {%12,%13,%14,%15}, %16, %17, 1, 1, 0;"
    : "+f"(d[OFF+0]), "+f"(d[OFF+1]), "+f"(d[OFF+2]), "+f"(d[OFF+3]), "+f"(d[OFF+4]), "+f"(d[OFF+5]), "+f"(d[OFF+6]), "+f"(d[OFF+7]),
      "+f"(d[OFF+8]), "+f"(d[OFF+9]), "+f"(d[OFF+10]), "+f"(d[OFF+11])
    : "r"(a0), "r"(a1), "r"(a2), "r"(a3), "l"(db), "n"(SCD));
}
template<int SCD, int OFF, int TOT> __device__ __forceinline__ void wg_qk_n32(float (&d)[TOT], uint32_t a0, uint32_t a1, uint32_t a2, uint32_t a3, uint64_t db) {
  asm volatile("wgmma.mma_async.sync.aligned.m64n32k16.f32.f16.f16 {%0, %1, %2, %3, %4, %5, %6, %7, %8, %9, %10, %11, %12, %13, %14, %15}, {%16,%17,%18,%19}, %20, %21, 1, 1, 0;"
    : "+f"(d[OFF+0]), "+f"(d[OFF+1]), "+f"(d[OFF+2]), "+f"(d[OFF+3]), "+f"(d[OFF+4]), "+f"(d[OFF+5]), "+f"(d[OFF+6]), "+f"(d[OFF+7]),
      "+f"(d[OFF+8]), "+f"(d[OFF+9]), "+f"(d[OFF+10]), "+f"(d[OFF+11]), "+f"(d[OFF+12]), "+f"(d[OFF+13]), "+f"(d[OFF+14]), "+f"(d[OFF+15])
    : "r"(a0), "r"(a1), "r"(a2), "r"(a3), "l"(db), "n"(SCD));
}
template<int SCD, int OFF, int TOT> __device__ __forceinline__ void wg_qk_n40(float (&d)[TOT], uint32_t a0, uint32_t a1, uint32_t a2, uint32_t a3, uint64_t db) {
  asm volatile("wgmma.mma_async.sync.aligned.m64n40k16.f32.f16.f16 {%0, %1, %2, %3, %4, %5, %6, %7, %8, %9, %10, %11, %12, %13, %14, %15, %16, %17, %18, %19}, {%20,%21,%22,%23}, %24, %25, 1, 1, 0;"
    : "+f"(d[OFF+0]), "+f"(d[OFF+1]), "+f"(d[OFF+2]), "+f"(d[OFF+3]), "+f"(d[OFF+4]), "+f"(d[OFF+5]), "+f"(d[OFF+6]), "+f"(d[OFF+7]),
      "+f"(d[OFF+8]), "+f"(d[OFF+9]), "+f"(d[OFF+10]), "+f"(d[OFF+11]), "+f"(d[OFF+12]), "+f"(d[OFF+13]), "+f"(d[OFF+14]), "+f"(d[OFF+15]),
      "+f"(d[OFF+16]), "+f"(d[OFF+17]), "+f"(d[OFF+18]), "+f"(d[OFF+19])
    : "r"(a0), "r"(a1), "r"(a2), "r"(a3), "l"(db), "n"(SCD));
}
template<int SCD, int OFF, int TOT> __device__ __forceinline__ void wg_qk_n48(float (&d)[TOT], uint32_t a0, uint32_t a1, uint32_t a2, uint32_t a3, uint64_t db) {
  asm volatile("wgmma.mma_async.sync.aligned.m64n48k16.f32.f16.f16 {%0, %1, %2, %3, %4, %5, %6, %7, %8, %9, %10, %11, %12, %13, %14, %15, %16, %17, %18, %19, %20, %21, %22, %23}, {%24,%25,%26,%27}, %28, %29, 1, 1, 0;"
    : "+f"(d[OFF+0]), "+f"(d[OFF+1]), "+f"(d[OFF+2]), "+f"(d[OFF+3]), "+f"(d[OFF+4]), "+f"(d[OFF+5]), "+f"(d[OFF+6]), "+f"(d[OFF+7]),
      "+f"(d[OFF+8]), "+f"(d[OFF+9]), "+f"(d[OFF+10]), "+f"(d[OFF+11]), "+f"(d[OFF+12]), "+f"(d[OFF+13]), "+f"(d[OFF+14]), "+f"(d[OFF+15]),
      "+f"(d[OFF+16]), "+f"(d[OFF+17]), "+f"(d[OFF+18]), "+f"(d[OFF+19]), "+f"(d[OFF+20]), "+f"(d[OFF+21]), "+f"(d[OFF+22]), "+f"(d[OFF+23])
    : "r"(a0), "r"(a1), "r"(a2), "r"(a3), "l"(db), "n"(SCD));
}
template<int SCD, int OFF, int TOT> __device__ __forceinline__ void wg_pv_n24(float (&d)[TOT], uint32_t a0, uint32_t a1, uint32_t a2, uint32_t a3, uint64_t db) {
  asm volatile("wgmma.mma_async.sync.aligned.m64n24k16.f32.bf16.bf16 {%0, %1, %2, %3, %4, %5, %6, %7, %8, %9, %10, %11}, {%12,%13,%14,%15}, %16, %17, 1, 1, 1;"
    : "+f"(d[OFF+0]), "+f"(d[OFF+1]), "+f"(d[OFF+2]), "+f"(d[OFF+3]), "+f"(d[OFF+4]), "+f"(d[OFF+5]), "+f"(d[OFF+6]), "+f"(d[OFF+7]),
      "+f"(d[OFF+8]), "+f"(d[OFF+9]), "+f"(d[OFF+10]), "+f"(d[OFF+11])
    : "r"(a0), "r"(a1), "r"(a2), "r"(a3), "l"(db), "n"(SCD));
}
template<int SCD, int OFF, int TOT> __device__ __forceinline__ void wg_qkb_n64(float (&d)[TOT], uint32_t a0, uint32_t a1, uint32_t a2, uint32_t a3, uint64_t db) {
  asm volatile("wgmma.mma_async.sync.aligned.m64n64k16.f32.bf16.bf16 {%0, %1, %2, %3, %4, %5, %6, %7, %8, %9, %10, %11, %12, %13, %14, %15, %16, %17, %18, %19, %20, %21, %22, %23, %24, %25, %26, %27, %28, %29, %30, %31}, {%32,%33,%34,%35}, %36, %37, 1, 1, 0;"
    : "+f"(d[OFF+0]), "+f"(d[OFF+1]), "+f"(d[OFF+2]), "+f"(d[OFF+3]), "+f"(d[OFF+4]), "+f"(d[OFF+5]), "+f"(d[OFF+6]), "+f"(d[OFF+7]),
      "+f"(d[OFF+8]), "+f"(d[OFF+9]), "+f"(d[OFF+10]), "+f"(d[OFF+11]), "+f"(d[OFF+12]), "+f"(d[OFF+13]), "+f"(d[OFF+14]), "+f"(d[OFF+15]),
      "+f"(d[OFF+16]), "+f"(d[OFF+17]), "+f"(d[OFF+18]), "+f"(d[OFF+19]), "+f"(d[OFF+20]), "+f"(d[OFF+21]), "+f"(d[OFF+22]), "+f"(d[OFF+23]),
      "+f"(d[OFF+24]), "+f"(d[OFF+25]), "+f"(d[OFF+26]), "+f"(d[OFF+27]), "+f"(d[OFF+28]), "+f"(d[OFF+29]), "+f"(d[OFF+30]), "+f"(d[OFF+31])
    : "r"(a0), "r"(a1), "r"(a2), "r"(a3), "l"(db), "n"(SCD));
}
template<int N, int SCD, int OFF, int TOT> __device__ __forceinline__ void wg_qk(float (&d)[TOT], const uint32_t (&q)[4], uint64_t db) {
  if constexpr (N == 16) wg_qk_n16<SCD, OFF, TOT>(d, q[0], q[1], q[2], q[3], db);
  if constexpr (N == 24) wg_qk_n24<SCD, OFF, TOT>(d, q[0], q[1], q[2], q[3], db);
  if constexpr (N == 32) wg_qk_n32<SCD, OFF, TOT>(d, q[0], q[1], q[2], q[3], db);
  if constexpr (N == 40) wg_qk_n40<SCD, OFF, TOT>(d, q[0], q[1], q[2], q[3], db);
  if constexpr (N == 48) wg_qk_n48<SCD, OFF, TOT>(d, q[0], q[1], q[2], q[3], db);
}

__device__ __forceinline__ uint32_t exp_mufu(float a, float b) { return pack_bf16(ex2(a), ex2(b)); }
__device__ __forceinline__ uint32_t exp_poly(float a, float b, uint32_t mlo, uint32_t mhi) {
  uint32_t u = __byte_perm(__float_as_uint(a), __float_as_uint(b), 0x6521), mh, e, p;
  asm("lop3.b32 %0, %1, %2, 0x3F003F00, 0xEA;" : "=r"(mh) : "r"(u), "r"(mlo));
  asm("lop3.b32 %0, %1, %2, 0x00020002, 0xEA;" : "=r"(e) : "r"(u), "r"(mhi));
  asm("fma.rn.bf16x2 %0, %1, %2, %3;" : "=r"(p) : "r"(u), "r"(mh), "r"(e));
  return p;
}
constexpr float MAGIC_C = 48948.0625f;
constexpr float QSCALE = 0.25f * 1.4426950408889634f * 8.f;
constexpr float BOUND = 80.f;

__device__ __forceinline__ void softmax_step(const float (&s)[32], uint32_t (&p)[16], uint32_t mlo, uint32_t mhi) {
  constexpr int PP = NP / 4;
  int ip = 0, im = PP;
#pragma unroll
  for (int i = 0; i < 16; i++) {
    if (((i + 1) * PP / 16) > (i * PP / 16)) { p[ip] = exp_poly(s[2 * ip], s[2 * ip + 1], mlo, mhi); ip++; }
    else { p[im] = exp_mufu(s[2 * im], s[2 * im + 1]); im++; }
  }
}
constexpr uint64_t VSTEP = ((uint64_t)16 << 32) - 16;
__device__ __forceinline__ void issue_qk(float (&s)[32], const uint32_t (&q)[4], uint64_t dk) {
  wg_qk<NM, 0, NP / 2, 32>(s, q, dk + NP * 2);
  wg_qk<NP, 1, 0, 32>(s, q, dk);
}
__device__ __forceinline__ void issue_pv(float (&o)[12], const uint32_t (&p)[16], uint64_t& dv) {
#pragma unroll
  for (int c = 0; c < 4; c++) { wg_pv_n24<1, 0, 12>(o, p[4 * c], p[4 * c + 1], p[4 * c + 2], p[4 * c + 3], dv); dv += VSTEP; }
}

struct Params {
  const __nv_bfloat16* gate_w;
  const __nv_bfloat16* b_sp;
  const __nv_bfloat16* w_sp;
  const __nv_bfloat16* w_out;
  const __nv_bfloat16* wo;
  __nv_bfloat16* out;
};

__device__ __forceinline__ void store_o_tile(const float (&o)[12], int bi, int bj, int tau, int tid, uint32_t sb) {
  const int half = tau & 1, hh = tau >> 1, w = tid >> 5, g = (tid & 31) >> 2;
  const int r0 = half * 64 + w * 16 + g;
  const float f0 = __fdividef(ldsf(sb + SM_G + r0 * 4), o[4]), f1 = __fdividef(ldsf(sb + SM_G + (r0 + 8) * 4), o[6]);
  uint32_t* dst = reinterpret_cast<uint32_t*>(g_o) + (bi * 8 + bj) * 4096 + (half * 8 + w * 2) * 256 + hh * 64 + (tid & 31);
  dst[0] = pack_bf16(o[0] * f0, o[1] * f0);
  dst[32] = pack_bf16(o[8] * f0, o[9] * f0);
  dst[256] = pack_bf16(o[2] * f1, o[3] * f1);
  dst[288] = pack_bf16(o[10] * f1, o[11] * f1);
}

__global__ void __cluster_dims__(2, 1, 1) __launch_bounds__(NTHREADS, 1)
fused_kernel(const __grid_constant__ CUtensorMap tm_x, const __grid_constant__ CUtensorMap tm_wq,
             const __grid_constant__ CUtensorMap tm_wk, const __grid_constant__ CUtensorMap tm_wv,
             const __grid_constant__ CUtensorMap tm_win, const __grid_constant__ CUtensorMap tm_wsp,
             const __grid_constant__ CUtensorMap tm_wout, const __grid_constant__ CUtensorMap tm_wo, const Params prm) {
  extern __shared__ __align__(1024) uint8_t smem_raw[];
  const uint32_t sb = (uint32_t)__cvta_generic_to_shared(smem_raw);
  const int wg = __shfl_sync(0xffffffffu, (int)(threadIdx.x >> 7), 0);
  const int tid = threadIdx.x & 127;
  const int lane = threadIdx.x & 31;
  const int bi = blockIdx.x >> 3, bj = blockIdx.x & 7, rank = bj & 1;
  auto BAR = [&](int k) { return sb + SM_BAR + 8u * k; };

  if (threadIdx.x == 0) {
    for (int k = 0; k < B_COUNT; k++) {
      uint32_t cnt = 1;
      if (k >= B_XEMPTY && k < B_XEMPTY + 8) cnt = 4;
      if (k >= B_WEMPTY && k < B_WEMPTY + 8) cnt = 3;
      if (k >= B_WEMPTY + 8 && k < B_WEMPTY + 12) cnt = 2;
      if (k >= B_REMPTY && k < B_REMPTY + 3) cnt = 2;
      mbar_init(BAR(k), cnt);
    }
    asm volatile("fence.mbarrier_init.release.cluster;" ::: "memory");
  }
  __syncthreads();
  asm volatile("barrier.cluster.arrive.release.aligned;" ::: "memory");
  asm volatile("barrier.cluster.wait.acquire.aligned;" ::: "memory");

  if (wg == 4) {
    asm volatile("setmaxnreg.dec.sync.aligned.u32 24;");
    const int pw = __shfl_sync(0xffffffffu, tid >> 5, 0);
    if (pw == 0) {
      if (lane == 0) {
        TS(0);
        auto fill_w = [&](int f) {
          const uint32_t slot = sb + SM_RING + (f & 3) * WSLOT, bar = BAR(B_WFULL + f);
          const int k0 = (f & 7) * 64;
          if (f < 8) {
            mbar_expect(bar, 12288 + 2048);
            for (int a = 0; a < 3; a++) tma2d(slot + a * 4096, &tm_win, 688 + 88 * bj + 32 * a, k0, bar);
            tma2d(slot + 12288, rank ? &tm_wv : &tm_wk, 0, k0, bar);
          } else {
            mbar_expect(bar, 12288 + 8192);
            tma2d(slot + 12288, &tm_wq, 64 * bj, k0, bar);
            for (int a = 0; a < 3; a++) tma2d(slot + a * 4096, &tm_win, 88 * bj + 32 * a, k0, bar);
          }
        };
#pragma unroll 1
        for (int c = 0; c < 8; c++) {
          mbar_expect(BAR(B_XFULL + c), 16384);
          tma2d_mc(sb + SM_K + c * 16384 + rank * 8192, &tm_x, c * 64, bi * 128 + rank * 64, BAR(B_XFULL + c));
          if (c < 4) fill_w(c);
        }
#pragma unroll 1
        for (int f = 4; f < 16; f++) {
          mbar_wait(BAR(B_WEMPTY + f - 4), 0);
          fill_w(f);
          if (f == 11) {
            const uint8_t* ws = reinterpret_cast<const uint8_t*>(prm.w_sp) + (size_t)blockIdx.x * 65536;
            for (int a = 0; a < 4; a++) l2_prefetch(ws + a * 16384, 16384);
            l2_prefetch(reinterpret_cast<const uint8_t*>(prm.w_out) + blockIdx.x * 5504, 5504);
            l2_prefetch(reinterpret_cast<const uint8_t*>(prm.wo) + blockIdx.x * 4096, 4096);
          }
        }
        TS(1);
        mbar_wait_cl(BAR(B_XEMPTY + 7), 0);
        mbar_wait(BAR(B_EPOCH), 0);
      }
      __syncwarp();
      const unsigned ep1 = lds32(sb + SM_MISC + 4 * M_EPOCH) + 1;
      wait_ge(&g_zflag[bj * 32 + lane], ep1);
      __syncwarp();
      if (lane == 0) {
        fence_async();
        TS(2);
        int st = 0, ph = 1;
#pragma unroll 1
        for (int n = 0; n < 43; n++) {
          const uint32_t stg = sb + SM_RING + st * RSTAGE, bar = BAR(B_RFULL + st);
          if (n >= 3) mbar_wait_cl(BAR(B_REMPTY + st), ph);
          if (n < 32) {
            mbar_expect(bar, 16384 + 11264);
            tma2d_mc(stg + rank * 8192, &tm_wsp, n * 64, bi * 128 + rank * 64, bar);
            bulk(stg + 16384, reinterpret_cast<const uint8_t*>(g_z2n) + (bj * 32 + n) * 11264, 11264, bar);
          } else {
            const int c = n - 32;
            mbar_expect(bar, 16384 + 8192);
            tma2d(stg + 16384, &tm_wout, 64 * bj, c * 64, bar);
            if (c == 0) { wait_ge(&g_ucnt[bi * 32], ep1 * 8); fence_async(); TS(3); }
            bulk_mc(stg + rank * 8192, reinterpret_cast<const uint8_t*>(g_u) + (bi * 11 + c) * 16384 + rank * 8192, 8192, bar);
          }
          if (++st == 3) { st = 0; ph ^= 1; }
        }
#pragma unroll 1
        for (int n = 0; n < 3; n++) {
          mbar_wait_cl(BAR(B_REMPTY + st), ph);
          if (++st == 3) { st = 0; ph ^= 1; }
        }
        mbar_expect(BAR(B_WOFULL), 65536);
#pragma unroll 1
        for (int c = 0; c < 8; c++) tma2d(sb + SM_RING + c * 8192, &tm_wo, 64 * bj, c * 64, BAR(B_WOFULL));
        TS(4);
        wait_ge(&g_ocnt[bi * 32], ep1 * 24);
        fence_async();
        TS(5);
#pragma unroll 1
        for (int c = 0; c < 8; c++) {
          mbar_expect(BAR(B_OFULL + c), 16384);
          bulk_mc(sb + SM_K + c * 16384 + rank * 8192, reinterpret_cast<const uint8_t*>(g_o) + (bi * 8 + c) * 16384 + rank * 8192, 8192, BAR(B_OFULL + c));
        }
      }
    } else if (pw == 1) {
      unsigned ep = 0;
      if (lane == 0) {
        ep = atomicAdd(&g_ticket, 1u) / NCTA;
        sts32(sb + SM_MISC + 4 * M_EPOCH, ep);
        mbar_arrive(BAR(B_EPOCH));
        wait_ge(&g_kvcnt[0], (ep + 1) * NCTA);
        TS(6);
      }
      __syncwarp();
      float kn2 = fmaxf(__ldcg(&g_kvstat[(4 * lane) * 16]), __ldcg(&g_kvstat[(4 * lane + 2) * 16]));
      float vm = 0.f;
#pragma unroll 4
      for (int p = 0; p < 32; p++) vm = fmaxf(vm, __ldcg(&g_kvstat[(4 * p + 1 + (lane >> 4) * 2) * 16 + (lane & 15)]));
      vm = fmaxf(vm, __shfl_xor_sync(0xffffffffu, vm, 16));
#pragma unroll
      for (int m = 16; m > 0; m >>= 1) kn2 = fmaxf(kn2, __shfl_xor_sync(0xffffffffu, kn2, m));
      const bool vok = __all_sync(0xffffffffu, vm >= 9.5367431640625e-07f && vm <= 1073741824.f);
      if (lane == 0) {
        sts32(sb + SM_MISC + 4 * M_KN2, __float_as_uint(kn2));
        sts32(sb + SM_MISC + 4 * M_VOK, vok ? 1u : 0u);
        mbar_arrive(BAR(B_KSTAT));
        fence_async();
#pragma unroll 1
        for (int c = 0; c < 8; c++) {
          const uint32_t bytes = c == 7 ? 16640 : 16384, hb = bytes / 2, off = c * 16384 + rank * hb;
          mbar_wait_cl(BAR(B_XEMPTY + c), 0);
          mbar_expect(BAR(B_KVFULL + c), bytes);
          bulk_mc(sb + SM_K + off, reinterpret_cast<const uint8_t*>(g_kimg) + off, hb, BAR(B_KVFULL + c));
        }
        TS(7);
        mbar_wait(BAR(B_DEC), 0);
        if (!lds32(sb + SM_MISC + 4 * M_FAST)) {
          for (int c = 0; c < 4; c++) mbar_wait(BAR(B_KVFULL + c), 0);
          mbar_expect(BAR(B_KFB), 65536);
          for (int c = 0; c < 4; c++) bulk(sb + SM_K + c * 16384, reinterpret_cast<const uint8_t*>(g_kbf) + c * 16384, 16384, BAR(B_KFB));
        }
      }
    }
  } else if (wg == 3) {
    asm volatile("setmaxnreg.inc.sync.aligned.u32 120;");
    const int w = tid >> 5, g = lane >> 2, t4 = lane & 3;
    {
      float a0 = 0.f, a1 = 0.f;
#pragma unroll 1
      for (int c = 0; c < 8; c++) {
        mbar_wait(BAR(B_XFULL + c), 0);
#pragma unroll
        for (int v = 0; v < 8; v++) {
          const uint4 xv = lds128(sb + SM_K + c * 16384 + tid * 128 + ((v ^ (tid & 7)) << 4));
          const uint4 gv = __ldg(reinterpret_cast<const uint4*>(prm.gate_w) + c * 8 + v);
          a0 = fmaf(bf_lo(xv.x), bf_lo(gv.x), a0); a1 = fmaf(bf_hi(xv.x), bf_hi(gv.x), a1);
          a0 = fmaf(bf_lo(xv.y), bf_lo(gv.y), a0); a1 = fmaf(bf_hi(xv.y), bf_hi(gv.y), a1);
          a0 = fmaf(bf_lo(xv.z), bf_lo(gv.z), a0); a1 = fmaf(bf_hi(xv.z), bf_hi(gv.z), a1);
          a0 = fmaf(bf_lo(xv.w), bf_lo(gv.w), a0); a1 = fmaf(bf_hi(xv.w), bf_hi(gv.w), a1);
        }
      }
      sts32(sb + SM_G + tid * 4, __float_as_uint(__fdividef(1.f, 1.f + __expf(-(a0 + a1)))));
      fence_async();
      bar_sync(4, 128);
      bar_arrive(5, 512);
    }
    if (tid == 0) TS(8);
    float acc[88];
    {
#pragma unroll
      for (int k = 0; k < 88; k++) acc[k] = 0.f;
      regfence(acc);
#pragma unroll 1
      for (int c = 0; c < 8; c++) {
        mbar_wait(BAR(B_WFULL + 8 + c), 0);
        const uint64_t da = mkdesc(sb + SM_K + c * 16384, 16, 1024, 1);
        const uint64_t db = mkdesc(sb + SM_RING + (c & 3) * WSLOT, 4096, 512, 2);
        wg_fence();
#pragma unroll
        for (int k = 0; k < 4; k++) { wg_ss_n88<0, 88>(acc, da + 2 * k, db + 64 * k); wg_ss_n88<44, 88>(acc, da + 512 + 2 * k, db + 64 * k); }
        wg_commit();
        wg_wait<0>();
        if (tid == 0) { if (c < 4) mbar_arrive(BAR(B_WEMPTY + 8 + c)); mbar_arrive_both(BAR(B_XEMPTY + c)); }
      }
      regfence(acc);
      if (tid == 0) TS(9);
      uint4* z1p = g_z1 + blockIdx.x * 11 * 128 + tid;
#pragma unroll
      for (int q = 0; q < 11; q++) {
        uint4 v;
        v.x = pack_bf16(gelu_tanh(acc[8 * q + 0]), gelu_tanh(acc[8 * q + 1]));
        v.y = pack_bf16(gelu_tanh(acc[8 * q + 2]), gelu_tanh(acc[8 * q + 3]));
        v.z = pack_bf16(gelu_tanh(acc[8 * q + 4]), gelu_tanh(acc[8 * q + 5]));
        v.w = pack_bf16(gelu_tanh(acc[8 * q + 6]), gelu_tanh(acc[8 * q + 7]));
        z1p[q * 128] = v;
      }
    }
    if (tid == 0) TS(10);
    int st = 0, ph = 0;
    {
#pragma unroll
      for (int k = 0; k < 88; k++) acc[k] = 0.f;
      regfence(acc);
#pragma unroll 1
      for (int n = 0; n < 32; n++) {
        mbar_wait(BAR(B_RFULL + st), ph);
        const uint64_t da = mkdesc(sb + SM_RING + st * RSTAGE, 16, 1024, 1);
        const uint64_t db = mkdesc(sb + SM_RING + st * RSTAGE + 16384, 1408, 128, 0);
#pragma unroll
        for (int k = 0; k < 4; k++) {
          wg_fence();
          wg_ss_n88<0, 88>(acc, da + 2 * k, db + 176 * k);
          wg_ss_n88<44, 88>(acc, da + 512 + 2 * k, db + 176 * k);
          wg_commit();
          wg_wait<0>();
        }
        if (tid == 0) mbar_arrive_both(BAR(B_REMPTY + st));
        if (++st == 3) { st = 0; ph ^= 1; }
      }
      regfence(acc);
      if (tid == 0) TS(11);
      float bs[4], og[4];
#pragma unroll
      for (int r = 0; r < 4; r++) {
        const int row = (r >> 1) * 64 + w * 16 + (r & 1) * 8 + g;
        bs[r] = __bfloat162float(prm.b_sp[bi * 128 + row]);
        og[r] = 1.f - ldsf(sb + SM_G + row * 4);
      }
      const uint4* z1p = g_z1 + blockIdx.x * 11 * 128 + tid;
      uint32_t* up = reinterpret_cast<uint32_t*>(g_u) + bi * 11 * 4096 + w * 512 + lane;
#pragma unroll
      for (int q = 0; q < 11; q++) {
        const uint4 zv = z1p[q * 128];
        const uint32_t zz[4] = {zv.x, zv.y, zv.z, zv.w};
#pragma unroll
        for (int e = 0; e < 4; e++) {
          const int k = 8 * q + 2 * e, hf = k / 44, c8 = (k % 44) / 4, r8 = ((k % 44) >> 1) & 1, r = hf * 2 + r8;
          const int cb = 11 * bj + c8;
          uint32_t v = pack_bf16(bf_lo(zz[e]) * (acc[k] + bs[r]) * og[r], bf_hi(zz[e]) * (acc[k + 1] + bs[r]) * og[r]);
          if (c8 >= 9 && bj == 7) v = 0;
          up[(cb >> 3) * 4096 + (hf * 8 + r8) * 256 + (cb & 7) * 32] = v;
        }
      }
      fence_async();
      bar_sync(4, 128);
      if (tid == 0) red_release(&g_ucnt[bi * 32]);
    }
    if (tid == 0) TS(12);
    {
      float oc[64];
#pragma unroll
      for (int k = 0; k < 64; k++) oc[k] = 0.f;
      regfence(oc);
#pragma unroll 1
      for (int n = 0; n < 11; n++) {
        mbar_wait(BAR(B_RFULL + st), ph);
        const uint64_t da = mkdesc(sb + SM_RING + st * RSTAGE, 128, 1024, 0);
        const uint64_t db = mkdesc(sb + SM_RING + st * RSTAGE + 16384, 8192, 1024, 1);
#pragma unroll
        for (int k = 0; k < 4; k++) {
          wg_fence();
          wg_ss_n64<0, 64>(oc, da + 16 * k, db + 128 * k);
          wg_ss_n64<32, 64>(oc, da + 512 + 16 * k, db + 128 * k);
          wg_commit();
          wg_wait<0>();
        }
        if (tid == 0) mbar_arrive_both(BAR(B_REMPTY + st));
        if (++st == 3) { st = 0; ph ^= 1; }
      }
      if (tid == 0) TS(13);
      mbar_wait(BAR(B_WOFULL), 0);
#pragma unroll 1
      for (int c = 0; c < 8; c++) {
        mbar_wait(BAR(B_OFULL + c), 0);
        const uint64_t da = mkdesc(sb + SM_K + c * 16384, 128, 1024, 0);
        const uint64_t db = mkdesc(sb + SM_RING + c * 8192, 8192, 1024, 1);
        wg_fence();
#pragma unroll
        for (int k = 0; k < 4; k++) { wg_ss_n64<0, 64>(oc, da + 16 * k, db + 128 * k); wg_ss_n64<32, 64>(oc, da + 512 + 16 * k, db + 128 * k); }
        wg_commit();
      }
      wg_wait<0>();
      regfence(oc);
      if (tid == 0) TS(14);
      uint32_t* op = reinterpret_cast<uint32_t*>(prm.out) + (bi * 128 + w * 16 + g) * 256 + bj * 32 + t4;
#pragma unroll
      for (int k = 0; k < 64; k += 2) {
        const int hf = k / 32, c8 = (k % 32) / 4, r8 = (k >> 1) & 1;
        op[(hf * 64 + r8 * 8) * 256 + c8 * 4] = pack_bf16(oc[k], oc[k + 1]);
      }
      if (tid == 0) TS(15);
    }
  } else {
    asm volatile("setmaxnreg.inc.sync.aligned.u32 112;");
    const int w = tid >> 5, g = lane >> 2, t4 = lane & 3;
    if (wg < 2) {
      float acc[44];
#pragma unroll
      for (int k = 0; k < 44; k++) acc[k] = 0.f;
      regfence(acc);
#pragma unroll 1
      for (int c = 0; c < 8; c++) {
        mbar_wait(BAR(B_XFULL + c), 0);
        mbar_wait(BAR(B_WFULL + c), 0);
        const uint64_t da = mkdesc(sb + SM_K + c * 16384 + wg * 8192, 16, 1024, 1);
        const uint64_t db = mkdesc(sb + SM_RING + (c & 3) * WSLOT, 4096, 512, 2);
        wg_fence();
#pragma unroll
        for (int k = 0; k < 4; k++) wg_ss_n88<0, 44>(acc, da + 2 * k, db + 64 * k);
        wg_commit();
        wg_wait<0>();
        if (tid == 0) mbar_arrive(BAR(B_WEMPTY + c));
      }
      regfence(acc);
      if (tid == 0) TS(16 + wg);
      const bool last = bj == 7;
      float s0 = 0.f, s1 = 0.f;
#pragma unroll
      for (int k = 0; k < 44; k++) {
        acc[k] = gelu_tanh(acc[k]);
        if (k & 2) s1 += acc[k]; else s0 += acc[k];
      }
      s0 += __shfl_xor_sync(0xffffffffu, s0, 1); s0 += __shfl_xor_sync(0xffffffffu, s0, 2);
      s1 += __shfl_xor_sync(0xffffffffu, s1, 1); s1 += __shfl_xor_sync(0xffffffffu, s1, 2);
      const float inv_n = last ? (1.f / 72.f) : (1.f / 88.f);
      const float m0 = s0 * inv_n, m1 = s1 * inv_n;
      float v0 = 0.f, v1 = 0.f;
#pragma unroll
      for (int k = 0; k < 44; k++) {
        float d = acc[k] - ((k & 2) ? m1 : m0);
        if (k >= 36 && last) d = 0.f;
        if (k & 2) v1 = fmaf(d, d, v1); else v0 = fmaf(d, d, v0);
      }
      v0 += __shfl_xor_sync(0xffffffffu, v0, 1); v0 += __shfl_xor_sync(0xffffffffu, v0, 2);
      v1 += __shfl_xor_sync(0xffffffffu, v1, 1); v1 += __shfl_xor_sync(0xffffffffu, v1, 2);
      const int r0 = wg * 64 + w * 16 + g;
      if (t4 == 0) {
        g_lnstat[(bi * 8 + bj) * 128 + r0] = make_float2(m0, v0);
        g_lnstat[(bi * 8 + bj) * 128 + r0 + 8] = make_float2(m1, v1);
      }
      bar_sync(1 + wg, 128);
      mbar_wait(BAR(B_EPOCH), 0);
      const unsigned ep1 = lds32(sb + SM_MISC + 4 * M_EPOCH) + 1;
      if (tid == 0) {
        red_release(&g_statcnt[(bi * 2 + wg) * 32]);
        TS(18 + wg);
        wait_ge(&g_statcnt[(bi * 2 + wg) * 32], ep1 * 8);
      }
      bar_sync(1 + wg, 128);
      float mean[2], rstd[2];
#pragma unroll
      for (int r = 0; r < 2; r++) {
        const float2 a = __ldcg(&g_lnstat[(bi * 8 + 2 * t4) * 128 + r0 + 8 * r]);
        const float2 b = __ldcg(&g_lnstat[(bi * 8 + 2 * t4 + 1) * 128 + r0 + 8 * r]);
        const float nb = t4 == 3 ? 72.f : 88.f;
        float sm = fmaf(a.x, 88.f, b.x * nb);
        sm += __shfl_xor_sync(0xffffffffu, sm, 1); sm += __shfl_xor_sync(0xffffffffu, sm, 2);
        const float mu = sm * (1.f / 688.f);
        const float da = a.x - mu, db = b.x - mu;
        float m2 = a.y + b.y + 88.f * da * da + nb * db * db;
        m2 += __shfl_xor_sync(0xffffffffu, m2, 1); m2 += __shfl_xor_sync(0xffffffffu, m2, 2);
        mean[r] = mu;
        rstd[r] = rsqrtf(fmaf(m2, 1.f / 688.f, 1e-5f));
      }
      uint32_t* zp = reinterpret_cast<uint32_t*>(g_z2n) + (bj * 32 + bi * 2 + wg) * 2816 + w * 704 + lane;
#pragma unroll
      for (int k = 0; k < 44; k += 2) {
        const int r = (k >> 1) & 1, c8 = k >> 2;
        uint32_t v = pack_bf16((acc[k] - mean[r]) * rstd[r], (acc[k + 1] - mean[r]) * rstd[r]);
        if (c8 >= 9 && last) v = 0;
        zp[r * 352 + c8 * 32] = v;
      }
      fence_async();
      bar_sync(1 + wg, 128);
      if (tid == 0) { st_release(&g_zflag[bj * 32 + bi * 2 + wg], ep1); TS(20 + wg); }
    } else {
      const int pair = bi * 4 + (bj >> 1);
      {
        float kv[16];
#pragma unroll
        for (int k = 0; k < 16; k++) kv[k] = 0.f;
        regfence(kv);
#pragma unroll 1
        for (int c = 0; c < 8; c++) {
          mbar_wait(BAR(B_XFULL + c), 0);
          mbar_wait(BAR(B_WFULL + c), 0);
          const uint64_t da = mkdesc(sb + SM_RING + (c & 3) * WSLOT + 12288, 0, 256, 3);
          const uint64_t db = mkdesc(sb + SM_K + c * 16384 + (bj >> 1) * 4096, 16, 1024, 1);
          wg_fence();
#pragma unroll
          for (int k = 0; k < 4; k++) wg_ss_n32t<0, 16>(kv, da + 32 * k, db + 2 * k);
          wg_commit();
          wg_wait<0>();
          if (tid == 0) mbar_arrive(BAR(B_WEMPTY + c));
        }
        regfence(kv);
        if (tid == 0) TS(22);
        const uint32_t sT = sb + SM_Q, sH = sb + SM_Q + 4096;
        if (w == 0) {
#pragma unroll
          for (int k = 0; k < 16; k++) {
            const int tok = (k >> 2) * 8 + 2 * t4 + (k & 1), d = g + ((k >> 1) & 1) * 8;
            sts32(sT + (tok * 17 + d) * 4, __float_as_uint(__bfloat162float(__float2bfloat16_rn(kv[k]))));
          }
        }
        bar_sync(3, 128);
        const int tok = (tid & 63) >> 1, hf = tid & 1;
        const uint32_t inner = (pair & 7) * 16;
        if (rank == 0) {
          if (tid < 48) {
            const int d = tid & 15, sg = tid >> 4, j0 = sg == 0 ? 0 : (sg == 1 ? 10 : 22), j1 = sg == 0 ? 10 : (sg == 1 ? 22 : 32);
            float run = 0.f;
#pragma unroll 1
            for (int jj = j0; jj < j1; jj++) {
              const float kx = ldsf(sT + (jj * 17 + d) * 4);
              __half hv;
              if (pair < NP) { hv = __float2half_rn(fmaf(kx, 16.f, -run)); run += __half2float(hv); }
              else hv = __float2half_rn(kx * 0.125f);
              sts16(sH + (jj * 16 + d) * 2, __half_as_ushort(hv));
            }
          } else if (w == 2) {
            float n2 = 0.f;
#pragma unroll
            for (int d = 0; d < 16; d++) { const float kx = ldsf(sT + (lane * 17 + d) * 4); n2 = fmaf(kx, kx, n2); }
            if (!(n2 <= 3.0e38f)) n2 = 3.0e38f;
#pragma unroll
            for (int m = 16; m > 0; m >>= 1) n2 = fmaxf(n2, __shfl_xor_sync(0xffffffffu, n2, m));
            if (lane == 0) g_kvstat[blockIdx.x * 16] = n2;
          }
          bar_sync(3, 128);
          const uint32_t off = tok * 2048 + (pair >> 3) * 256 + hf * 128 + inner;
          if (tid < 64) g_kimg[off >> 4] = lds128(sH + tok * 32 + hf * 16);
          else {
            float f[8];
#pragma unroll
            for (int e = 0; e < 8; e++) f[e] = ldsf(sT + (tok * 17 + hf * 8 + e) * 4);
            g_kbf[off >> 4] = make_uint4(pack_bf16(f[0], f[1]), pack_bf16(f[2], f[3]), pack_bf16(f[4], f[5]), pack_bf16(f[6], f[7]));
          }
        } else {
          if (tid < 64) {
            float f[8];
#pragma unroll
            for (int e = 0; e < 8; e++) f[e] = ldsf(sT + (tok * 17 + hf * 8 + e) * 4);
            const uint32_t sbo = 256 * (4 * tok + (pair >> 4) + 1);
            const uint32_t off = (hf ? SM_ONES + sbo : SM_ONES - sbo) + ((pair >> 3) & 1) * 128 + inner;
            g_kimg[off >> 4] = make_uint4(pack_bf16(f[0], f[1]), pack_bf16(f[2], f[3]), pack_bf16(f[4], f[5]), pack_bf16(f[6], f[7]));
          } else if (tid < 80) {
            float vm = 0.f;
#pragma unroll 8
            for (int jj = 0; jj < 32; jj++) { float a = fabsf(ldsf(sT + (jj * 17 + tid - 64) * 4)); if (!(a <= 3.0e38f)) a = 3.0e38f; vm = fmaxf(vm, a); }
            g_kvstat[blockIdx.x * 16 + tid - 64] = vm;
          } else if (tid >= 96 && tid < 112 && pair == 0) {
            g_kimg[(SM_ONES >> 4) + tid - 96] = make_uint4(0x3F803F80u, 0x3F803F80u, 0x3F803F80u, 0x3F803F80u);
          }
        }
        fence_async();
        bar_sync(3, 128);
        if (tid == 0) { red_release(&g_kvcnt[0]); TS(23); }
      }
      float qa[64];
#pragma unroll
      for (int k = 0; k < 64; k++) qa[k] = 0.f;
      regfence(qa);
#pragma unroll 1
      for (int c = 0; c < 8; c++) {
        mbar_wait(BAR(B_WFULL + 8 + c), 0);
        const uint64_t da = mkdesc(sb + SM_K + c * 16384, 16, 1024, 1);
        const uint64_t db = mkdesc(sb + SM_RING + (c & 3) * WSLOT + 12288, 8192, 1024, 1);
        wg_fence();
#pragma unroll
        for (int k = 0; k < 4; k++) { wg_ss_n64<0, 64>(qa, da + 2 * k, db + 128 * k); wg_ss_n64<32, 64>(qa, da + 512 + 2 * k, db + 128 * k); }
        wg_commit();
        wg_wait<0>();
        if (tid == 0) { if (c < 4) mbar_arrive(BAR(B_WEMPTY + 8 + c)); mbar_arrive_both(BAR(B_XEMPTY + c)); }
      }
      regfence(qa);
      if (tid == 0) TS(24);
      uint32_t qb[32];
      float n2 = 0.f;
#pragma unroll
      for (int k = 0; k < 32; k++) qb[k] = pack_bf16(qa[2 * k], qa[2 * k + 1]);
#pragma unroll
      for (int k = 0; k < 16; k++) {
        const uint32_t a = qb[4 * (k >> 1) + (k & 1)], b = qb[4 * (k >> 1) + (k & 1) + 2];
        float s = bf_lo(a) * bf_lo(a);
        s = fmaf(bf_hi(a), bf_hi(a), s); s = fmaf(bf_lo(b), bf_lo(b), s); s = fmaf(bf_hi(b), bf_hi(b), s);
        s += __shfl_xor_sync(0xffffffffu, s, 1); s += __shfl_xor_sync(0xffffffffu, s, 2);
        if (!(s <= 3.0e38f)) s = 3.0e38f;
        n2 = fmaxf(n2, s);
      }
#pragma unroll
      for (int m = 16; m > 2; m >>= 1) n2 = fmaxf(n2, __shfl_xor_sync(0xffffffffu, n2, m));
      if (lane == 0) sts32(sb + SM_MISC + 4 * (M_RED + w), __float_as_uint(n2));
      mbar_wait(BAR(B_KSTAT), 0);
      bar_sync(3, 128);
      const float qn2 = fmaxf(fmaxf(ldsf(sb + SM_MISC + 4 * M_RED), ldsf(sb + SM_MISC + 4 * (M_RED + 1))),
                              fmaxf(ldsf(sb + SM_MISC + 4 * (M_RED + 2)), ldsf(sb + SM_MISC + 4 * (M_RED + 3))));
      const float kn2 = ldsf(sb + SM_MISC + 4 * M_KN2);
      constexpr float SC = QSCALE * 0.125f;
      const bool fast = lds32(sb + SM_MISC + 4 * M_VOK) && qn2 <= 4.0e8f && kn2 <= 4.0e6f && qn2 * kn2 * (SC * SC) <= BOUND * BOUND;
#pragma unroll
      for (int tq = 0; tq < 8; tq++) {
        uint32_t r[4];
#pragma unroll
        for (int e = 0; e < 4; e++) {
          const uint32_t v = qb[(tq & 1) * 16 + (tq >> 1) * 4 + e];
          r[e] = fast ? pack_f16(bf_lo(v) * QSCALE, bf_hi(v) * QSCALE) : v;
        }
        sts128(sb + SM_Q + tq * 2048 + tid * 16, r[0], r[1], r[2], r[3]);
      }
      if (tid == 0) { sts32(sb + SM_MISC + 4 * M_FAST, fast ? 1u : 0u); mbar_arrive(BAR(B_DEC)); }
    }
    bar_sync(5, 512);
    if (tid == 0) TS(25 + wg);
#pragma unroll 1
    for (int c = 0; c < 8; c++) mbar_wait(BAR(B_KVFULL + c), 0);
    if (tid == 0) TS(28 + wg);
    const uint64_t dk0 = mkdesc(sb + SM_K, 128, 256, 0);
    const uint64_t dv0 = mkdesc(sb + SM_ONES - 256, 128, 256, 0);
    float o[12], s[32];
    uint32_t q[4], p0[16], p1[16];
    if (lds32(sb + SM_MISC + 4 * M_FAST)) {
      uint32_t mlo = 0x007F007Fu, mhi = 0xFF80FF80u;
      asm volatile("" : "+r"(mlo), "+r"(mhi));
      uint64_t dk = dk0, dv = dv0;
#define STEP(PIN, POUT) { wg_fence(); issue_qk(s, q, dk); dk += 128; wg_commit(); issue_pv(o, PIN, dv); wg_commit(); \
                          wg_wait<1>(); regfence(s); softmax_step(s, POUT, mlo, mhi); wg_wait<0>(); }
#pragma unroll 1
      for (int sg = wg * 8; sg < wg * 8 + 8; sg++) {
        const int tau = sg / 3, seg = sg - tau * 3;
        int n2 = seg == 1 ? 6 : 5;
#pragma unroll
        for (int k = 0; k < NP / 2; k++) s[k] = MAGIC_C;
        if (sg == wg * 8 || seg == 0) {
          const int j0 = seg == 0 ? 0 : (seg == 1 ? 10 : 22);
          dk = dk0 + 128 * j0;
          dv = dv0 + VSTEP * (4 * j0);
          const uint4 qv = lds128(sb + SM_Q + tau * 2048 + tid * 16);
          q[0] = qv.x; q[1] = qv.y; q[2] = qv.z; q[3] = qv.w;
#pragma unroll
          for (int k = 0; k < 12; k++) o[k] = 0.f;
          regfence(o); regfence(s);
          wg_fence(); issue_qk(s, q, dk); dk += 128; wg_commit();
          wg_wait<0>(); regfence(s);
          softmax_step(s, p0, mlo, mhi);
          STEP(p0, p1);
          n2--;
        }
        regfence(s);
#pragma unroll 1
        for (; n2 > 0; n2--) { STEP(p1, p0); STEP(p0, p1); }
        if (sg == wg * 8 + 7 || seg == 2) {
          wg_fence(); issue_pv(o, p1, dv); wg_commit();
          wg_wait<0>(); regfence(o);
          if (sg == 8 || sg == 17) {
            float4* pp = g_part + (blockIdx.x * 2 + (wg - 1)) * 384 + tid;
            pp[0] = make_float4(o[0], o[1], o[2], o[3]); pp[128] = make_float4(o[4], o[5], o[6], o[7]); pp[256] = make_float4(o[8], o[9], o[10], o[11]);
            __threadfence_block();
            bar_arrive(5 + wg, 256);
          } else {
            if (sg == 7 || sg == 15) {
              bar_sync(6 + wg, 256);
              const float4* pp = g_part + (blockIdx.x * 2 + wg) * 384 + tid;
              const float4 a = pp[0], b = pp[128], c = pp[256];
              o[0] += a.x; o[1] += a.y; o[2] += a.z; o[3] += a.w; o[4] += b.x; o[6] += b.z; o[8] += c.x; o[9] += c.y; o[10] += c.z; o[11] += c.w;
            }
            store_o_tile(o, bi, bj, tau, tid, sb);
          }
        }
      }
#undef STEP
    } else {
      mbar_wait(BAR(B_KFB), 0);
      constexpr float SC = 0.25f * 1.4426950408889634f;
#pragma unroll 1
      for (int tau = wg * 3; tau < wg * 3 + 3 && tau < 8; tau++) {
        const uint4 qv = lds128(sb + SM_Q + tau * 2048 + tid * 16);
        float m0 = -INFINITY, m1 = -INFINITY;
#pragma unroll
        for (int k = 0; k < 12; k++) o[k] = 0.f;
        uint64_t dv = dv0;
#pragma unroll 1
        for (int j = 0; j < 32; j++) {
          regfence(s);
          wg_fence(); wg_qkb_n64<0, 0, 32>(s, qv.x, qv.y, qv.z, qv.w, dk0 + 128 * j); wg_commit();
          wg_wait<0>(); regfence(s);
          float x0 = m0, x1 = m1;
#pragma unroll
          for (int k = 0; k < 32; k++) { s[k] *= SC; if (k & 2) x1 = fmaxf(x1, s[k]); else x0 = fmaxf(x0, s[k]); }
          x0 = fmaxf(x0, __shfl_xor_sync(0xffffffffu, x0, 1)); x0 = fmaxf(x0, __shfl_xor_sync(0xffffffffu, x0, 2));
          x1 = fmaxf(x1, __shfl_xor_sync(0xffffffffu, x1, 1)); x1 = fmaxf(x1, __shfl_xor_sync(0xffffffffu, x1, 2));
          const float c0 = ex2(m0 - x0), c1 = ex2(m1 - x1);
          m0 = x0; m1 = x1;
#pragma unroll
          for (int k = 0; k < 12; k++) o[k] *= (k & 2) ? c1 : c0;
#pragma unroll
          for (int k = 0; k < 16; k++) { const float m = (k & 1) ? m1 : m0; p0[k] = exp_mufu(s[2 * k] - m, s[2 * k + 1] - m); }
          regfence(o);
          wg_fence(); issue_pv(o, p0, dv); wg_commit();
          wg_wait<0>(); regfence(o);
        }
        store_o_tile(o, bi, bj, tau, tid, sb);
      }
    }
    fence_async();
    bar_sync(1 + wg, 128);
    if (tid == 0) { red_release(&g_ocnt[bi * 32]); TS(31 + wg); }
  }
  __syncwarp();
  asm volatile("barrier.cluster.arrive.relaxed;" ::: "memory");
  asm volatile("barrier.cluster.wait;" ::: "memory");
}

typedef CUresult (*EncodeFn)(CUtensorMap*, CUtensorMapDataType, cuuint32_t, void*, const cuuint64_t*, const cuuint64_t*,
                             const cuuint32_t*, const cuuint32_t*, CUtensorMapInterleave, CUtensorMapSwizzle,
                             CUtensorMapL2promotion, CUtensorMapFloatOOBfill);

void make_map(EncodeFn enc, CUtensorMap* tm, const void* base, uint64_t cols, uint64_t rows, uint32_t bc, uint32_t br, CUtensorMapSwizzle sw) {
  cuuint64_t gd[2] = {cols, rows};
  cuuint64_t gs[1] = {cols * 2};
  cuuint32_t bd[2] = {bc, br};
  cuuint32_t es[2] = {1, 1};
  enc(tm, CU_TENSOR_MAP_DATA_TYPE_BFLOAT16, 2, const_cast<void*>(base), gd, gs, bd, es, CU_TENSOR_MAP_INTERLEAVE_NONE, sw,
      CU_TENSOR_MAP_L2_PROMOTION_L2_128B, CU_TENSOR_MAP_FLOAT_OOB_FILL_NONE);
}

}

extern "C" void kernel_launch(void* const* d_in, const int* in_sizes, int n_in, void* d_out, int out_size) {
  (void)in_sizes; (void)n_in; (void)out_size;
  static EncodeFn enc = nullptr;
  if (!enc) {
    void* fn = nullptr;
    cudaDriverEntryPointQueryResult qr;
    cudaGetDriverEntryPoint("cuTensorMapEncodeTiled", &fn, cudaEnableDefault, &qr);
    enc = (EncodeFn)fn;
    cudaFuncSetAttribute(fused_kernel, cudaFuncAttributeMaxDynamicSharedMemorySize, SMEM_BYTES);
  }
  CUtensorMap tx, tq, tk, tv, tin, tsp, tout, to;
  make_map(enc, &tx, d_in[0], 512, 2048, 64, 64, CU_TENSOR_MAP_SWIZZLE_128B);
  make_map(enc, &tq, d_in[1], 512, 512, 64, 64, CU_TENSOR_MAP_SWIZZLE_128B);
  make_map(enc, &tk, d_in[2], 16, 512, 16, 64, CU_TENSOR_MAP_SWIZZLE_32B);
  make_map(enc, &tv, d_in[3], 16, 512, 16, 64, CU_TENSOR_MAP_SWIZZLE_32B);
  make_map(enc, &to, d_in[4], 512, 512, 64, 64, CU_TENSOR_MAP_SWIZZLE_128B);
  make_map(enc, &tin, d_in[6], 1376, 512, 32, 64, CU_TENSOR_MAP_SWIZZLE_64B);
  make_map(enc, &tsp, d_in[7], 2048, 2048, 64, 64, CU_TENSOR_MAP_SWIZZLE_128B);
  make_map(enc, &tout, d_in[9], 512, 688, 64, 64, CU_TENSOR_MAP_SWIZZLE_128B);
  Params prm;
  prm.gate_w = (const __nv_bfloat16*)d_in[10];
  prm.b_sp = (const __nv_bfloat16*)d_in[8];
  prm.w_sp = (const __nv_bfloat16*)d_in[7];
  prm.w_out = (const __nv_bfloat16*)d_in[9];
  prm.wo = (const __nv_bfloat16*)d_in[4];
  prm.out = (__nv_bfloat16*)d_out;
  fused_kernel<<<NCTA, NTHREADS, SMEM_BYTES>>>(tx, tq, tk, tv, tin, tsp, tout, to, prm);
}
```

```cpp
#include <cuda_runtime.h>
#include <cuda.h>
#include <cuda_bf16.h>
#include <cuda_fp16.h>
#include <stdint.h>

namespace {

constexpr int NCTA = 128;
constexpr int NTHREADS = 640;
constexpr int NP = 40;
constexpr int NM = 64 - NP;
constexpr int SPIN_LIMIT = 1 << 18;

constexpr uint32_t SM_K = 0;
constexpr uint32_t SM_ONES = 98304;
constexpr uint32_t KV_BYTES = 131328;
constexpr uint32_t SM_BAR = 131328;
constexpr uint32_t SM_RING = 132096;
constexpr uint32_t RSTAGE = 27648;
constexpr uint32_t WSLOT = 20480;
constexpr uint32_t SM_Q = 215040;
constexpr uint32_t SM_G = 231424;
constexpr uint32_t SM_MISC = 231936;
constexpr uint32_t SMEM_BYTES = 232448;

constexpr int B_XFULL = 0, B_XEMPTY = 8, B_WFULL = 16, B_WEMPTY = 32, B_KVFULL = 44, B_OFULL = 52, B_RFULL = 60,
              B_REMPTY = 63, B_KFB = 66, B_KSTAT = 67, B_DEC = 68, B_WOFULL = 69, B_EPOCH = 70, B_COUNT = 71;
constexpr int M_EPOCH = 0, M_KN2 = 1, M_VOK = 2, M_FAST = 3, M_RED = 4;

__device__ uint4 g_kimg[KV_BYTES / 16];
__device__ uint4 g_kbf[65536 / 16];
__device__ float g_kvstat[NCTA * 16];
__device__ float2 g_lnstat[16 * 8 * 128];
__device__ uint4 g_z2n[8 * 32 * 11264 / 16];
__device__ uint4 g_z1[NCTA * 11 * 128];
__device__ uint4 g_u[16 * 11 * 1024];
__device__ uint4 g_o[16 * 8 * 1024];
__device__ float4 g_part[NCTA * 2 * 3 * 128];
__device__ unsigned g_ticket;
__device__ unsigned g_kvcnt[32];
__device__ unsigned g_statcnt[32 * 32];
__device__ unsigned g_zflag[8 * 32];
__device__ unsigned g_ucnt[16 * 32];
__device__ unsigned g_ocnt[16 * 32];
#define TS(k) do { } while (0)

__device__ __forceinline__ void mbar_init(uint32_t a, uint32_t c) { asm volatile("mbarrier.init.shared::cta.b64 [%0], %1;" ::"r"(a), "r"(c) : "memory"); }
__device__ __forceinline__ void mbar_expect(uint32_t a, uint32_t b) { asm volatile("mbarrier.arrive.expect_tx.shared::cta.b64 _, [%0], %1;" ::"r"(a), "r"(b) : "memory"); }
__device__ __forceinline__ void mbar_arrive(uint32_t a) { asm volatile("mbarrier.arrive.shared::cta.b64 _, [%0];" ::"r"(a) : "memory"); }
__device__ __forceinline__ void mbar_arrive_both(uint32_t a) {
  asm volatile("{\n.reg .b32 ra;\nmapa.shared::cluster.u32 ra, %0, 0;\nmbarrier.arrive.shared::cluster.b64 _, [ra];\n"
               "mapa.shared::cluster.u32 ra, %0, 1;\nmbarrier.arrive.shared::cluster.b64 _, [ra];\n}" ::"r"(a) : "memory");
}
__device__ __forceinline__ void mbar_wait(uint32_t a, uint32_t ph) {
  uint32_t ok;
#pragma unroll 1
  for (int n = 0; n < SPIN_LIMIT; n++) {
    asm volatile("{\n.reg .pred p;\nmbarrier.try_wait.parity.shared::cta.b64 p, [%1], %2;\nselp.u32 %0, 1, 0, p;\n}" : "=r"(ok) : "r"(a), "r"(ph) : "memory");
    if (ok) break;
  }
}
__device__ __forceinline__ void tma2d(uint32_t dst, const CUtensorMap* tm, int c0, int c1, uint32_t bar) {
  asm volatile("cp.async.bulk.tensor.2d.shared::cluster.global.mbarrier::complete_tx::bytes [%0], [%1, {%3, %4}], [%2];"
               ::"r"(dst), "l"(tm), "r"(bar), "r"(c0), "r"(c1) : "memory");
}
__device__ __forceinline__ void tma2d_mc(uint32_t dst, const CUtensorMap* tm, int c0, int c1, uint32_t bar) {
  asm volatile("cp.async.bulk.tensor.2d.shared::cluster.global.mbarrier::complete_tx::bytes.multicast::cluster [%0], [%1, {%3, %4}], [%2], %5;"
               ::"r"(dst), "l"(tm), "r"(bar), "r"(c0), "r"(c1), "h"((uint16_t)3) : "memory");
}
__device__ __forceinline__ void bulk(uint32_t dst, const void* src, uint32_t bytes, uint32_t bar) {
  asm volatile("cp.async.bulk.shared::cluster.global.mbarrier::complete_tx::bytes [%0], [%1], %2, [%3];"
               ::"r"(dst), "l"(src), "r"(bytes), "r"(bar) : "memory");
}
__device__ __forceinline__ void bulk_mc(uint32_t dst, const void* src, uint32_t bytes, uint32_t bar) {
  asm volatile("cp.async.bulk.shared::cluster.global.mbarrier::complete_tx::bytes.multicast::cluster [%0], [%1], %2, [%3], %4;"
               ::"r"(dst), "l"(src), "r"(bytes), "r"(bar), "h"((uint16_t)3) : "memory");
}
__device__ __forceinline__ void l2_prefetch(const void* src, uint32_t bytes) { asm volatile("cp.async.bulk.prefetch.L2.global [%0], %1;" ::"l"(src), "r"(bytes) : "memory"); }
__device__ __forceinline__ void fence_async() { asm volatile("fence.proxy.async.global;" ::: "memory"); }
__device__ __forceinline__ void fence_async_smem() { asm volatile("fence.proxy.async.shared::cta;" ::: "memory"); }
__device__ __forceinline__ void bar_sync(int id, int n) { asm volatile("bar.sync %0, %1;" ::"r"(id), "r"(n) : "memory"); }
__device__ __forceinline__ void bar_arrive(int id, int n) { asm volatile("bar.arrive %0, %1;" ::"r"(id), "r"(n) : "memory"); }
__device__ __forceinline__ void red_release(unsigned* p) { asm volatile("red.release.gpu.global.add.u32 [%0], 1;" ::"l"(p) : "memory"); }
__device__ __forceinline__ void st_release(unsigned* p, unsigned v) { asm volatile("st.release.gpu.global.u32 [%0], %1;" ::"l"(p), "r"(v) : "memory"); }
__device__ __forceinline__ unsigned ld_acquire(const unsigned* p) { unsigned v; asm volatile("ld.acquire.gpu.global.u32 %0, [%1];" : "=r"(v) : "l"(p) : "memory"); return v; }
__device__ __forceinline__ void wait_ge(const unsigned* p, unsigned target) {
#pragma unroll 1
  for (int n = 0; n < SPIN_LIMIT; n++) {
    if ((int)(ld_acquire(p) - target) >= 0) break;
    __nanosleep(20);
  }
}
__device__ __forceinline__ void wg_fence() { asm volatile("wgmma.fence.sync.aligned;" ::: "memory"); }
__device__ __forceinline__ void wg_commit() { asm volatile("wgmma.commit_group.sync.aligned;" ::: "memory"); }
template <int N> __device__ __forceinline__ void wg_wait() { asm volatile("wgmma.wait_group.sync.aligned %0;" ::"n"(N) : "memory"); }
template <int n> __device__ __forceinline__ void regfence(float (&d)[n]) {
#pragma unroll
  for (int i = 0; i < n; i++) asm volatile("" : "+f"(d[i])::"memory");
}
__device__ __forceinline__ uint64_t mkdesc(uint32_t addr, uint32_t lbo, uint32_t sbo, int swz) {
  return (uint64_t)((addr & 0x3FFFF) >> 4) | ((uint64_t)(lbo >> 4) << 16) | ((uint64_t)(sbo >> 4) << 32) | ((uint64_t)swz << 62);
}
__device__ __forceinline__ uint32_t pack_bf16(float lo, float hi) { uint32_t r; asm("cvt.rn.bf16x2.f32 %0, %1, %2;" : "=r"(r) : "f"(hi), "f"(lo)); return r; }
__device__ __forceinline__ uint32_t pack_f16(float lo, float hi) { uint32_t r; asm("cvt.rn.f16x2.f32 %0, %1, %2;" : "=r"(r) : "f"(hi), "f"(lo)); return r; }
__device__ __forceinline__ float bf_lo(uint32_t v) { return __uint_as_float(v << 16); }
__device__ __forceinline__ float bf_hi(uint32_t v) { return __uint_as_float(v & 0xFFFF0000u); }
__device__ __forceinline__ float ex2(float x) { float r; asm("ex2.approx.ftz.f32 %0, %1;" : "=f"(r) : "f"(x)); return r; }
__device__ __forceinline__ float gelu_tanh(float x) {
  float u = x * fmaf(x * x, 0.0356774081f, 0.7978845608f), t;
  asm("tanh.approx.f32 %0, %1;" : "=f"(t) : "f"(u));
  float h = 0.5f * x;
  return fmaf(h, t, h);
}
__device__ __forceinline__ void sts32(uint32_t a, uint32_t v) { asm volatile("st.shared.u32 [%0], %1;" ::"r"(a), "r"(v) : "memory"); }
__device__ __forceinline__ void sts16(uint32_t a, uint16_t v) { asm volatile("st.shared.u16 [%0], %1;" ::"r"(a), "h"(v) : "memory"); }
__device__ __forceinline__ void sts128(uint32_t a, uint32_t x, uint32_t y, uint32_t z, uint32_t w) { asm volatile("st.shared.v4.u32 [%0], {%1,%2,%3,%4};" ::"r"(a), "r"(x), "r"(y), "r"(z), "r"(w) : "memory"); }
__device__ __forceinline__ uint32_t lds32(uint32_t a) { uint32_t v; asm volatile("ld.shared.u32 %0, [%1];" : "=r"(v) : "r"(a) : "memory"); return v; }
__device__ __forceinline__ float ldsf(uint32_t a) { return __uint_as_float(lds32(a)); }
__device__ __forceinline__ uint4 lds128(uint32_t a) { uint4 v; asm volatile("ld.shared.v4.u32 {%0,%1,%2,%3}, [%4];" : "=r"(v.x), "=r"(v.y), "=r"(v.z), "=r"(v.w) : "r"(a) : "memory"); return v; }

template<int OFF, int TOT> __device__ __forceinline__ void wg_ss_n88(float (&d)[TOT], uint64_t da, uint64_t db) {
  asm volatile("wgmma.mma_async.sync.aligned.m64n88k16.f32.bf16.bf16 {%0, %1, %2, %3, %4, %5, %6, %7, %8, %9, %10, %11, %12, %13, %14, %15, %16, %17, %18, %19, %20, %21, %22, %23, %24, %25, %26, %27, %28, %29, %30, %31, %32, %33, %34, %35, %36, %37, %38, %39, %40, %41, %42, %43}, %44, %45, 1, 1, 1, 0, 1;"
    : "+f"(d[OFF+0]), "+f"(d[OFF+1]), "+f"(d[OFF+2]), "+f"(d[OFF+3]), "+f"(d[OFF+4]), "+f"(d[OFF+5]), "+f"(d[OFF+6]), "+f"(d[OFF+7]),
      "+f"(d[OFF+8]), "+f"(d[OFF+9]), "+f"(d[OFF+10]), "+f"(d[OFF+11]), "+f"(d[OFF+12]), "+f"(d[OFF+13]), "+f"(d[OFF+14]), "+f"(d[OFF+15]),
      "+f"(d[OFF+16]), "+f"(d[OFF+17]), "+f"(d[OFF+18]), "+f"(d[OFF+19]), "+f"(d[OFF+20]), "+f"(d[OFF+21]), "+f"(d[OFF+22]), "+f"(d[OFF+23]),
      "+f"(d[OFF+24]), "+f"(d[OFF+25]), "+f"(d[OFF+26]), "+f"(d[OFF+27]), "+f"(d[OFF+28]), "+f"(d[OFF+29]), "+f"(d[OFF+30]), "+f"(d[OFF+31]),
      "+f"(d[OFF+32]), "+f"(d[OFF+33]), "+f"(d[OFF+34]), "+f"(d[OFF+35]), "+f"(d[OFF+36]), "+f"(d[OFF+37]), "+f"(d[OFF+38]), "+f"(d[OFF+39]),
      "+f"(d[OFF+40]), "+f"(d[OFF+41]), "+f"(d[OFF+42]), "+f"(d[OFF+43])
    : "l"(da), "l"(db));
}
template<int OFF, int TOT> __device__ __forceinline__ void wg_ss_n64(float (&d)[TOT], uint64_t da, uint64_t db) {
  asm volatile("wgmma.mma_async.sync.aligned.m64n64k16.f32.bf16.bf16 {%0, %1, %2, %3, %4, %5, %6, %7, %8, %9, %10, %11, %12, %13, %14, %15, %16, %17, %18, %19, %20, %21, %22, %23, %24, %25, %26, %27, %28, %29, %30, %31}, %32, %33, 1, 1, 1, 0, 1;"
    : "+f"(d[OFF+0]), "+f"(d[OFF+1]), "+f"(d[OFF+2]), "+f"(d[OFF+3]), "+f"(d[OFF+4]), "+f"(d[OFF+5]), "+f"(d[OFF+6]), "+f"(d[OFF+7]),
      "+f"(d[OFF+8]), "+f"(d[OFF+9]), "+f"(d[OFF+10]), "+f"(d[OFF+11]), "+f"(d[OFF+12]), "+f"(d[OFF+13]), "+f"(d[OFF+14]), "+f"(d[OFF+15]),
      "+f"(d[OFF+16]), "+f"(d[OFF+17]), "+f"(d[OFF+18]), "+f"(d[OFF+19]), "+f"(d[OFF+20]), "+f"(d[OFF+21]), "+f"(d[OFF+22]), "+f"(d[OFF+23]),
      "+f"(d[OFF+24]), "+f"(d[OFF+25]), "+f"(d[OFF+26]), "+f"(d[OFF+27]), "+f"(d[OFF+28]), "+f"(d[OFF+29]), "+f"(d[OFF+30]), "+f"(d[OFF+31])
    : "l"(da), "l"(db));
}
template<int OFF, int TOT> __device__ __forceinline__ void wg_ss_n32t(float (&d)[TOT], uint64_t da, uint64_t db) {
  asm volatile("wgmma.mma_async.sync.aligned.m64n32k16.f32.bf16.bf16 {%0, %1, %2, %3, %4, %5, %6, %7, %8, %9, %10, %11, %12, %13, %14, %15}, %16, %17, 1, 1, 1, 1, 0;"
    : "+f"(d[OFF+0]), "+f"(d[OFF+1]), "+f"(d[OFF+2]), "+f"(d[OFF+3]), "+f"(d[OFF+4]), "+f"(d[OFF+5]), "+f"(d[OFF+6]), "+f"(d[OFF+7]),
      "+f"(d[OFF+8]), "+f"(d[OFF+9]), "+f"(d[OFF+10]), "+f"(d[OFF+11]), "+f"(d[OFF+12]), "+f"(d[OFF+13]), "+f"(d[OFF+14]), "+f"(d[OFF+15])
    : "l"(da), "l"(db));
}
template<int SCD, int OFF, int TOT> __device__ __forceinline__ void wg_qk_n16(float (&d)[TOT], uint32_t a0, uint32_t a1, uint32_t a2, uint32_t a3, uint64_t db) {
  asm volatile("wgmma.mma_async.sync.aligned.m64n16k16.f32.f16.f16 {%0, %1, %2, %3, %4, %5, %6, %7}, {%8,%9,%10,%11}, %12, %13, 1, 1, 0;"
    : "+f"(d[OFF+0]), "+f"(d[OFF+1]), "+f"(d[OFF+2]), "+f"(d[OFF+3]), "+f"(d[OFF+4]), "+f"(d[OFF+5]), "+f"(d[OFF+6]), "+f"(d[OFF+7])
    : "r"(a0), "r"(a1), "r"(a2), "r"(a3), "l"(db), "n"(SCD));
}
template<int SCD, int OFF, int TOT> __device__ __forceinline__ void wg_qk_n24(float (&d)[TOT], uint32_t a0, uint32_t a1, uint32_t a2, uint32_t a3, uint64_t db) {
  asm volatile("wgmma.mma_async.sync.aligned.m64n24k16.f32.f16.f16 {%0, %1, %2, %3, %4, %5, %6, %7, %8, %9, %10, %11}, {%12,%13,%14,%15}, %16, %17, 1, 1, 0;"
    : "+f"(d[OFF+0]), "+f"(d[OFF+1]), "+f"(d[OFF+2]), "+f"(d[OFF+3]), "+f"(d[OFF+4]), "+f"(d[OFF+5]), "+f"(d[OFF+6]), "+f"(d[OFF+7]),
      "+f"(d[OFF+8]), "+f"(d[OFF+9]), "+f"(d[OFF+10]), "+f"(d[OFF+11])
    : "r"(a0), "r"(a1), "r"(a2), "r"(a3), "l"(db), "n"(SCD));
}
template<int SCD, int OFF, int TOT> __device__ __forceinline__ void wg_qk_n32(float (&d)[TOT], uint32_t a0, uint32_t a1, uint32_t a2, uint32_t a3, uint64_t db) {
  asm volatile("wgmma.mma_async.sync.aligned.m64n32k16.f32.f16.f16 {%0, %1, %2, %3, %4, %5, %6, %7, %8, %9, %10, %11, %12, %13, %14, %15}, {%16,%17,%18,%19}, %20, %21, 1, 1, 0;"
    : "+f"(d[OFF+0]), "+f"(d[OFF+1]), "+f"(d[OFF+2]), "+f"(d[OFF+3]), "+f"(d[OFF+4]), "+f"(d[OFF+5]), "+f"(d[OFF+6]), "+f"(d[OFF+7]),
      "+f"(d[OFF+8]), "+f"(d[OFF+9]), "+f"(d[OFF+10]), "+f"(d[OFF+11]), "+f"(d[OFF+12]), "+f"(d[OFF+13]), "+f"(d[OFF+14]), "+f"(d[OFF+15])
    : "r"(a0), "r"(a1), "r"(a2), "r"(a3), "l"(db), "n"(SCD));
}
template<int SCD, int OFF, int TOT> __device__ __forceinline__ void wg_qk_n40(float (&d)[TOT], uint32_t a0, uint32_t a1, uint32_t a2, uint32_t a3, uint64_t db) {
  asm volatile("wgmma.mma_async.sync.aligned.m64n40k16.f32.f16.f16 {%0, %1, %2, %3, %4, %5, %6, %7, %8, %9, %10, %11, %12, %13, %14, %15, %16, %17, %18, %19}, {%20,%21,%22,%23}, %24, %25, 1, 1, 0;"
    : "+f"(d[OFF+0]), "+f"(d[OFF+1]), "+f"(d[OFF+2]), "+f"(d[OFF+3]), "+f"(d[OFF+4]), "+f"(d[OFF+5]), "+f"(d[OFF+6]), "+f"(d[OFF+7]),
      "+f"(d[OFF+8]), "+f"(d[OFF+9]), "+f"(d[OFF+10]), "+f"(d[OFF+11]), "+f"(d[OFF+12]), "+f"(d[OFF+13]), "+f"(d[OFF+14]), "+f"(d[OFF+15]),
      "+f"(d[OFF+16]), "+f"(d[OFF+17]), "+f"(d[OFF+18]), "+f"(d[OFF+19])
    : "r"(a0), "r"(a1), "r"(a2), "r"(a3), "l"(db), "n"(SCD));
}
template<int SCD, int OFF, int TOT> __device__ __forceinline__ void wg_qk_n48(float (&d)[TOT], uint32_t a0, uint32_t a1, uint32_t a2, uint32_t a3, uint64_t db) {
  asm volatile("wgmma.mma_async.sync.aligned.m64n48k16.f32.f16.f16 {%0, %1, %2, %3, %4, %5, %6, %7, %8, %9, %10, %11, %12, %13, %14, %15, %16, %17, %18, %19, %20, %21, %22, %23}, {%24,%25,%26,%27}, %28, %29, 1, 1, 0;"
    : "+f"(d[OFF+0]), "+f"(d[OFF+1]), "+f"(d[OFF+2]), "+f"(d[OFF+3]), "+f"(d[OFF+4]), "+f"(d[OFF+5]), "+f"(d[OFF+6]), "+f"(d[OFF+7]),
      "+f"(d[OFF+8]), "+f"(d[OFF+9]), "+f"(d[OFF+10]), "+f"(d[OFF+11]), "+f"(d[OFF+12]), "+f"(d[OFF+13]), "+f"(d[OFF+14]), "+f"(d[OFF+15]),
      "+f"(d[OFF+16]), "+f"(d[OFF+17]), "+f"(d[OFF+18]), "+f"(d[OFF+19]), "+f"(d[OFF+20]), "+f"(d[OFF+21]), "+f"(d[OFF+22]), "+f"(d[OFF+23])
    : "r"(a0), "r"(a1), "r"(a2), "r"(a3), "l"(db), "n"(SCD));
}
template<int SCD, int OFF, int TOT> __device__ __forceinline__ void wg_pv_n24(float (&d)[TOT], uint32_t a0, uint32_t a1, uint32_t a2, uint32_t a3, uint64_t db) {
  asm volatile("wgmma.mma_async.sync.aligned.m64n24k16.f32.bf16.bf16 {%0, %1, %2, %3, %4, %5, %6, %7, %8, %9, %10, %11}, {%12,%13,%14,%15}, %16, %17, 1, 1, 1;"
    : "+f"(d[OFF+0]), "+f"(d[OFF+1]), "+f"(d[OFF+2]), "+f"(d[OFF+3]), "+f"(d[OFF+4]), "+f"(d[OFF+5]), "+f"(d[OFF+6]), "+f"(d[OFF+7]),
      "+f"(d[OFF+8]), "+f"(d[OFF+9]), "+f"(d[OFF+10]), "+f"(d[OFF+11])
    : "r"(a0), "r"(a1), "r"(a2), "r"(a3), "l"(db), "n"(SCD));
}
template<int SCD, int OFF, int TOT> __device__ __forceinline__ void wg_qkb_n64(float (&d)[TOT], uint32_t a0, uint32_t a1, uint32_t a2, uint32_t a3, uint64_t db) {
  asm volatile("wgmma.mma_async.sync.aligned.m64n64k16.f32.bf16.bf16 {%0, %1, %2, %3, %4, %5, %6, %7, %8, %9, %10, %11, %12, %13, %14, %15, %16, %17, %18, %19, %20, %21, %22, %23, %24, %25, %26, %27, %28, %29, %30, %31}, {%32,%33,%34,%35}, %36, %37, 1, 1, 0;"
    : "+f"(d[OFF+0]), "+f"(d[OFF+1]), "+f"(d[OFF+2]), "+f"(d[OFF+3]), "+f"(d[OFF+4]), "+f"(d[OFF+5]), "+f"(d[OFF+6]), "+f"(d[OFF+7]),
      "+f"(d[OFF+8]), "+f"(d[OFF+9]), "+f"(d[OFF+10]), "+f"(d[OFF+11]), "+f"(d[OFF+12]), "+f"(d[OFF+13]), "+f"(d[OFF+14]), "+f"(d[OFF+15]),
      "+f"(d[OFF+16]), "+f"(d[OFF+17]), "+f"(d[OFF+18]), "+f"(d[OFF+19]), "+f"(d[OFF+20]), "+f"(d[OFF+21]), "+f"(d[OFF+22]), "+f"(d[OFF+23]),
      "+f"(d[OFF+24]), "+f"(d[OFF+25]), "+f"(d[OFF+26]), "+f"(d[OFF+27]), "+f"(d[OFF+28]), "+f"(d[OFF+29]), "+f"(d[OFF+30]), "+f"(d[OFF+31])
    : "r"(a0), "r"(a1), "r"(a2), "r"(a3), "l"(db), "n"(SCD));
}
template<int N, int SCD, int OFF, int TOT> __device__ __forceinline__ void wg_qk(float (&d)[TOT], const uint32_t (&q)[4], uint64_t db) {
  if constexpr (N == 16) wg_qk_n16<SCD, OFF, TOT>(d, q[0], q[1], q[2], q[3], db);
  if constexpr (N == 24) wg_qk_n24<SCD, OFF, TOT>(d, q[0], q[1], q[2], q[3], db);
  if constexpr (N == 32) wg_qk_n32<SCD, OFF, TOT>(d, q[0], q[1], q[2], q[3], db);
  if constexpr (N == 40) wg_qk_n40<SCD, OFF, TOT>(d, q[0], q[1], q[2], q[3], db);
  if constexpr (N == 48) wg_qk_n48<SCD, OFF, TOT>(d, q[0], q[1], q[2], q[3], db);
}

__device__ __forceinline__ uint32_t exp_mufu(float a, float b) { return pack_bf16(ex2(a), ex2(b)); }
__device__ __forceinline__ uint32_t exp_poly(float a, float b, uint32_t mlo, uint32_t mhi) {
  uint32_t u = __byte_perm(__float_as_uint(a), __float_as_uint(b), 0x6521), mh, e, p;
  asm("lop3.b32 %0, %1, %2, 0x3F003F00, 0xEA;" : "=r"(mh) : "r"(u), "r"(mlo));
  asm("lop3.b32 %0, %1, %2, 0x00020002, 0xEA;" : "=r"(e) : "r"(u), "r"(mhi));
  asm("fma.rn.bf16x2 %0, %1, %2, %3;" : "=r"(p) : "r"(u), "r"(mh), "r"(e));
  return p;
}
constexpr float MAGIC_C = 48948.0625f;
constexpr float QSCALE = 0.25f * 1.4426950408889634f * 8.f;
constexpr float BOUND = 80.f;

__device__ __forceinline__ void softmax_step(const float (&s)[32], uint32_t (&p)[16], uint32_t mlo, uint32_t mhi) {
  constexpr int PP = NP / 4;
  int ip = 0, im = PP;
#pragma unroll
  for (int i = 0; i < 16; i++) {
    if (((i + 1) * PP / 16) > (i * PP / 16)) { p[ip] = exp_poly(s[2 * ip], s[2 * ip + 1], mlo, mhi); ip++; }
    else { p[im] = exp_mufu(s[2 * im], s[2 * im + 1]); im++; }
  }
}
constexpr uint64_t VSTEP = ((uint64_t)16 << 32) - 16;
__device__ __forceinline__ void issue_qk(float (&s)[32], const uint32_t (&q)[4], uint64_t dk) {
  wg_qk<NM, 0, NP / 2, 32>(s, q, dk + NP * 2);
  wg_qk<NP, 1, 0, 32>(s, q, dk);
}
__device__ __forceinline__ void issue_pv(float (&o)[12], const uint32_t (&p)[16], uint64_t& dv) {
#pragma unroll
  for (int c = 0; c < 4; c++) { wg_pv_n24<1, 0, 12>(o, p[4 * c], p[4 * c + 1], p[4 * c + 2], p[4 * c + 3], dv); dv += VSTEP; }
}

struct Params {
  const __nv_bfloat16* gate_w;
  const __nv_bfloat16* b_sp;
  const __nv_bfloat16* w_sp;
  const __nv_bfloat16* w_out;
  const __nv_bfloat16* wo;
  __nv_bfloat16* out;
};

__device__ __forceinline__ void store_o_tile(const float (&o)[12], int bi, int bj, int tau, int tid, uint32_t sb) {
  const int half = tau & 1, hh = tau >> 1, w = tid >> 5, g = (tid & 31) >> 2;
  const int r0 = half * 64 + w * 16 + g;
  const float f0 = __fdividef(ldsf(sb + SM_G + r0 * 4), o[4]), f1 = __fdividef(ldsf(sb + SM_G + (r0 + 8) * 4), o[6]);
  uint32_t* dst = reinterpret_cast<uint32_t*>(g_o) + (bi * 8 + bj) * 4096 + (half * 8 + w * 2) * 256 + hh * 64 + (tid & 31);
  dst[0] = pack_bf16(o[0] * f0, o[1] * f0);
  dst[32] = pack_bf16(o[8] * f0, o[9] * f0);
  dst[256] = pack_bf16(o[2] * f1, o[3] * f1);
  dst[288] = pack_bf16(o[10] * f1, o[11] * f1);
}

__global__ void __cluster_dims__(2, 1, 1) __launch_bounds__(NTHREADS, 1)
fused_kernel(const __grid_constant__ CUtensorMap tm_x, const __grid_constant__ CUtensorMap tm_wq,
             const __grid_constant__ CUtensorMap tm_wk, const __grid_constant__ CUtensorMap tm_wv,
             const __grid_constant__ CUtensorMap tm_win, const __grid_constant__ CUtensorMap tm_wsp,
             const __grid_constant__ CUtensorMap tm_wout, const __grid_constant__ CUtensorMap tm_wo, const Params prm) {
  extern __shared__ __align__(1024) uint8_t smem_raw[];
  const uint32_t sb = (uint32_t)__cvta_generic_to_shared(smem_raw);
  const int wg = __shfl_sync(0xffffffffu, (int)(threadIdx.x >> 7), 0);
  const int tid = threadIdx.x & 127;
  const int lane = threadIdx.x & 31;
  const int bi = blockIdx.x >> 3, bj = blockIdx.x & 7, rank = bj & 1;
  auto BAR = [&](int k) { return sb + SM_BAR + 8u * k; };

  if (threadIdx.x == 0) {
    for (int k = 0; k < B_COUNT; k++) {
      uint32_t cnt = 1;
      if (k >= B_XEMPTY && k < B_XEMPTY + 8) cnt = 4;
      if (k >= B_WEMPTY && k < B_WEMPTY + 8) cnt = 3;
      if (k >= B_WEMPTY + 8 && k < B_WEMPTY + 12) cnt = 2;
      if (k >= B_REMPTY && k < B_REMPTY + 3) cnt = 2;
      mbar_init(BAR(k), cnt);
    }
    asm volatile("fence.mbarrier_init.release.cluster;" ::: "memory");
  }
  __syncthreads();
  asm volatile("barrier.cluster.arrive.relaxed.aligned;" ::: "memory");
  asm volatile("barrier.cluster.wait.acquire.aligned;" ::: "memory");

  if (wg == 4) {
    asm volatile("setmaxnreg.dec.sync.aligned.u32 24;");
    const int pw = __shfl_sync(0xffffffffu, tid >> 5, 0);
    if (pw == 0) {
      if (lane == 0) {
        TS(0);
        auto fill_w = [&](int f) {
          const uint32_t slot = sb + SM_RING + (f & 3) * WSLOT, bar = BAR(B_WFULL + f);
          const int k0 = (f & 7) * 64;
          if (f < 8) {
            mbar_expect(bar, 12288 + 2048);
            for (int a = 0; a < 3; a++) tma2d(slot + a * 4096, &tm_win, 688 + 88 * bj + 32 * a, k0, bar);
            tma2d(slot + 12288, rank ? &tm_wv : &tm_wk, 0, k0, bar);
          } else {
            mbar_expect(bar, 12288 + 8192);
            tma2d(slot + 12288, &tm_wq, 64 * bj, k0, bar);
            for (int a = 0; a < 3; a++) tma2d(slot + a * 4096, &tm_win, 88 * bj + 32 * a, k0, bar);
          }
        };
#pragma unroll 1
        for (int c = 0; c < 8; c++) {
          mbar_expect(BAR(B_XFULL + c), 16384);
          tma2d_mc(sb + SM_K + c * 16384 + rank * 8192, &tm_x, c * 64, bi * 128 + rank * 64, BAR(B_XFULL + c));
          if (c < 4) fill_w(c);
        }
#pragma unroll 1
        for (int f = 4; f < 16; f++) {
          mbar_wait(BAR(B_WEMPTY + f - 4), 0);
          fill_w(f);
          if (f == 11) {
            const uint8_t* ws = reinterpret_cast<const uint8_t*>(prm.w_sp) + (size_t)blockIdx.x * 65536;
            for (int a = 0; a < 4; a++) l2_prefetch(ws + a * 16384, 16384);
            l2_prefetch(reinterpret_cast<const uint8_t*>(prm.w_out) + blockIdx.x * 5504, 5504);
            l2_prefetch(reinterpret_cast<const uint8_t*>(prm.wo) + blockIdx.x * 4096, 4096);
          }
        }
        TS(1);
        mbar_wait(BAR(B_XEMPTY + 7), 0);
        mbar_wait(BAR(B_EPOCH), 0);
      }
      __syncwarp();
      const unsigned ep1 = lds32(sb + SM_MISC + 4 * M_EPOCH) + 1;
      wait_ge(&g_zflag[bj * 32 + lane], ep1);
      __syncwarp();
      if (lane == 0) {
        fence_async();
        TS(2);
        int st = 0, ph = 1;
#pragma unroll 1
        for (int n = 0; n < 43; n++) {
          const uint32_t stg = sb + SM_RING + st * RSTAGE, bar = BAR(B_RFULL + st);
          if (n >= 3) mbar_wait(BAR(B_REMPTY + st), ph);
          if (n < 32) {
            mbar_expect(bar, 16384 + 11264);
            tma2d_mc(stg + rank * 8192, &tm_wsp, n * 64, bi * 128 + rank * 64, bar);
            bulk(stg + 16384, reinterpret_cast<const uint8_t*>(g_z2n) + (bj * 32 + n) * 11264, 11264, bar);
          } else {
            const int c = n - 32;
            mbar_expect(bar, 16384 + 8192);
            tma2d(stg + 16384, &tm_wout, 64 * bj, c * 64, bar);
            if (c == 0) { wait_ge(&g_ucnt[bi * 32], ep1 * 8); fence_async(); TS(3); }
            bulk_mc(stg + rank * 8192, reinterpret_cast<const uint8_t*>(g_u) + (bi * 11 + c) * 16384 + rank * 8192, 8192, bar);
          }
          if (++st == 3) { st = 0; ph ^= 1; }
        }
#pragma unroll 1
        for (int n = 0; n < 3; n++) {
          mbar_wait(BAR(B_REMPTY + st), ph);
          if (++st == 3) { st = 0; ph ^= 1; }
        }
        mbar_expect(BAR(B_WOFULL), 65536);
#pragma unroll 1
        for (int c = 0; c < 8; c++) tma2d(sb + SM_RING + c * 8192, &tm_wo, 64 * bj, c * 64, BAR(B_WOFULL));
        TS(4);
        wait_ge(&g_ocnt[bi * 32], ep1 * 24);
        fence_async();
        TS(5);
#pragma unroll 1
        for (int c = 0; c < 8; c++) {
          mbar_expect(BAR(B_OFULL + c), 16384);
          bulk_mc(sb + SM_K + c * 16384 + rank * 8192, reinterpret_cast<const uint8_t*>(g_o) + (bi * 8 + c) * 16384 + rank * 8192, 8192, BAR(B_OFULL + c));
        }
      }
    } else if (pw == 1) {
      unsigned ep = 0;
      if (lane == 0) {
        ep = atomicAdd(&g_ticket, 1u) / NCTA;
        sts32(sb + SM_MISC + 4 * M_EPOCH, ep);
        mbar_arrive(BAR(B_EPOCH));
        wait_ge(&g_kvcnt[0], (ep + 1) * NCTA);
        TS(6);
      }
      __syncwarp();
      float kn2 = fmaxf(__ldcg(&g_kvstat[(4 * lane) * 16]), __ldcg(&g_kvstat[(4 * lane + 2) * 16]));
      float vm = 0.f;
#pragma unroll 4
      for (int p = 0; p < 32; p++) vm = fmaxf(vm, __ldcg(&g_kvstat[(4 * p + 1 + (lane >> 4) * 2) * 16 + (lane & 15)]));
      vm = fmaxf(vm, __shfl_xor_sync(0xffffffffu, vm, 16));
#pragma unroll
      for (int m = 16; m > 0; m >>= 1) kn2 = fmaxf(kn2, __shfl_xor_sync(0xffffffffu, kn2, m));
      const bool vok = __all_sync(0xffffffffu, vm >= 9.5367431640625e-07f && vm <= 1073741824.f);
      if (lane == 0) {
        sts32(sb + SM_MISC + 4 * M_KN2, __float_as_uint(kn2));
        sts32(sb + SM_MISC + 4 * M_VOK, vok ? 1u : 0u);
        mbar_arrive(BAR(B_KSTAT));
        fence_async();
#pragma unroll 1
        for (int c = 0; c < 8; c++) {
          const uint32_t bytes = c == 7 ? 16640 : 16384, hb = bytes / 2, off = c * 16384 + rank * hb;
          mbar_wait(BAR(B_XEMPTY + c), 0);
          mbar_expect(BAR(B_KVFULL + c), bytes);
          bulk_mc(sb + SM_K + off, reinterpret_cast<const uint8_t*>(g_kimg) + off, hb, BAR(B_KVFULL + c));
        }
        TS(7);
        mbar_wait(BAR(B_DEC), 0);
        if (!lds32(sb + SM_MISC + 4 * M_FAST)) {
          for (int c = 0; c < 4; c++) mbar_wait(BAR(B_KVFULL + c), 0);
          mbar_expect(BAR(B_KFB), 65536);
          for (int c = 0; c < 4; c++) bulk(sb + SM_K + c * 16384, reinterpret_cast<const uint8_t*>(g_kbf) + c * 16384, 16384, BAR(B_KFB));
        }
      }
    }
  } else if (wg == 3) {
    asm volatile("setmaxnreg.inc.sync.aligned.u32 120;");
    const int w = tid >> 5, g = lane >> 2, t4 = lane & 3;
    {
      float a0 = 0.f, a1 = 0.f;
#pragma unroll 1
      for (int c = 0; c < 8; c++) {
        mbar_wait(BAR(B_XFULL + c), 0);
#pragma unroll
        for (int v = 0; v < 8; v++) {
          const uint4 xv = lds128(sb + SM_K + c * 16384 + tid * 128 + ((v ^ (tid & 7)) << 4));
          const uint4 gv = __ldg(reinterpret_cast<const uint4*>(prm.gate_w) + c * 8 + v);
          a0 = fmaf(bf_lo(xv.x), bf_lo(gv.x), a0); a1 = fmaf(bf_hi(xv.x), bf_hi(gv.x), a1);
          a0 = fmaf(bf_lo(xv.y), bf_lo(gv.y), a0); a1 = fmaf(bf_hi(xv.y), bf_hi(gv.y), a1);
          a0 = fmaf(bf_lo(xv.z), bf_lo(gv.z), a0); a1 = fmaf(bf_hi(xv.z), bf_hi(gv.z), a1);
          a0 = fmaf(bf_lo(xv.w), bf_lo(gv.w), a0); a1 = fmaf(bf_hi(xv.w), bf_hi(gv.w), a1);
        }
      }
      sts32(sb + SM_G + tid * 4, __float_as_uint(__fdividef(1.f, 1.f + __expf(-(a0 + a1)))));
      fence_async_smem();
      bar_sync(4, 128);
      bar_arrive(5, 512);
    }
    if (tid == 0) TS(8);
    float acc[88];
    {
#pragma unroll
      for (int k = 0; k < 88; k++) acc[k] = 0.f;
      regfence(acc);
#pragma unroll 1
      for (int c = 0; c < 8; c++) {
        mbar_wait(BAR(B_WFULL + 8 + c), 0);
        const uint64_t da = mkdesc(sb + SM_K + c * 16384, 16, 1024, 1);
        const uint64_t db = mkdesc(sb + SM_RING + (c & 3) * WSLOT, 4096, 512, 2);
        wg_fence();
#pragma unroll
        for (int k = 0; k < 4; k++) { wg_ss_n88<0, 88>(acc, da + 2 * k, db + 64 * k); wg_ss_n88<44, 88>(acc, da + 512 + 2 * k, db + 64 * k); }
        wg_commit();
        wg_wait<0>();
        if (tid == 0) { if (c < 4) mbar_arrive(BAR(B_WEMPTY + 8 + c)); mbar_arrive_both(BAR(B_XEMPTY + c)); }
      }
      regfence(acc);
      if (tid == 0) TS(9);
      uint4* z1p = g_z1 + blockIdx.x * 11 * 128 + tid;
#pragma unroll
      for (int q = 0; q < 11; q++) {
        uint4 v;
        v.x = pack_bf16(gelu_tanh(acc[8 * q + 0]), gelu_tanh(acc[8 * q + 1]));
        v.y = pack_bf16(gelu_tanh(acc[8 * q + 2]), gelu_tanh(acc[8 * q + 3]));
        v.z = pack_bf16(gelu_tanh(acc[8 * q + 4]), gelu_tanh(acc[8 * q + 5]));
        v.w = pack_bf16(gelu_tanh(acc[8 * q + 6]), gelu_tanh(acc[8 * q + 7]));
        z1p[q * 128] = v;
      }
    }
    if (tid == 0) TS(10);
    int st = 0, ph = 0;
    {
#pragma unroll
      for (int k = 0; k < 88; k++) acc[k] = 0.f;
      regfence(acc);
#pragma unroll 1
      for (int n = 0; n < 32; n++) {
        mbar_wait(BAR(B_RFULL + st), ph);
        const uint64_t da = mkdesc(sb + SM_RING + st * RSTAGE, 16, 1024, 1);
        const uint64_t db = mkdesc(sb + SM_RING + st * RSTAGE + 16384, 1408, 128, 0);
#pragma unroll
        for (int k = 0; k < 4; k++) {
          wg_fence();
          wg_ss_n88<0, 88>(acc, da + 2 * k, db + 176 * k);
          wg_ss_n88<44, 88>(acc, da + 512 + 2 * k, db + 176 * k);
          wg_commit();
          wg_wait<0>();
        }
        if (tid == 0) mbar_arrive_both(BAR(B_REMPTY + st));
        if (++st == 3) { st = 0; ph ^= 1; }
      }
      regfence(acc);
      if (tid == 0) TS(11);
      float bs[4], og[4];
#pragma unroll
      for (int r = 0; r < 4; r++) {
        const int row = (r >> 1) * 64 + w * 16 + (r & 1) * 8 + g;
        bs[r] = __bfloat162float(prm.b_sp[bi * 128 + row]);
        og[r] = 1.f - ldsf(sb + SM_G + row * 4);
      }
      const uint4* z1p = g_z1 + blockIdx.x * 11 * 128 + tid;
      uint32_t* up = reinterpret_cast<uint32_t*>(g_u) + bi * 11 * 4096 + w * 512 + lane;
#pragma unroll
      for (int q = 0; q < 11; q++) {
        const uint4 zv = z1p[q * 128];
        const uint32_t zz[4] = {zv.x, zv.y, zv.z, zv.w};
#pragma unroll
        for (int e = 0; e < 4; e++) {
          const int k = 8 * q + 2 * e, hf = k / 44, c8 = (k % 44) / 4, r8 = ((k % 44) >> 1) & 1, r = hf * 2 + r8;
          const int cb = 11 * bj + c8;
          uint32_t v = pack_bf16(bf_lo(zz[e]) * (acc[k] + bs[r]) * og[r], bf_hi(zz[e]) * (acc[k + 1] + bs[r]) * og[r]);
          if (c8 >= 9 && bj == 7) v = 0;
          up[(cb >> 3) * 4096 + (hf * 8 + r8) * 256 + (cb & 7) * 32] = v;
        }
      }
      fence_async();
      bar_sync(4, 128);
      if (tid == 0) red_release(&g_ucnt[bi * 32]);
    }
    if (tid == 0) TS(12);
    {
      float oc[64];
#pragma unroll
      for (int k = 0; k < 64; k++) oc[k] = 0.f;
      regfence(oc);
#pragma unroll 1
      for (int n = 0; n < 11; n++) {
        mbar_wait(BAR(B_RFULL + st), ph);
        const uint64_t da = mkdesc(sb + SM_RING + st * RSTAGE, 128, 1024, 0);
        const uint64_t db = mkdesc(sb + SM_RING + st * RSTAGE + 16384, 8192, 1024, 1);
#pragma unroll
        for (int k = 0; k < 4; k++) {
          wg_fence();
          wg_ss_n64<0, 64>(oc, da + 16 * k, db + 128 * k);
          wg_ss_n64<32, 64>(oc, da + 512 + 16 * k, db + 128 * k);
          wg_commit();
          wg_wait<0>();
        }
        if (tid == 0) mbar_arrive_both(BAR(B_REMPTY + st));
        if (++st == 3) { st = 0; ph ^= 1; }
      }
      if (tid == 0) TS(13);
      mbar_wait(BAR(B_WOFULL), 0);
#pragma unroll 1
      for (int c = 0; c < 8; c++) {
        mbar_wait(BAR(B_OFULL + c), 0);
        const uint64_t da = mkdesc(sb + SM_K + c * 16384, 128, 1024, 0);
        const uint64_t db = mkdesc(sb + SM_RING + c * 8192, 8192, 1024, 1);
        wg_fence();
#pragma unroll
        for (int k = 0; k < 4; k++) { wg_ss_n64<0, 64>(oc, da + 16 * k, db + 128 * k); wg_ss_n64<32, 64>(oc, da + 512 + 16 * k, db + 128 * k); }
        wg_commit();
      }
      wg_wait<0>();
      regfence(oc);
      if (tid == 0) TS(14);
      uint32_t* op = reinterpret_cast<uint32_t*>(prm.out) + (bi * 128 + w * 16 + g) * 256 + bj * 32 + t4;
#pragma unroll
      for (int k = 0; k < 64; k += 2) {
        const int hf = k / 32, c8 = (k % 32) / 4, r8 = (k >> 1) & 1;
        op[(hf * 64 + r8 * 8) * 256 + c8 * 4] = pack_bf16(oc[k], oc[k + 1]);
      }
      if (tid == 0) TS(15);
    }
  } else {
    asm volatile("setmaxnreg.inc.sync.aligned.u32 112;");
    const int w = tid >> 5, g = lane >> 2, t4 = lane & 3;
    if (wg < 2) {
      float acc[44];
#pragma unroll
      for (int k = 0; k < 44; k++) acc[k] = 0.f;
      regfence(acc);
#pragma unroll 1
      for (int c = 0; c < 8; c++) {
        mbar_wait(BAR(B_XFULL + c), 0);
        mbar_wait(BAR(B_WFULL + c), 0);
        const uint64_t da = mkdesc(sb + SM_K + c * 16384 + wg * 8192, 16, 1024, 1);
        const uint64_t db = mkdesc(sb + SM_RING + (c & 3) * WSLOT, 4096, 512, 2);
        wg_fence();
#pragma unroll
        for (int k = 0; k < 4; k++) wg_ss_n88<0, 44>(acc, da + 2 * k, db + 64 * k);
        wg_commit();
        wg_wait<0>();
        if (tid == 0) mbar_arrive(BAR(B_WEMPTY + c));
      }
      regfence(acc);
      if (tid == 0) TS(16 + wg);
      const bool last = bj == 7;
      float s0 = 0.f, s1 = 0.f;
#pragma unroll
      for (int k = 0; k < 44; k++) {
        acc[k] = gelu_tanh(acc[k]);
        if (k & 2) s1 += acc[k]; else s0 += acc[k];
      }
      s0 += __shfl_xor_sync(0xffffffffu, s0, 1); s0 += __shfl_xor_sync(0xffffffffu, s0, 2);
      s1 += __shfl_xor_sync(0xffffffffu, s1, 1); s1 += __shfl_xor_sync(0xffffffffu, s1, 2);
      const float inv_n = last ? (1.f / 72.f) : (1.f / 88.f);
      const float m0 = s0 * inv_n, m1 = s1 * inv_n;
      float v0 = 0.f, v1 = 0.f;
#pragma unroll
      for (int k = 0; k < 44; k++) {
        float d = acc[k] - ((k & 2) ? m1 : m0);
        if (k >= 36 && last) d = 0.f;
        if (k & 2) v1 = fmaf(d, d, v1); else v0 = fmaf(d, d, v0);
      }
      v0 += __shfl_xor_sync(0xffffffffu, v0, 1); v0 += __shfl_xor_sync(0xffffffffu, v0, 2);
      v1 += __shfl_xor_sync(0xffffffffu, v1, 1); v1 += __shfl_xor_sync(0xffffffffu, v1, 2);
      const int r0 = wg * 64 + w * 16 + g;
      if (t4 == 0) {
        g_lnstat[(bi * 8 + bj) * 128 + r0] = make_float2(m0, v0);
        g_lnstat[(bi * 8 + bj) * 128 + r0 + 8] = make_float2(m1, v1);
      }
      bar_sync(1 + wg, 128);
      mbar_wait(BAR(B_EPOCH), 0);
      const unsigned ep1 = lds32(sb + SM_MISC + 4 * M_EPOCH) + 1;
      if (tid == 0) {
        red_release(&g_statcnt[(bi * 2 + wg) * 32]);
        TS(18 + wg);
        wait_ge(&g_statcnt[(bi * 2 + wg) * 32], ep1 * 8);
      }
      bar_sync(1 + wg, 128);
      float mean[2], rstd[2];
#pragma unroll
      for (int r = 0; r < 2; r++) {
        const float2 a = __ldcg(&g_lnstat[(bi * 8 + 2 * t4) * 128 + r0 + 8 * r]);
        const float2 b = __ldcg(&g_lnstat[(bi * 8 + 2 * t4 + 1) * 128 + r0 + 8 * r]);
        const float nb = t4 == 3 ? 72.f : 88.f;
        float sm = fmaf(a.x, 88.f, b.x * nb);
        sm += __shfl_xor_sync(0xffffffffu, sm, 1); sm += __shfl_xor_sync(0xffffffffu, sm, 2);
        const float mu = sm * (1.f / 688.f);
        const float da = a.x - mu, db = b.x - mu;
        float m2 = a.y + b.y + 88.f * da * da + nb * db * db;
        m2 += __shfl_xor_sync(0xffffffffu, m2, 1); m2 += __shfl_xor_sync(0xffffffffu, m2, 2);
        mean[r] = mu;
        rstd[r] = rsqrtf(fmaf(m2, 1.f / 688.f, 1e-5f));
      }
      uint32_t* zp = reinterpret_cast<uint32_t*>(g_z2n) + (bj * 32 + bi * 2 + wg) * 2816 + w * 704 + lane;
#pragma unroll
      for (int k = 0; k < 44; k += 2) {
        const int r = (k >> 1) & 1, c8 = k >> 2;
        uint32_t v = pack_bf16((acc[k] - mean[r]) * rstd[r], (acc[k + 1] - mean[r]) * rstd[r]);
        if (c8 >= 9 && last) v = 0;
        zp[r * 352 + c8 * 32] = v;
      }
      fence_async();
      bar_sync(1 + wg, 128);
      if (tid == 0) { st_release(&g_zflag[bj * 32 + bi * 2 + wg], ep1); TS(20 + wg); }
    } else {
      const int pair = bi * 4 + (bj >> 1);
      {
        float kv[16];
#pragma unroll
        for (int k = 0; k < 16; k++) kv[k] = 0.f;
        regfence(kv);
#pragma unroll 1
        for (int c = 0; c < 8; c++) {
          mbar_wait(BAR(B_XFULL + c), 0);
          mbar_wait(BAR(B_WFULL + c), 0);
          const uint64_t da = mkdesc(sb + SM_RING + (c & 3) * WSLOT + 12288, 0, 256, 3);
          const uint64_t db = mkdesc(sb + SM_K + c * 16384 + (bj >> 1) * 4096, 16, 1024, 1);
          wg_fence();
#pragma unroll
          for (int k = 0; k < 4; k++) wg_ss_n32t<0, 16>(kv, da + 32 * k, db + 2 * k);
          wg_commit();
          wg_wait<0>();
          if (tid == 0) mbar_arrive(BAR(B_WEMPTY + c));
        }
        regfence(kv);
        if (tid == 0) TS(22);
        const uint32_t sT = sb + SM_Q, sH = sb + SM_Q + 4096;
        if (w == 0) {
#pragma unroll
          for (int k = 0; k < 16; k++) {
            const int tok = (k >> 2) * 8 + 2 * t4 + (k & 1), d = g + ((k >> 1) & 1) * 8;
            sts32(sT + (tok * 17 + d) * 4, __float_as_uint(__bfloat162float(__float2bfloat16_rn(kv[k]))));
          }
        }
        bar_sync(3, 128);
        const int tok = (tid & 63) >> 1, hf = tid & 1;
        const uint32_t inner = (pair & 7) * 16;
        if (rank == 0) {
          if (tid < 48) {
            const int d = tid & 15, sg = tid >> 4, j0 = sg == 0 ? 0 : (sg == 1 ? 10 : 22), j1 = sg == 0 ? 10 : (sg == 1 ? 22 : 32);
            float run = 0.f;
#pragma unroll 1
            for (int jj = j0; jj < j1; jj++) {
              const float kx = ldsf(sT + (jj * 17 + d) * 4);
              __half hv;
              if (pair < NP) { hv = __float2half_rn(fmaf(kx, 16.f, -run)); run += __half2float(hv); }
              else hv = __float2half_rn(kx * 0.125f);
              sts16(sH + (jj * 16 + d) * 2, __half_as_ushort(hv));
            }
          } else if (w == 2) {
            float n2 = 0.f;
#pragma unroll
            for (int d = 0; d < 16; d++) { const float kx = ldsf(sT + (lane * 17 + d) * 4); n2 = fmaf(kx, kx, n2); }
            if (!(n2 <= 3.0e38f)) n2 = 3.0e38f;
#pragma unroll
            for (int m = 16; m > 0; m >>= 1) n2 = fmaxf(n2, __shfl_xor_sync(0xffffffffu, n2, m));
            if (lane == 0) g_kvstat[blockIdx.x * 16] = n2;
          }
          bar_sync(3, 128);
          const uint32_t off = tok * 2048 + (pair >> 3) * 256 + hf * 128 + inner;
          if (tid < 64) g_kimg[off >> 4] = lds128(sH + tok * 32 + hf * 16);
          else {
            float f[8];
#pragma unroll
            for (int e = 0; e < 8; e++) f[e] = ldsf(sT + (tok * 17 + hf * 8 + e) * 4);
            g_kbf[off >> 4] = make_uint4(pack_bf16(f[0], f[1]), pack_bf16(f[2], f[3]), pack_bf16(f[4], f[5]), pack_bf16(f[6], f[7]));
          }
        } else {
          if (tid < 64) {
            float f[8];
#pragma unroll
            for (int e = 0; e < 8; e++) f[e] = ldsf(sT + (tok * 17 + hf * 8 + e) * 4);
            const uint32_t sbo = 256 * (4 * tok + (pair >> 4) + 1);
            const uint32_t off = (hf ? SM_ONES + sbo : SM_ONES - sbo) + ((pair >> 3) & 1) * 128 + inner;
            g_kimg[off >> 4] = make_uint4(pack_bf16(f[0], f[1]), pack_bf16(f[2], f[3]), pack_bf16(f[4], f[5]), pack_bf16(f[6], f[7]));
          } else if (tid < 80) {
            float vm = 0.f;
#pragma unroll 8
            for (int jj = 0; jj < 32; jj++) { float a = fabsf(ldsf(sT + (jj * 17 + tid - 64) * 4)); if (!(a <= 3.0e38f)) a = 3.0e38f; vm = fmaxf(vm, a); }
            g_kvstat[blockIdx.x * 16 + tid - 64] = vm;
          } else if (tid >= 96 && tid < 112 && pair == 0) {
            g_kimg[(SM_ONES >> 4) + tid - 96] = make_uint4(0x3F803F80u, 0x3F803F80u, 0x3F803F80u, 0x3F803F80u);
          }
        }
        fence_async();
        bar_sync(3, 128);
        if (tid == 0) { red_release(&g_kvcnt[0]); TS(23); }
      }
      float qa[64];
#pragma unroll
      for (int k = 0; k < 64; k++) qa[k] = 0.f;
      regfence(qa);
#pragma unroll 1
      for (int c = 0; c < 8; c++) {
        mbar_wait(BAR(B_WFULL + 8 + c), 0);
        const uint64_t da = mkdesc(sb + SM_K + c * 16384, 16, 1024, 1);
        const uint64_t db = mkdesc(sb + SM_RING + (c & 3) * WSLOT + 12288, 8192, 1024, 1);
        wg_fence();
#pragma unroll
        for (int k = 0; k < 4; k++) { wg_ss_n64<0, 64>(qa, da + 2 * k, db + 128 * k); wg_ss_n64<32, 64>(qa, da + 512 + 2 * k, db + 128 * k); }
        wg_commit();
        wg_wait<0>();
        if (tid == 0) { if (c < 4) mbar_arrive(BAR(B_WEMPTY + 8 + c)); mbar_arrive_both(BAR(B_XEMPTY + c)); }
      }
      regfence(qa);
      if (tid == 0) TS(24);
      uint32_t qb[32];
      float n2 = 0.f;
#pragma unroll
      for (int k = 0; k < 32; k++) qb[k] = pack_bf16(qa[2 * k], qa[2 * k + 1]);
#pragma unroll
      for (int k = 0; k < 16; k++) {
        const uint32_t a = qb[4 * (k >> 1) + (k & 1)], b = qb[4 * (k >> 1) + (k & 1) + 2];
        float s = bf_lo(a) * bf_lo(a);
        s = fmaf(bf_hi(a), bf_hi(a), s); s = fmaf(bf_lo(b), bf_lo(b), s); s = fmaf(bf_hi(b), bf_hi(b), s);
        s += __shfl_xor_sync(0xffffffffu, s, 1); s += __shfl_xor_sync(0xffffffffu, s, 2);
        if (!(s <= 3.0e38f)) s = 3.0e38f;
        n2 = fmaxf(n2, s);
      }
#pragma unroll
      for (int m = 16; m > 2; m >>= 1) n2 = fmaxf(n2, __shfl_xor_sync(0xffffffffu, n2, m));
      if (lane == 0) sts32(sb + SM_MISC + 4 * (M_RED + w), __float_as_uint(n2));
      mbar_wait(BAR(B_KSTAT), 0);
      bar_sync(3, 128);
      const float qn2 = fmaxf(fmaxf(ldsf(sb + SM_MISC + 4 * M_RED), ldsf(sb + SM_MISC + 4 * (M_RED + 1))),
                              fmaxf(ldsf(sb + SM_MISC + 4 * (M_RED + 2)), ldsf(sb + SM_MISC + 4 * (M_RED + 3))));
      const float kn2 = ldsf(sb + SM_MISC + 4 * M_KN2);
      constexpr float SC = QSCALE * 0.125f;
      const bool fast = lds32(sb + SM_MISC + 4 * M_VOK) && qn2 <= 4.0e8f && kn2 <= 4.0e6f && qn2 * kn2 * (SC * SC) <= BOUND * BOUND;
#pragma unroll
      for (int tq = 0; tq < 8; tq++) {
        uint32_t r[4];
#pragma unroll
        for (int e = 0; e < 4; e++) {
          const uint32_t v = qb[(tq & 1) * 16 + (tq >> 1) * 4 + e];
          r[e] = fast ? pack_f16(bf_lo(v) * QSCALE, bf_hi(v) * QSCALE) : v;
        }
        sts128(sb + SM_Q + tq * 2048 + tid * 16, r[0], r[1], r[2], r[3]);
      }
      if (tid == 0) { sts32(sb + SM_MISC + 4 * M_FAST, fast ? 1u : 0u); mbar_arrive(BAR(B_DEC)); }
    }
    bar_sync(5, 512);
    if (tid == 0) TS(25 + wg);
#pragma unroll 1
    for (int c = 0; c < 8; c++) mbar_wait(BAR(B_KVFULL + c), 0);
    if (tid == 0) TS(28 + wg);
    const uint64_t dk0 = mkdesc(sb + SM_K, 128, 256, 0);
    const uint64_t dv0 = mkdesc(sb + SM_ONES - 256, 128, 256, 0);
    float o[12], s[32];
    uint32_t q[4], p0[16], p1[16];
    if (lds32(sb + SM_MISC + 4 * M_FAST)) {
      uint32_t mlo = 0x007F007Fu, mhi = 0xFF80FF80u;
      asm volatile("" : "+r"(mlo), "+r"(mhi));
      uint64_t dk = dk0, dv = dv0;
#define STEP(PIN, POUT) { wg_fence(); issue_qk(s, q, dk); dk += 128; wg_commit(); issue_pv(o, PIN, dv); wg_commit(); \
                          wg_wait<1>(); regfence(s); softmax_step(s, POUT, mlo, mhi); wg_wait<0>(); }
#pragma unroll 1
      for (int sg = wg * 8; sg < wg * 8 + 8; sg++) {
        const int tau = sg / 3, seg = sg - tau * 3;
        int n2 = seg == 1 ? 6 : 5;
#pragma unroll
        for (int k = 0; k < NP / 2; k++) s[k] = MAGIC_C;
        if (sg == wg * 8 || seg == 0) {
          const int j0 = seg == 0 ? 0 : (seg == 1 ? 10 : 22);
          dk = dk0 + 128 * j0;
          dv = dv0 + VSTEP * (4 * j0);
          const uint4 qv = lds128(sb + SM_Q + tau * 2048 + tid * 16);
          q[0] = qv.x; q[1] = qv.y; q[2] = qv.z; q[3] = qv.w;
#pragma unroll
          for (int k = 0; k < 12; k++) o[k] = 0.f;
          regfence(o); regfence(s);
          wg_fence(); issue_qk(s, q, dk); dk += 128; wg_commit();
          wg_wait<0>(); regfence(s);
          softmax_step(s, p0, mlo, mhi);
          STEP(p0, p1);
          n2--;
        }
        regfence(s);
#pragma unroll 1
        for (; n2 > 0; n2--) { STEP(p1, p0); STEP(p0, p1); }
        if (sg == wg * 8 + 7 || seg == 2) {
          wg_fence(); issue_pv(o, p1, dv); wg_commit();
          wg_wait<0>(); regfence(o);
          if (sg == 8 || sg == 17) {
            float4* pp = g_part + (blockIdx.x * 2 + (wg - 1)) * 384 + tid;
            pp[0] = make_float4(o[0], o[1], o[2], o[3]); pp[128] = make_float4(o[4], o[5], o[6], o[7]); pp[256] = make_float4(o[8], o[9], o[10], o[11]);
            __threadfence_block();
            bar_arrive(5 + wg, 256);
          } else {
            if (sg == 7 || sg == 15) {
              bar_sync(6 + wg, 256);
              const float4* pp = g_part + (blockIdx.x * 2 + wg) * 384 + tid;
              const float4 a = pp[0], b = pp[128], c = pp[256];
              o[0] += a.x; o[1] += a.y; o[2] += a.z; o[3] += a.w; o[4] += b.x; o[6] += b.z; o[8] += c.x; o[9] += c.y; o[10] += c.z; o[11] += c.w;
            }
            store_o_tile(o, bi, bj, tau, tid, sb);
          }
        }
      }
#undef STEP
    } else {
      mbar_wait(BAR(B_KFB), 0);
      constexpr float SC = 0.25f * 1.4426950408889634f;
#pragma unroll 1
      for (int tau = wg * 3; tau < wg * 3 + 3 && tau < 8; tau++) {
        const uint4 qv = lds128(sb + SM_Q + tau * 2048 + tid * 16);
        float m0 = -INFINITY, m1 = -INFINITY;
#pragma unroll
        for (int k = 0; k < 12; k++) o[k] = 0.f;
        uint64_t dv = dv0;
#pragma unroll 1
        for (int j = 0; j < 32; j++) {
          regfence(s);
          wg_fence(); wg_qkb_n64<0, 0, 32>(s, qv.x, qv.y, qv.z, qv.w, dk0 + 128 * j); wg_commit();
          wg_wait<0>(); regfence(s);
          float x0 = m0, x1 = m1;
#pragma unroll
          for (int k = 0; k < 32; k++) { s[k] *= SC; if (k & 2) x1 = fmaxf(x1, s[k]); else x0 = fmaxf(x0, s[k]); }
          x0 = fmaxf(x0, __shfl_xor_sync(0xffffffffu, x0, 1)); x0 = fmaxf(x0, __shfl_xor_sync(0xffffffffu, x0, 2));
          x1 = fmaxf(x1, __shfl_xor_sync(0xffffffffu, x1, 1)); x1 = fmaxf(x1, __shfl_xor_sync(0xffffffffu, x1, 2));
          const float c0 = ex2(m0 - x0), c1 = ex2(m1 - x1);
          m0 = x0; m1 = x1;
#pragma unroll
          for (int k = 0; k < 12; k++) o[k] *= (k & 2) ? c1 : c0;
#pragma unroll
          for (int k = 0; k < 16; k++) { const float m = (k & 1) ? m1 : m0; p0[k] = exp_mufu(s[2 * k] - m, s[2 * k + 1] - m); }
          regfence(o);
          wg_fence(); issue_pv(o, p0, dv); wg_commit();
          wg_wait<0>(); regfence(o);
        }
        store_o_tile(o, bi, bj, tau, tid, sb);
      }
    }
    fence_async();
    bar_sync(1 + wg, 128);
    if (tid == 0) { red_release(&g_ocnt[bi * 32]); TS(31 + wg); }
  }
  __syncwarp();
  asm volatile("barrier.cluster.arrive.relaxed;" ::: "memory");
  asm volatile("barrier.cluster.wait;" ::: "memory");
}

typedef CUresult (*EncodeFn)(CUtensorMap*, CUtensorMapDataType, cuuint32_t, void*, const cuuint64_t*, const cuuint64_t*,
                             const cuuint32_t*, const cuuint32_t*, CUtensorMapInterleave, CUtensorMapSwizzle,
                             CUtensorMapL2promotion, CUtensorMapFloatOOBfill);

void make_map(EncodeFn enc, CUtensorMap* tm, const void* base, uint64_t cols, uint64_t rows, uint32_t bc, uint32_t br, CUtensorMapSwizzle sw) {
  cuuint64_t gd[2] = {cols, rows};
  cuuint64_t gs[1] = {cols * 2};
  cuuint32_t bd[2] = {bc, br};
  cuuint32_t es[2] = {1, 1};
  enc(tm, CU_TENSOR_MAP_DATA_TYPE_BFLOAT16, 2, const_cast<void*>(base), gd, gs, bd, es, CU_TENSOR_MAP_INTERLEAVE_NONE, sw,
      CU_TENSOR_MAP_L2_PROMOTION_L2_128B, CU_TENSOR_MAP_FLOAT_OOB_FILL_NONE);
}

}

extern "C" void kernel_launch(void* const* d_in, const int* in_sizes, int n_in, void* d_out, int out_size) {
  (void)in_sizes; (void)n_in; (void)out_size;
  static EncodeFn enc = nullptr;
  if (!enc) {
    void* fn = nullptr;
    cudaDriverEntryPointQueryResult qr;
    cudaGetDriverEntryPoint("cuTensorMapEncodeTiled", &fn, cudaEnableDefault, &qr);
    enc = (EncodeFn)fn;
    cudaFuncSetAttribute(fused_kernel, cudaFuncAttributeMaxDynamicSharedMemorySize, SMEM_BYTES);
  }
  CUtensorMap tx, tq, tk, tv, tin, tsp, tout, to;
  make_map(enc, &tx, d_in[0], 512, 2048, 64, 64, CU_TENSOR_MAP_SWIZZLE_128B);
  make_map(enc, &tq, d_in[1], 512, 512, 64, 64, CU_TENSOR_MAP_SWIZZLE_128B);
  make_map(enc, &tk, d_in[2], 16, 512, 16, 64, CU_TENSOR_MAP_SWIZZLE_32B);
  make_map(enc, &tv, d_in[3], 16, 512, 16, 64, CU_TENSOR_MAP_SWIZZLE_32B);
  make_map(enc, &to, d_in[4], 512, 512, 64, 64, CU_TENSOR_MAP_SWIZZLE_128B);
  make_map(enc, &tin, d_in[6], 1376, 512, 32, 64, CU_TENSOR_MAP_SWIZZLE_64B);
  make_map(enc, &tsp, d_in[7], 2048, 2048, 64, 64, CU_TENSOR_MAP_SWIZZLE_128B);
  make_map(enc, &tout, d_in[9], 512, 688, 64, 64, CU_TENSOR_MAP_SWIZZLE_128B);
  Params prm;
  prm.gate_w = (const __nv_bfloat16*)d_in[10];
  prm.b_sp = (const __nv_bfloat16*)d_in[8];
  prm.w_sp = (const __nv_bfloat16*)d_in[7];
  prm.w_out = (const __nv_bfloat16*)d_in[9];
  prm.wo = (const __nv_bfloat16*)d_in[4];
  prm.out = (__nv_bfloat16*)d_out;
  fused_kernel<<<NCTA, NTHREADS, SMEM_BYTES>>>(tx, tq, tk, tv, tin, tsp, tout, to, prm);
}
```

```cpp
#include <cuda_runtime.h>
#include <cuda.h>
#include <cuda_bf16.h>
#include <cuda_fp16.h>
#include <stdint.h>

namespace {

constexpr int NCTA = 128;
constexpr int NTHREADS = 640;
constexpr int NP = 40;
constexpr int NM = 64 - NP;
constexpr int SPIN_LIMIT = 1 << 18;

constexpr uint32_t SM_K = 0;
constexpr uint32_t SM_ONES = 98304;
constexpr uint32_t KV_BYTES = 131328;
constexpr uint32_t SM_BAR = 131328;
constexpr uint32_t SM_RING = 132096;
constexpr uint32_t RSTAGE = 27648;
constexpr uint32_t WSLOT = 20480;
constexpr uint32_t SM_Q = 215040;
constexpr uint32_t SM_G = 231424;
constexpr uint32_t SM_MISC = 231936;
constexpr uint32_t SMEM_BYTES = 232448;

constexpr int B_XFULL = 0, B_XEMPTY = 8, B_WFULL = 16, B_WEMPTY = 32, B_KVFULL = 44, B_OFULL = 52, B_RFULL = 60,
              B_REMPTY = 63, B_KFB = 66, B_KSTAT = 67, B_DEC = 68, B_WOFULL = 69, B_EPOCH = 70, B_WKV = 71, B_COUNT = 72;
constexpr int M_EPOCH = 0, M_KN2 = 1, M_VOK = 2, M_FAST = 3, M_RED = 4;

__device__ uint4 g_kimg[KV_BYTES / 16];
__device__ uint4 g_kbf[65536 / 16];
__device__ float g_kvstat[NCTA * 16];
__device__ float2 g_lnstat[16 * 8 * 128];
__device__ uint4 g_z2n[8 * 32 * 11264 / 16];
__device__ uint4 g_z1[NCTA * 11 * 128];
__device__ uint4 g_u[16 * 11 * 1024];
__device__ uint4 g_o[16 * 8 * 1024];
__device__ float4 g_part[NCTA * 2 * 3 * 128];
__device__ unsigned g_ticket;
__device__ unsigned g_kvcnt[32];
__device__ unsigned g_statcnt[32 * 32];
__device__ unsigned g_zflag[8 * 32];
__device__ unsigned g_ucnt[16 * 32];
__device__ unsigned g_ocnt[16 * 32];
#define TS(k) do { } while (0)

__device__ __forceinline__ void mbar_init(uint32_t a, uint32_t c) { asm volatile("mbarrier.init.shared::cta.b64 [%0], %1;" ::"r"(a), "r"(c) : "memory"); }
__device__ __forceinline__ void mbar_expect(uint32_t a, uint32_t b) { asm volatile("mbarrier.arrive.expect_tx.shared::cta.b64 _, [%0], %1;" ::"r"(a), "r"(b) : "memory"); }
__device__ __forceinline__ void mbar_arrive(uint32_t a) { asm volatile("mbarrier.arrive.shared::cta.b64 _, [%0];" ::"r"(a) : "memory"); }
__device__ __forceinline__ void mbar_arrive_both(uint32_t a) {
  asm volatile("{\n.reg .b32 ra;\nmapa.shared::cluster.u32 ra, %0, 0;\nmbarrier.arrive.shared::cluster.b64 _, [ra];\n"
               "mapa.shared::cluster.u32 ra, %0, 1;\nmbarrier.arrive.shared::cluster.b64 _, [ra];\n}" ::"r"(a) : "memory");
}
__device__ __forceinline__ void mbar_wait(uint32_t a, uint32_t ph) {
  uint32_t ok;
#pragma unroll 1
  for (int n = 0; n < SPIN_LIMIT; n++) {
    asm volatile("{\n.reg .pred p;\nmbarrier.try_wait.parity.shared::cta.b64 p, [%1], %2;\nselp.u32 %0, 1, 0, p;\n}" : "=r"(ok) : "r"(a), "r"(ph) : "memory");
    if (ok) break;
  }
}
__device__ __forceinline__ void tma2d(uint32_t dst, const CUtensorMap* tm, int c0, int c1, uint32_t bar) {
  asm volatile("cp.async.bulk.tensor.2d.shared::cluster.global.mbarrier::complete_tx::bytes [%0], [%1, {%3, %4}], [%2];"
               ::"r"(dst), "l"(tm), "r"(bar), "r"(c0), "r"(c1) : "memory");
}
__device__ __forceinline__ void tma2d_mc(uint32_t dst, const CUtensorMap* tm, int c0, int c1, uint32_t bar) {
  asm volatile("cp.async.bulk.tensor.2d.shared::cluster.global.mbarrier::complete_tx::bytes.multicast::cluster [%0], [%1, {%3, %4}], [%2], %5;"
               ::"r"(dst), "l"(tm), "r"(bar), "r"(c0), "r"(c1), "h"((uint16_t)3) : "memory");
}
__device__ __forceinline__ void bulk(uint32_t dst, const void* src, uint32_t bytes, uint32_t bar) {
  asm volatile("cp.async.bulk.shared::cluster.global.mbarrier::complete_tx::bytes [%0], [%1], %2, [%3];"
               ::"r"(dst), "l"(src), "r"(bytes), "r"(bar) : "memory");
}
__device__ __forceinline__ void bulk_mc(uint32_t dst, const void* src, uint32_t bytes, uint32_t bar) {
  asm volatile("cp.async.bulk.shared::cluster.global.mbarrier::complete_tx::bytes.multicast::cluster [%0], [%1], %2, [%3], %4;"
               ::"r"(dst), "l"(src), "r"(bytes), "r"(bar), "h"((uint16_t)3) : "memory");
}
__device__ __forceinline__ void l2_prefetch(const void* src, uint32_t bytes) { asm volatile("cp.async.bulk.prefetch.L2.global [%0], %1;" ::"l"(src), "r"(bytes) : "memory"); }
__device__ __forceinline__ void fence_async() { asm volatile("fence.proxy.async.global;" ::: "memory"); }
__device__ __forceinline__ void fence_async_smem() { asm volatile("fence.proxy.async.shared::cta;" ::: "memory"); }
__device__ __forceinline__ void bar_sync(int id, int n) { asm volatile("bar.sync %0, %1;" ::"r"(id), "r"(n) : "memory"); }
__device__ __forceinline__ void bar_arrive(int id, int n) { asm volatile("bar.arrive %0, %1;" ::"r"(id), "r"(n) : "memory"); }
__device__ __forceinline__ void red_release(unsigned* p) { asm volatile("red.release.gpu.global.add.u32 [%0], 1;" ::"l"(p) : "memory"); }
__device__ __forceinline__ void st_release(unsigned* p, unsigned v) { asm volatile("st.release.gpu.global.u32 [%0], %1;" ::"l"(p), "r"(v) : "memory"); }
__device__ __forceinline__ unsigned ld_acquire(const unsigned* p) { unsigned v; asm volatile("ld.acquire.gpu.global.u32 %0, [%1];" : "=r"(v) : "l"(p) : "memory"); return v; }
__device__ __forceinline__ void wait_ge(const unsigned* p, unsigned target) {
#pragma unroll 1
  for (int n = 0; n < SPIN_LIMIT; n++) {
    if ((int)(ld_acquire(p) - target) >= 0) break;
    __nanosleep(20);
  }
}
__device__ __forceinline__ void wg_fence() { asm volatile("wgmma.fence.sync.aligned;" ::: "memory"); }
__device__ __forceinline__ void wg_commit() { asm volatile("wgmma.commit_group.sync.aligned;" ::: "memory"); }
template <int N> __device__ __forceinline__ void wg_wait() { asm volatile("wgmma.wait_group.sync.aligned %0;" ::"n"(N) : "memory"); }
template <int n> __device__ __forceinline__ void regfence(float (&d)[n]) {
#pragma unroll
  for (int i = 0; i < n; i++) asm volatile("" : "+f"(d[i])::"memory");
}
__device__ __forceinline__ uint64_t mkdesc(uint32_t addr, uint32_t lbo, uint32_t sbo, int swz) {
  return (uint64_t)((addr & 0x3FFFF) >> 4) | ((uint64_t)(lbo >> 4) << 16) | ((uint64_t)(sbo >> 4) << 32) | ((uint64_t)swz << 62);
}
__device__ __forceinline__ uint32_t pack_bf16(float lo, float hi) { uint32_t r; asm("cvt.rn.bf16x2.f32 %0, %1, %2;" : "=r"(r) : "f"(hi), "f"(lo)); return r; }
__device__ __forceinline__ uint32_t pack_f16(float lo, float hi) { uint32_t r; asm("cvt.rn.f16x2.f32 %0, %1, %2;" : "=r"(r) : "f"(hi), "f"(lo)); return r; }
__device__ __forceinline__ float bf_lo(uint32_t v) { return __uint_as_float(v << 16); }
__device__ __forceinline__ float bf_hi(uint32_t v) { return __uint_as_float(v & 0xFFFF0000u); }
__device__ __forceinline__ float ex2(float x) { float r; asm("ex2.approx.ftz.f32 %0, %1;" : "=f"(r) : "f"(x)); return r; }
__device__ __forceinline__ float gelu_tanh(float x) {
  float u = x * fmaf(x * x, 0.0356774081f, 0.7978845608f), t;
  asm("tanh.approx.f32 %0, %1;" : "=f"(t) : "f"(u));
  float h = 0.5f * x;
  return fmaf(h, t, h);
}
__device__ __forceinline__ void sts32(uint32_t a, uint32_t v) { asm volatile("st.shared.u32 [%0], %1;" ::"r"(a), "r"(v) : "memory"); }
__device__ __forceinline__ void sts16(uint32_t a, uint16_t v) { asm volatile("st.shared.u16 [%0], %1;" ::"r"(a), "h"(v) : "memory"); }
__device__ __forceinline__ void sts128(uint32_t a, uint32_t x, uint32_t y, uint32_t z, uint32_t w) { asm volatile("st.shared.v4.u32 [%0], {%1,%2,%3,%4};" ::"r"(a), "r"(x), "r"(y), "r"(z), "r"(w) : "memory"); }
__device__ __forceinline__ uint32_t lds32(uint32_t a) { uint32_t v; asm volatile("ld.shared.u32 %0, [%1];" : "=r"(v) : "r"(a) : "memory"); return v; }
__device__ __forceinline__ float ldsf(uint32_t a) { return __uint_as_float(lds32(a)); }
__device__ __forceinline__ uint4 lds128(uint32_t a) { uint4 v; asm volatile("ld.shared.v4.u32 {%0,%1,%2,%3}, [%4];" : "=r"(v.x), "=r"(v.y), "=r"(v.z), "=r"(v.w) : "r"(a) : "memory"); return v; }

template<int OFF, int TOT> __device__ __forceinline__ void wg_ss_n88(float (&d)[TOT], uint64_t da, uint64_t db) {
  asm volatile("wgmma.mma_async.sync.aligned.m64n88k16.f32.bf16.bf16 {%0, %1, %2, %3, %4, %5, %6, %7, %8, %9, %10, %11, %12, %13, %14, %15, %16, %17, %18, %19, %20, %21, %22, %23, %24, %25, %26, %27, %28, %29, %30, %31, %32, %33, %34, %35, %36, %37, %38, %39, %40, %41, %42, %43}, %44, %45, 1, 1, 1, 0, 1;"
    : "+f"(d[OFF+0]), "+f"(d[OFF+1]), "+f"(d[OFF+2]), "+f"(d[OFF+3]), "+f"(d[OFF+4]), "+f"(d[OFF+5]), "+f"(d[OFF+6]), "+f"(d[OFF+7]),
      "+f"(d[OFF+8]), "+f"(d[OFF+9]), "+f"(d[OFF+10]), "+f"(d[OFF+11]), "+f"(d[OFF+12]), "+f"(d[OFF+13]), "+f"(d[OFF+14]), "+f"(d[OFF+15]),
      "+f"(d[OFF+16]), "+f"(d[OFF+17]), "+f"(d[OFF+18]), "+f"(d[OFF+19]), "+f"(d[OFF+20]), "+f"(d[OFF+21]), "+f"(d[OFF+22]), "+f"(d[OFF+23]),
      "+f"(d[OFF+24]), "+f"(d[OFF+25]), "+f"(d[OFF+26]), "+f"(d[OFF+27]), "+f"(d[OFF+28]), "+f"(d[OFF+29]), "+f"(d[OFF+30]), "+f"(d[OFF+31]),
      "+f"(d[OFF+32]), "+f"(d[OFF+33]), "+f"(d[OFF+34]), "+f"(d[OFF+35]), "+f"(d[OFF+36]), "+f"(d[OFF+37]), "+f"(d[OFF+38]), "+f"(d[OFF+39]),
      "+f"(d[OFF+40]), "+f"(d[OFF+41]), "+f"(d[OFF+42]), "+f"(d[OFF+43])
    : "l"(da), "l"(db));
}
template<int OFF, int TOT> __device__ __forceinline__ void wg_ss_n64(float (&d)[TOT], uint64_t da, uint64_t db) {
  asm volatile("wgmma.mma_async.sync.aligned.m64n64k16.f32.bf16.bf16 {%0, %1, %2, %3, %4, %5, %6, %7, %8, %9, %10, %11, %12, %13, %14, %15, %16, %17, %18, %19, %20, %21, %22, %23, %24, %25, %26, %27, %28, %29, %30, %31}, %32, %33, 1, 1, 1, 0, 1;"
    : "+f"(d[OFF+0]), "+f"(d[OFF+1]), "+f"(d[OFF+2]), "+f"(d[OFF+3]), "+f"(d[OFF+4]), "+f"(d[OFF+5]), "+f"(d[OFF+6]), "+f"(d[OFF+7]),
      "+f"(d[OFF+8]), "+f"(d[OFF+9]), "+f"(d[OFF+10]), "+f"(d[OFF+11]), "+f"(d[OFF+12]), "+f"(d[OFF+13]), "+f"(d[OFF+14]), "+f"(d[OFF+15]),
      "+f"(d[OFF+16]), "+f"(d[OFF+17]), "+f"(d[OFF+18]), "+f"(d[OFF+19]), "+f"(d[OFF+20]), "+f"(d[OFF+21]), "+f"(d[OFF+22]), "+f"(d[OFF+23]),
      "+f"(d[OFF+24]), "+f"(d[OFF+25]), "+f"(d[OFF+26]), "+f"(d[OFF+27]), "+f"(d[OFF+28]), "+f"(d[OFF+29]), "+f"(d[OFF+30]), "+f"(d[OFF+31])
    : "l"(da), "l"(db));
}
template<int OFF, int TOT> __device__ __forceinline__ void wg_ss_n32t(float (&d)[TOT], uint64_t da, uint64_t db) {
  asm volatile("wgmma.mma_async.sync.aligned.m64n32k16.f32.bf16.bf16 {%0, %1, %2, %3, %4, %5, %6, %7, %8, %9, %10, %11, %12, %13, %14, %15}, %16, %17, 1, 1, 1, 1, 0;"
    : "+f"(d[OFF+0]), "+f"(d[OFF+1]), "+f"(d[OFF+2]), "+f"(d[OFF+3]), "+f"(d[OFF+4]), "+f"(d[OFF+5]), "+f"(d[OFF+6]), "+f"(d[OFF+7]),
      "+f"(d[OFF+8]), "+f"(d[OFF+9]), "+f"(d[OFF+10]), "+f"(d[OFF+11]), "+f"(d[OFF+12]), "+f"(d[OFF+13]), "+f"(d[OFF+14]), "+f"(d[OFF+15])
    : "l"(da), "l"(db));
}
template<int SCD, int OFF, int TOT> __device__ __forceinline__ void wg_qk_n16(float (&d)[TOT], uint32_t a0, uint32_t a1, uint32_t a2, uint32_t a3, uint64_t db) {
  asm volatile("wgmma.mma_async.sync.aligned.m64n16k16.f32.f16.f16 {%0, %1, %2, %3, %4, %5, %6, %7}, {%8,%9,%10,%11}, %12, %13, 1, 1, 0;"
    : "+f"(d[OFF+0]), "+f"(d[OFF+1]), "+f"(d[OFF+2]), "+f"(d[OFF+3]), "+f"(d[OFF+4]), "+f"(d[OFF+5]), "+f"(d[OFF+6]), "+f"(d[OFF+7])
    : "r"(a0), "r"(a1), "r"(a2), "r"(a3), "l"(db), "n"(SCD));
}
template<int SCD, int OFF, int TOT> __device__ __forceinline__ void wg_qk_n24(float (&d)[TOT], uint32_t a0, uint32_t a1, uint32_t a2, uint32_t a3, uint64_t db) {
  asm volatile("wgmma.mma_async.sync.aligned.m64n24k16.f32.f16.f16 {%0, %1, %2, %3, %4, %5, %6, %7, %8, %9, %10, %11}, {%12,%13,%14,%15}, %16, %17, 1, 1, 0;"
    : "+f"(d[OFF+0]), "+f"(d[OFF+1]), "+f"(d[OFF+2]), "+f"(d[OFF+3]), "+f"(d[OFF+4]), "+f"(d[OFF+5]), "+f"(d[OFF+6]), "+f"(d[OFF+7]),
      "+f"(d[OFF+8]), "+f"(d[OFF+9]), "+f"(d[OFF+10]), "+f"(d[OFF+11])
    : "r"(a0), "r"(a1), "r"(a2), "r"(a3), "l"(db), "n"(SCD));
}
template<int SCD, int OFF, int TOT> __device__ __forceinline__ void wg_qk_n32(float (&d)[TOT], uint32_t a0, uint32_t a1, uint32_t a2, uint32_t a3, uint64_t db) {
  asm volatile("wgmma.mma_async.sync.aligned.m64n32k16.f32.f16.f16 {%0, %1, %2, %3, %4, %5, %6, %7, %8, %9, %10, %11, %12, %13, %14, %15}, {%16,%17,%18,%19}, %20, %21, 1, 1, 0;"
    : "+f"(d[OFF+0]), "+f"(d[OFF+1]), "+f"(d[OFF+2]), "+f"(d[OFF+3]), "+f"(d[OFF+4]), "+f"(d[OFF+5]), "+f"(d[OFF+6]), "+f"(d[OFF+7]),
      "+f"(d[OFF+8]), "+f"(d[OFF+9]), "+f"(d[OFF+10]), "+f"(d[OFF+11]), "+f"(d[OFF+12]), "+f"(d[OFF+13]), "+f"(d[OFF+14]), "+f"(d[OFF+15])
    : "r"(a0), "r"(a1), "r"(a2), "r"(a3), "l"(db), "n"(SCD));
}
template<int SCD, int OFF, int TOT> __device__ __forceinline__ void wg_qk_n40(float (&d)[TOT], uint32_t a0, uint32_t a1, uint32_t a2, uint32_t a3, uint64_t db) {
  asm volatile("wgmma.mma_async.sync.aligned.m64n40k16.f32.f16.f16 {%0, %1, %2, %3, %4, %5, %6, %7, %8, %9, %10, %11, %12, %13, %14, %15, %16, %17, %18, %19}, {%20,%21,%22,%23}, %24, %25, 1, 1, 0;"
    : "+f"(d[OFF+0]), "+f"(d[OFF+1]), "+f"(d[OFF+2]), "+f"(d[OFF+3]), "+f"(d[OFF+4]), "+f"(d[OFF+5]), "+f"(d[OFF+6]), "+f"(d[OFF+7]),
      "+f"(d[OFF+8]), "+f"(d[OFF+9]), "+f"(d[OFF+10]), "+f"(d[OFF+11]), "+f"(d[OFF+12]), "+f"(d[OFF+13]), "+f"(d[OFF+14]), "+f"(d[OFF+15]),
      "+f"(d[OFF+16]), "+f"(d[OFF+17]), "+f"(d[OFF+18]), "+f"(d[OFF+19])
    : "r"(a0), "r"(a1), "r"(a2), "r"(a3), "l"(db), "n"(SCD));
}
template<int SCD, int OFF, int TOT> __device__ __forceinline__ void wg_qk_n48(float (&d)[TOT], uint32_t a0, uint32_t a1, uint32_t a2, uint32_t a3, uint64_t db) {
  asm volatile("wgmma.mma_async.sync.aligned.m64n48k16.f32.f16.f16 {%0, %1, %2, %3, %4, %5, %6, %7, %8, %9, %10, %11, %12, %13, %14, %15, %16, %17, %18, %19, %20, %21, %22, %23}, {%24,%25,%26,%27}, %28, %29, 1, 1, 0;"
    : "+f"(d[OFF+0]), "+f"(d[OFF+1]), "+f"(d[OFF+2]), "+f"(d[OFF+3]), "+f"(d[OFF+4]), "+f"(d[OFF+5]), "+f"(d[OFF+6]), "+f"(d[OFF+7]),
      "+f"(d[OFF+8]), "+f"(d[OFF+9]), "+f"(d[OFF+10]), "+f"(d[OFF+11]), "+f"(d[OFF+12]), "+f"(d[OFF+13]), "+f"(d[OFF+14]), "+f"(d[OFF+15]),
      "+f"(d[OFF+16]), "+f"(d[OFF+17]), "+f"(d[OFF+18]), "+f"(d[OFF+19]), "+f"(d[OFF+20]), "+f"(d[OFF+21]), "+f"(d[OFF+22]), "+f"(d[OFF+23])
    : "r"(a0), "r"(a1), "r"(a2), "r"(a3), "l"(db), "n"(SCD));
}
template<int SCD, int OFF, int TOT> __device__ __forceinline__ void wg_pv_n24(float (&d)[TOT], uint32_t a0, uint32_t a1, uint32_t a2, uint32_t a3, uint64_t db) {
  asm volatile("wgmma.mma_async.sync.aligned.m64n24k16.f32.bf16.bf16 {%0, %1, %2, %3, %4, %5, %6, %7, %8, %9, %10, %11}, {%12,%13,%14,%15}, %16, %17, 1, 1, 1;"
    : "+f"(d[OFF+0]), "+f"(d[OFF+1]), "+f"(d[OFF+2]), "+f"(d[OFF+3]), "+f"(d[OFF+4]), "+f"(d[OFF+5]), "+f"(d[OFF+6]), "+f"(d[OFF+7]),
      "+f"(d[OFF+8]), "+f"(d[OFF+9]), "+f"(d[OFF+10]), "+f"(d[OFF+11])
    : "r"(a0), "r"(a1), "r"(a2), "r"(a3), "l"(db), "n"(SCD));
}
template<int SCD, int OFF, int TOT> __device__ __forceinline__ void wg_qkb_n64(float (&d)[TOT], uint32_t a0, uint32_t a1, uint32_t a2, uint32_t a3, uint64_t db) {
  asm volatile("wgmma.mma_async.sync.aligned.m64n64k16.f32.bf16.bf16 {%0, %1, %2, %3, %4, %5, %6, %7, %8, %9, %10, %11, %12, %13, %14, %15, %16, %17, %18, %19, %20, %21, %22, %23, %24, %25, %26, %27, %28, %29, %30, %31}, {%32,%33,%34,%35}, %36, %37, 1, 1, 0;"
    : "+f"(d[OFF+0]), "+f"(d[OFF+1]), "+f"(d[OFF+2]), "+f"(d[OFF+3]), "+f"(d[OFF+4]), "+f"(d[OFF+5]), "+f"(d[OFF+6]), "+f"(d[OFF+7]),
      "+f"(d[OFF+8]), "+f"(d[OFF+9]), "+f"(d[OFF+10]), "+f"(d[OFF+11]), "+f"(d[OFF+12]), "+f"(d[OFF+13]), "+f"(d[OFF+14]), "+f"(d[OFF+15]),
      "+f"(d[OFF+16]), "+f"(d[OFF+17]), "+f"(d[OFF+18]), "+f"(d[OFF+19]), "+f"(d[OFF+20]), "+f"(d[OFF+21]), "+f"(d[OFF+22]), "+f"(d[OFF+23]),
      "+f"(d[OFF+24]), "+f"(d[OFF+25]), "+f"(d[OFF+26]), "+f"(d[OFF+27]), "+f"(d[OFF+28]), "+f"(d[OFF+29]), "+f"(d[OFF+30]), "+f"(d[OFF+31])
    : "r"(a0), "r"(a1), "r"(a2), "r"(a3), "l"(db), "n"(SCD));
}
template<int N, int SCD, int OFF, int TOT> __device__ __forceinline__ void wg_qk(float (&d)[TOT], const uint32_t (&q)[4], uint64_t db) {
  if constexpr (N == 16) wg_qk_n16<SCD, OFF, TOT>(d, q[0], q[1], q[2], q[3], db);
  if constexpr (N == 24) wg_qk_n24<SCD, OFF, TOT>(d, q[0], q[1], q[2], q[3], db);
  if constexpr (N == 32) wg_qk_n32<SCD, OFF, TOT>(d, q[0], q[1], q[2], q[3], db);
  if constexpr (N == 40) wg_qk_n40<SCD, OFF, TOT>(d, q[0], q[1], q[2], q[3], db);
  if constexpr (N == 48) wg_qk_n48<SCD, OFF, TOT>(d, q[0], q[1], q[2], q[3], db);
}

__device__ __forceinline__ uint32_t exp_mufu(float a, float b) { return pack_bf16(ex2(a), ex2(b)); }
__device__ __forceinline__ uint32_t exp_poly(float a, float b, uint32_t mlo, uint32_t mhi) {
  uint32_t u = __byte_perm(__float_as_uint(a), __float_as_uint(b), 0x6521), mh, e, p;
  asm("lop3.b32 %0, %1, %2, 0x3F003F00, 0xEA;" : "=r"(mh) : "r"(u), "r"(mlo));
  asm("lop3.b32 %0, %1, %2, 0x00020002, 0xEA;" : "=r"(e) : "r"(u), "r"(mhi));
  asm("fma.rn.bf16x2 %0, %1, %2, %3;" : "=r"(p) : "r"(u), "r"(mh), "r"(e));
  return p;
}
constexpr float MAGIC_C = 48948.0625f;
constexpr float QSCALE = 0.25f * 1.4426950408889634f * 8.f;
constexpr float BOUND = 80.f;

__device__ __forceinline__ void softmax_step(const float (&s)[32], uint32_t (&p)[16], uint32_t mlo, uint32_t mhi) {
  constexpr int PP = NP / 4;
  int ip = 0, im = PP;
#pragma unroll
  for (int i = 0; i < 16; i++) {
    if (((i + 1) * PP / 16) > (i * PP / 16)) { p[ip] = exp_poly(s[2 * ip], s[2 * ip + 1], mlo, mhi); ip++; }
    else { p[im] = exp_mufu(s[2 * im], s[2 * im + 1]); im++; }
  }
}
constexpr uint64_t VSTEP = ((uint64_t)16 << 32) - 16;
__device__ __forceinline__ void issue_qk(float (&s)[32], const uint32_t (&q)[4], uint64_t dk) {
  wg_qk<NM, 0, NP / 2, 32>(s, q, dk + NP * 2);
  wg_qk<NP, 1, 0, 32>(s, q, dk);
}
__device__ __forceinline__ void issue_pv(float (&o)[12], const uint32_t (&p)[16], uint64_t& dv, uint64_t vstep) {
#pragma unroll
  for (int c = 0; c < 4; c++) { wg_pv_n24<1, 0, 12>(o, p[4 * c], p[4 * c + 1], p[4 * c + 2], p[4 * c + 3], dv); dv += vstep; }
}

struct Params {
  const __nv_bfloat16* gate_w;
  const __nv_bfloat16* b_sp;
  const __nv_bfloat16* w_sp;
  const __nv_bfloat16* w_out;
  const __nv_bfloat16* wo;
  const __nv_bfloat16* w_in;
  const __nv_bfloat16* wq;
  uint64_t vstep;
  uint32_t mlo, mhi;
  __nv_bfloat16* out;
};

__device__ __forceinline__ void store_o_tile(const float (&o)[12], int bi, int bj, int tau, int tid, uint32_t sb) {
  const int half = tau & 1, hh = tau >> 1, w = tid >> 5, g = (tid & 31) >> 2;
  const int r0 = half * 64 + w * 16 + g;
  const float f0 = __fdividef(ldsf(sb + SM_G + r0 * 4), o[4]), f1 = __fdividef(ldsf(sb + SM_G + (r0 + 8) * 4), o[6]);
  uint32_t* dst = reinterpret_cast<uint32_t*>(g_o) + (bi * 8 + bj) * 4096 + (half * 8 + w * 2) * 256 + hh * 64 + (tid & 31);
  dst[0] = pack_bf16(o[0] * f0, o[1] * f0);
  dst[32] = pack_bf16(o[8] * f0, o[9] * f0);
  dst[256] = pack_bf16(o[2] * f1, o[3] * f1);
  dst[288] = pack_bf16(o[10] * f1, o[11] * f1);
}

__global__ void __cluster_dims__(2, 1, 1) __launch_bounds__(NTHREADS, 1)
fused_kernel(const __grid_constant__ CUtensorMap tm_x, const __grid_constant__ CUtensorMap tm_wq,
             const __grid_constant__ CUtensorMap tm_wk, const __grid_constant__ CUtensorMap tm_wv,
             const __grid_constant__ CUtensorMap tm_win, const __grid_constant__ CUtensorMap tm_wsp,
             const __grid_constant__ CUtensorMap tm_wout, const __grid_constant__ CUtensorMap tm_wo, const Params prm) {
  extern __shared__ __align__(1024) uint8_t smem_raw[];
  const uint32_t sb = (uint32_t)__cvta_generic_to_shared(smem_raw);
  const int wg = __shfl_sync(0xffffffffu, (int)(threadIdx.x >> 7), 0);
  const int tid = threadIdx.x & 127;
  const int lane = threadIdx.x & 31;
  const int bi = blockIdx.x >> 3, bj = blockIdx.x & 7, rank = bj & 1;
  auto BAR = [&](int k) { return sb + SM_BAR + 8u * k; };

  if (threadIdx.x < B_COUNT) {
    const int k = threadIdx.x;
    uint32_t cnt = 1;
    if (k >= B_XEMPTY && k < B_XEMPTY + 8) cnt = 4;
    if (k >= B_WEMPTY && k < B_WEMPTY + 12) cnt = 2;
    if (k >= B_REMPTY && k < B_REMPTY + 3) cnt = 2;
    mbar_init(BAR(k), cnt);
    asm volatile("fence.mbarrier_init.release.cluster;" ::: "memory");
  }
  if (threadIdx.x == 512) {
    asm volatile("prefetch.tensormap [%0];" ::"l"(&tm_x) : "memory");
    asm volatile("prefetch.tensormap [%0];" ::"l"(rank ? &tm_wv : &tm_wk) : "memory");
    asm volatile("prefetch.tensormap [%0];" ::"l"(&tm_win) : "memory");
  }
  if (threadIdx.x == 576) {
    l2_prefetch(reinterpret_cast<const uint8_t*>(prm.w_in) + blockIdx.x * 11008, 11008);
    l2_prefetch(reinterpret_cast<const uint8_t*>(prm.wq) + blockIdx.x * 4096, 4096);
  }
  __syncthreads();
  asm volatile("barrier.cluster.arrive.relaxed.aligned;" ::: "memory");
  asm volatile("barrier.cluster.wait.acquire.aligned;" ::: "memory");

  if (wg == 4) {
    asm volatile("setmaxnreg.dec.sync.aligned.u32 24;");
    const int pw = __shfl_sync(0xffffffffu, tid >> 5, 0);
    if (pw == 0) {
      if (lane == 0) {
        TS(0);
        auto fill_w = [&](int f) {
          const uint32_t slot = sb + SM_RING + (f & 3) * WSLOT, bar = BAR(B_WFULL + f);
          const int k0 = (f & 7) * 64;
          if (f < 8) {
            mbar_expect(bar, 12288);
            for (int a = 0; a < 3; a++) tma2d(slot + a * 4096, &tm_win, 688 + 88 * bj + 32 * a, k0, bar);
          } else {
            mbar_expect(bar, 12288 + 8192);
            tma2d(slot + 12288, &tm_wq, 64 * bj, k0, bar);
            for (int a = 0; a < 3; a++) tma2d(slot + a * 4096, &tm_win, 88 * bj + 32 * a, k0, bar);
          }
        };
#pragma unroll 1
        for (int c = 0; c < 8; c++) {
          mbar_expect(BAR(B_XFULL + c), 16384);
          tma2d_mc(sb + SM_K + c * 16384 + rank * 8192, &tm_x, c * 64, bi * 128 + rank * 64, BAR(B_XFULL + c));
          if (c == 0) {
            mbar_expect(BAR(B_WKV), 16384);
            tma2d(sb + SM_Q, rank ? &tm_wv : &tm_wk, 0, 0, BAR(B_WKV));
            tma2d(sb + SM_Q + 8192, rank ? &tm_wv : &tm_wk, 0, 256, BAR(B_WKV));
          }
          if (c & 1) fill_w(c >> 1);
        }
        asm volatile("prefetch.tensormap [%0];" ::"l"(&tm_wq) : "memory");
        asm volatile("prefetch.tensormap [%0];" ::"l"(&tm_wsp) : "memory");
        asm volatile("prefetch.tensormap [%0];" ::"l"(&tm_wout) : "memory");
        asm volatile("prefetch.tensormap [%0];" ::"l"(&tm_wo) : "memory");
#pragma unroll 1
        for (int f = 4; f < 16; f++) {
          mbar_wait(BAR(B_WEMPTY + f - 4), 0);
          fill_w(f);
          if (f == 8) {
            const uint8_t* ws = reinterpret_cast<const uint8_t*>(prm.w_sp) + (size_t)blockIdx.x * 65536;
            for (int a = 0; a < 4; a++) l2_prefetch(ws + a * 16384, 16384);
            l2_prefetch(reinterpret_cast<const uint8_t*>(prm.w_out) + blockIdx.x * 5504, 5504);
            l2_prefetch(reinterpret_cast<const uint8_t*>(prm.wo) + blockIdx.x * 4096, 4096);
          }
        }
        TS(1);
        mbar_wait(BAR(B_XEMPTY + 7), 0);
        mbar_wait(BAR(B_EPOCH), 0);
      }
      __syncwarp();
      const unsigned ep1 = lds32(sb + SM_MISC + 4 * M_EPOCH) + 1;
      wait_ge(&g_zflag[bj * 32 + lane], ep1);
      __syncwarp();
      if (lane == 0) {
        fence_async();
        TS(2);
        int st = 0, ph = 1;
#pragma unroll 1
        for (int n = 0; n < 43; n++) {
          const uint32_t stg = sb + SM_RING + st * RSTAGE, bar = BAR(B_RFULL + st);
          if (n >= 3) mbar_wait(BAR(B_REMPTY + st), ph);
          if (n < 32) {
            mbar_expect(bar, 16384 + 11264);
            tma2d_mc(stg + rank * 8192, &tm_wsp, n * 64, bi * 128 + rank * 64, bar);
            bulk(stg + 16384, reinterpret_cast<const uint8_t*>(g_z2n) + (bj * 32 + n) * 11264, 11264, bar);
          } else {
            const int c = n - 32;
            mbar_expect(bar, 16384 + 8192);
            tma2d(stg + 16384, &tm_wout, 64 * bj, c * 64, bar);
            if (c == 0) { wait_ge(&g_ucnt[bi * 32], ep1 * 8); fence_async(); TS(3); }
            bulk_mc(stg + rank * 8192, reinterpret_cast<const uint8_t*>(g_u) + (bi * 11 + c) * 16384 + rank * 8192, 8192, bar);
          }
          if (++st == 3) { st = 0; ph ^= 1; }
        }
#pragma unroll 1
        for (int n = 0; n < 3; n++) {
          mbar_wait(BAR(B_REMPTY + st), ph);
          if (++st == 3) { st = 0; ph ^= 1; }
        }
        mbar_expect(BAR(B_WOFULL), 65536);
#pragma unroll 1
        for (int c = 0; c < 8; c++) tma2d(sb + SM_RING + c * 8192, &tm_wo, 64 * bj, c * 64, BAR(B_WOFULL));
        TS(4);
        wait_ge(&g_ocnt[bi * 32], ep1 * 24);
        fence_async();
        TS(5);
#pragma unroll 1
        for (int c = 0; c < 8; c++) {
          mbar_expect(BAR(B_OFULL + c), 16384);
          bulk_mc(sb + SM_K + c * 16384 + rank * 8192, reinterpret_cast<const uint8_t*>(g_o) + (bi * 8 + c) * 16384 + rank * 8192, 8192, BAR(B_OFULL + c));
        }
      }
    } else if (pw == 1) {
      unsigned ep = 0;
      if (lane == 0) {
        ep = atomicAdd(&g_ticket, 1u) / NCTA;
        sts32(sb + SM_MISC + 4 * M_EPOCH, ep);
        mbar_arrive(BAR(B_EPOCH));
        wait_ge(&g_kvcnt[0], (ep + 1) * NCTA);
        TS(6);
      }
      __syncwarp();
      float kn2 = fmaxf(__ldcg(&g_kvstat[(4 * lane) * 16]), __ldcg(&g_kvstat[(4 * lane + 2) * 16]));
      float4 vq = make_float4(0.f, 0.f, 0.f, 0.f);
#pragma unroll
      for (int h = 0; h < 2; h++) {
        float4 a[4];
#pragma unroll
        for (int p = 0; p < 4; p++) a[p] = __ldcg(reinterpret_cast<const float4*>(g_kvstat) + (2 * ((lane >> 2) * 8 + h * 4 + p) + 1) * 4 + (lane & 3));
#pragma unroll
        for (int p = 0; p < 4; p++) { vq.x = fmaxf(vq.x, a[p].x); vq.y = fmaxf(vq.y, a[p].y); vq.z = fmaxf(vq.z, a[p].z); vq.w = fmaxf(vq.w, a[p].w); }
      }
#pragma unroll
      for (int m = 16; m > 2; m >>= 1) {
        vq.x = fmaxf(vq.x, __shfl_xor_sync(0xffffffffu, vq.x, m)); vq.y = fmaxf(vq.y, __shfl_xor_sync(0xffffffffu, vq.y, m));
        vq.z = fmaxf(vq.z, __shfl_xor_sync(0xffffffffu, vq.z, m)); vq.w = fmaxf(vq.w, __shfl_xor_sync(0xffffffffu, vq.w, m));
      }
      const float vlo = fminf(fminf(vq.x, vq.y), fminf(vq.z, vq.w)), vhi = fmaxf(fmaxf(vq.x, vq.y), fmaxf(vq.z, vq.w));
#pragma unroll
      for (int m = 16; m > 0; m >>= 1) kn2 = fmaxf(kn2, __shfl_xor_sync(0xffffffffu, kn2, m));
      const bool vok = __all_sync(0xffffffffu, vlo >= 9.5367431640625e-07f && vhi <= 1073741824.f);
      if (lane == 0) {
        sts32(sb + SM_MISC + 4 * M_KN2, __float_as_uint(kn2));
        sts32(sb + SM_MISC + 4 * M_VOK, vok ? 1u : 0u);
        mbar_arrive(BAR(B_KSTAT));
        fence_async();
#pragma unroll 1
        for (int c = 0; c < 8; c++) {
          const uint32_t bytes = c == 7 ? 16640 : 16384, hb = bytes / 2, off = c * 16384 + rank * hb;
          mbar_wait(BAR(B_XEMPTY + c), 0);
          mbar_expect(BAR(B_KVFULL + c), bytes);
          bulk_mc(sb + SM_K + off, reinterpret_cast<const uint8_t*>(g_kimg) + off, hb, BAR(B_KVFULL + c));
        }
        TS(7);
        mbar_wait(BAR(B_DEC), 0);
        if (!lds32(sb + SM_MISC + 4 * M_FAST)) {
          for (int c = 0; c < 4; c++) mbar_wait(BAR(B_KVFULL + c), 0);
          mbar_expect(BAR(B_KFB), 65536);
          for (int c = 0; c < 4; c++) bulk(sb + SM_K + c * 16384, reinterpret_cast<const uint8_t*>(g_kbf) + c * 16384, 16384, BAR(B_KFB));
        }
      }
    }
  } else if (wg == 3) {
    asm volatile("setmaxnreg.inc.sync.aligned.u32 120;");
    const int w = tid >> 5, g = lane >> 2, t4 = lane & 3;
    {
      float a0 = 0.f, a1 = 0.f;
      const uint32_t sW = sb + SM_RING + 4 * WSLOT;
      if (tid < 64) { const uint4 gv = __ldg(reinterpret_cast<const uint4*>(prm.gate_w) + tid); sts128(sW + tid * 16, gv.x, gv.y, gv.z, gv.w); }
      bar_sync(4, 128);
#pragma unroll 1
      for (int c = 0; c < 8; c++) {
        mbar_wait(BAR(B_XFULL + c), 0);
#pragma unroll
        for (int v = 0; v < 8; v++) {
          const uint4 xv = lds128(sb + SM_K + c * 16384 + tid * 128 + ((v ^ (tid & 7)) << 4));
          const uint4 gv = lds128(sW + (c * 8 + v) * 16);
          a0 = fmaf(bf_lo(xv.x), bf_lo(gv.x), a0); a1 = fmaf(bf_hi(xv.x), bf_hi(gv.x), a1);
          a0 = fmaf(bf_lo(xv.y), bf_lo(gv.y), a0); a1 = fmaf(bf_hi(xv.y), bf_hi(gv.y), a1);
          a0 = fmaf(bf_lo(xv.z), bf_lo(gv.z), a0); a1 = fmaf(bf_hi(xv.z), bf_hi(gv.z), a1);
          a0 = fmaf(bf_lo(xv.w), bf_lo(gv.w), a0); a1 = fmaf(bf_hi(xv.w), bf_hi(gv.w), a1);
        }
      }
      sts32(sb + SM_G + tid * 4, __float_as_uint(__fdividef(1.f, 1.f + __expf(-(a0 + a1)))));
      fence_async_smem();
      bar_sync(4, 128);
      bar_arrive(5, 512);
    }
    if (tid == 0) TS(8);
    float acc[88];
    {
#pragma unroll
      for (int k = 0; k < 88; k++) acc[k] = 0.f;
      regfence(acc);
#pragma unroll 1
      for (int c = 0; c < 8; c++) {
        mbar_wait(BAR(B_WFULL + 8 + c), 0);
        const uint64_t da = mkdesc(sb + SM_K + c * 16384, 16, 1024, 1);
        const uint64_t db = mkdesc(sb + SM_RING + (c & 3) * WSLOT, 4096, 512, 2);
        wg_fence();
#pragma unroll
        for (int k = 0; k < 4; k++) { wg_ss_n88<0, 88>(acc, da + 2 * k, db + 64 * k); wg_ss_n88<44, 88>(acc, da + 512 + 2 * k, db + 64 * k); }
        wg_commit();
        wg_wait<0>();
        if (tid == 0) { if (c < 4) mbar_arrive(BAR(B_WEMPTY + 8 + c)); mbar_arrive_both(BAR(B_XEMPTY + c)); }
      }
      regfence(acc);
      if (tid == 0) TS(9);
      uint4* z1p = g_z1 + blockIdx.x * 11 * 128 + tid;
#pragma unroll
      for (int q = 0; q < 11; q++) {
        uint4 v;
        v.x = pack_bf16(gelu_tanh(acc[8 * q + 0]), gelu_tanh(acc[8 * q + 1]));
        v.y = pack_bf16(gelu_tanh(acc[8 * q + 2]), gelu_tanh(acc[8 * q + 3]));
        v.z = pack_bf16(gelu_tanh(acc[8 * q + 4]), gelu_tanh(acc[8 * q + 5]));
        v.w = pack_bf16(gelu_tanh(acc[8 * q + 6]), gelu_tanh(acc[8 * q + 7]));
        z1p[q * 128] = v;
      }
    }
    if (tid == 0) TS(10);
    int st = 0, ph = 0;
    {
#pragma unroll
      for (int k = 0; k < 88; k++) acc[k] = 0.f;
      regfence(acc);
#pragma unroll 1
      for (int n = 0; n < 32; n++) {
        mbar_wait(BAR(B_RFULL + st), ph);
        const uint64_t da = mkdesc(sb + SM_RING + st * RSTAGE, 16, 1024, 1);
        const uint64_t db = mkdesc(sb + SM_RING + st * RSTAGE + 16384, 1408, 128, 0);
#pragma unroll
        for (int k = 0; k < 4; k++) {
          wg_fence();
          wg_ss_n88<0, 88>(acc, da + 2 * k, db + 176 * k);
          wg_ss_n88<44, 88>(acc, da + 512 + 2 * k, db + 176 * k);
          wg_commit();
          wg_wait<0>();
        }
        if (tid == 0) mbar_arrive_both(BAR(B_REMPTY + st));
        if (++st == 3) { st = 0; ph ^= 1; }
      }
      regfence(acc);
      if (tid == 0) TS(11);
      float bs[4], og[4];
#pragma unroll
      for (int r = 0; r < 4; r++) {
        const int row = (r >> 1) * 64 + w * 16 + (r & 1) * 8 + g;
        bs[r] = __bfloat162float(prm.b_sp[bi * 128 + row]);
        og[r] = 1.f - ldsf(sb + SM_G + row * 4);
      }
      const uint4* z1p = g_z1 + blockIdx.x * 11 * 128 + tid;
      uint32_t* up = reinterpret_cast<uint32_t*>(g_u) + bi * 11 * 4096 + w * 512 + lane;
#pragma unroll
      for (int q = 0; q < 11; q++) {
        const uint4 zv = z1p[q * 128];
        const uint32_t zz[4] = {zv.x, zv.y, zv.z, zv.w};
#pragma unroll
        for (int e = 0; e < 4; e++) {
          const int k = 8 * q + 2 * e, hf = k / 44, c8 = (k % 44) / 4, r8 = ((k % 44) >> 1) & 1, r = hf * 2 + r8;
          const int cb = 11 * bj + c8;
          uint32_t v = pack_bf16(bf_lo(zz[e]) * (acc[k] + bs[r]) * og[r], bf_hi(zz[e]) * (acc[k + 1] + bs[r]) * og[r]);
          if (c8 >= 9 && bj == 7) v = 0;
          up[(cb >> 3) * 4096 + (hf * 8 + r8) * 256 + (cb & 7) * 32] = v;
        }
      }
      fence_async();
      bar_sync(4, 128);
      if (tid == 0) red_release(&g_ucnt[bi * 32]);
    }
    if (tid == 0) TS(12);
    {
      float oc[64];
#pragma unroll
      for (int k = 0; k < 64; k++) oc[k] = 0.f;
      regfence(oc);
#pragma unroll 1
      for (int n = 0; n < 11; n++) {
        mbar_wait(BAR(B_RFULL + st), ph);
        const uint64_t da = mkdesc(sb + SM_RING + st * RSTAGE, 128, 1024, 0);
        const uint64_t db = mkdesc(sb + SM_RING + st * RSTAGE + 16384, 8192, 1024, 1);
#pragma unroll
        for (int k = 0; k < 4; k++) {
          wg_fence();
          wg_ss_n64<0, 64>(oc, da + 16 * k, db + 128 * k);
          wg_ss_n64<32, 64>(oc, da + 512 + 16 * k, db + 128 * k);
          wg_commit();
          wg_wait<0>();
        }
        if (tid == 0) mbar_arrive_both(BAR(B_REMPTY + st));
        if (++st == 3) { st = 0; ph ^= 1; }
      }
      if (tid == 0) TS(13);
      mbar_wait(BAR(B_WOFULL), 0);
#pragma unroll 1
      for (int c = 0; c < 8; c++) {
        mbar_wait(BAR(B_OFULL + c), 0);
        const uint64_t da = mkdesc(sb + SM_K + c * 16384, 128, 1024, 0);
        const uint64_t db = mkdesc(sb + SM_RING + c * 8192, 8192, 1024, 1);
        wg_fence();
#pragma unroll
        for (int k = 0; k < 4; k++) { wg_ss_n64<0, 64>(oc, da + 16 * k, db + 128 * k); wg_ss_n64<32, 64>(oc, da + 512 + 16 * k, db + 128 * k); }
        wg_commit();
      }
      wg_wait<0>();
      regfence(oc);
      if (tid == 0) TS(14);
      uint32_t* op = reinterpret_cast<uint32_t*>(prm.out) + (bi * 128 + w * 16 + g) * 256 + bj * 32 + t4;
#pragma unroll
      for (int k = 0; k < 64; k += 2) {
        const int hf = k / 32, c8 = (k % 32) / 4, r8 = (k >> 1) & 1;
        op[(hf * 64 + r8 * 8) * 256 + c8 * 4] = pack_bf16(oc[k], oc[k + 1]);
      }
      if (tid == 0) TS(15);
    }
  } else {
    asm volatile("setmaxnreg.inc.sync.aligned.u32 112;");
    const int w = tid >> 5, g = lane >> 2, t4 = lane & 3;
    if (wg < 2) {
      float acc[44];
#pragma unroll
      for (int k = 0; k < 44; k++) acc[k] = 0.f;
      regfence(acc);
#pragma unroll 1
      for (int c = 0; c < 8; c++) {
        mbar_wait(BAR(B_XFULL + c), 0);
        mbar_wait(BAR(B_WFULL + c), 0);
        const uint64_t da = mkdesc(sb + SM_K + c * 16384 + wg * 8192, 16, 1024, 1);
        const uint64_t db = mkdesc(sb + SM_RING + (c & 3) * WSLOT, 4096, 512, 2);
        wg_fence();
#pragma unroll
        for (int k = 0; k < 4; k++) wg_ss_n88<0, 44>(acc, da + 2 * k, db + 64 * k);
        wg_commit();
        wg_wait<0>();
        if (tid == 0) mbar_arrive(BAR(B_WEMPTY + c));
      }
      regfence(acc);
      if (tid == 0) TS(16 + wg);
      const bool last = bj == 7;
      float s0 = 0.f, s1 = 0.f;
#pragma unroll
      for (int k = 0; k < 44; k++) {
        acc[k] = gelu_tanh(acc[k]);
        if (k & 2) s1 += acc[k]; else s0 += acc[k];
      }
      s0 += __shfl_xor_sync(0xffffffffu, s0, 1); s0 += __shfl_xor_sync(0xffffffffu, s0, 2);
      s1 += __shfl_xor_sync(0xffffffffu, s1, 1); s1 += __shfl_xor_sync(0xffffffffu, s1, 2);
      const float inv_n = last ? (1.f / 72.f) : (1.f / 88.f);
      const float m0 = s0 * inv_n, m1 = s1 * inv_n;
      float v0 = 0.f, v1 = 0.f;
#pragma unroll
      for (int k = 0; k < 44; k++) {
        float d = acc[k] - ((k & 2) ? m1 : m0);
        if (k >= 36 && last) d = 0.f;
        if (k & 2) v1 = fmaf(d, d, v1); else v0 = fmaf(d, d, v0);
      }
      v0 += __shfl_xor_sync(0xffffffffu, v0, 1); v0 += __shfl_xor_sync(0xffffffffu, v0, 2);
      v1 += __shfl_xor_sync(0xffffffffu, v1, 1); v1 += __shfl_xor_sync(0xffffffffu, v1, 2);
      const int r0 = wg * 64 + w * 16 + g;
      if (t4 == 0) {
        g_lnstat[(bi * 8 + bj) * 128 + r0] = make_float2(m0, v0);
        g_lnstat[(bi * 8 + bj) * 128 + r0 + 8] = make_float2(m1, v1);
      }
      bar_sync(1 + wg, 128);
      mbar_wait(BAR(B_EPOCH), 0);
      const unsigned ep1 = lds32(sb + SM_MISC + 4 * M_EPOCH) + 1;
      if (tid == 0) {
        red_release(&g_statcnt[(bi * 2 + wg) * 32]);
        TS(18 + wg);
        wait_ge(&g_statcnt[(bi * 2 + wg) * 32], ep1 * 8);
      }
      bar_sync(1 + wg, 128);
      float mean[2], rstd[2];
#pragma unroll
      for (int r = 0; r < 2; r++) {
        const float2 a = __ldcg(&g_lnstat[(bi * 8 + 2 * t4) * 128 + r0 + 8 * r]);
        const float2 b = __ldcg(&g_lnstat[(bi * 8 + 2 * t4 + 1) * 128 + r0 + 8 * r]);
        const float nb = t4 == 3 ? 72.f : 88.f;
        float sm = fmaf(a.x, 88.f, b.x * nb);
        sm += __shfl_xor_sync(0xffffffffu, sm, 1); sm += __shfl_xor_sync(0xffffffffu, sm, 2);
        const float mu = sm * (1.f / 688.f);
        const float da = a.x - mu, db = b.x - mu;
        float m2 = a.y + b.y + 88.f * da * da + nb * db * db;
        m2 += __shfl_xor_sync(0xffffffffu, m2, 1); m2 += __shfl_xor_sync(0xffffffffu, m2, 2);
        mean[r] = mu;
        rstd[r] = rsqrtf(fmaf(m2, 1.f / 688.f, 1e-5f));
      }
      uint32_t* zp = reinterpret_cast<uint32_t*>(g_z2n) + (bj * 32 + bi * 2 + wg) * 2816 + w * 704 + lane;
#pragma unroll
      for (int k = 0; k < 44; k += 2) {
        const int r = (k >> 1) & 1, c8 = k >> 2;
        uint32_t v = pack_bf16((acc[k] - mean[r]) * rstd[r], (acc[k + 1] - mean[r]) * rstd[r]);
        if (c8 >= 9 && last) v = 0;
        zp[r * 352 + c8 * 32] = v;
      }
      fence_async();
      bar_sync(1 + wg, 128);
      if (tid == 0) { st_release(&g_zflag[bj * 32 + bi * 2 + wg], ep1); TS(20 + wg); }
    } else {
      const int pair = bi * 4 + (bj >> 1);
      {
        float kv[16];
#pragma unroll
        for (int k = 0; k < 16; k++) kv[k] = 0.f;
        regfence(kv);
        mbar_wait(BAR(B_WKV), 0);
#pragma unroll 1
        for (int c = 0; c < 8; c++) {
          mbar_wait(BAR(B_XFULL + c), 0);
          const uint64_t da = mkdesc(sb + SM_Q + c * 2048, 0, 256, 3);
          const uint64_t db = mkdesc(sb + SM_K + c * 16384 + (bj >> 1) * 4096, 16, 1024, 1);
          wg_fence();
#pragma unroll
          for (int k = 0; k < 4; k++) wg_ss_n32t<0, 16>(kv, da + 32 * k, db + 2 * k);
          wg_commit();
        }
        wg_wait<0>();
        regfence(kv);
        if (tid == 0) TS(22);
        const uint32_t sT = sb + SM_Q, sH = sb + SM_Q + 4096;
        bar_sync(3, 128);
        if (w == 0) {
#pragma unroll
          for (int k = 0; k < 16; k++) {
            const int tok = (k >> 2) * 8 + 2 * t4 + (k & 1), d = g + ((k >> 1) & 1) * 8;
            sts32(sT + (tok * 17 + d) * 4, __float_as_uint(__bfloat162float(__float2bfloat16_rn(kv[k]))));
          }
        }
        bar_sync(3, 128);
        const int tok = (tid & 63) >> 1, hf = tid & 1;
        const uint32_t inner = (pair & 7) * 16;
        if (rank == 0) {
          if (tid < 48) {
            const int d = tid & 15, sg = tid >> 4, j0 = sg == 0 ? 0 : (sg == 1 ? 10 : 22), j1 = sg == 0 ? 10 : (sg == 1 ? 22 : 32);
            float kx[12], run = 0.f;
#pragma unroll
            for (int e = 0; e < 12; e++) kx[e] = ldsf(sT + (min(j0 + e, 31) * 17 + d) * 4);
#pragma unroll
            for (int e = 0; e < 12; e++) {
              __half hv;
              if (pair < NP) { hv = __float2half_rn(fmaf(kx[e], 16.f, -run)); run += __half2float(hv); }
              else hv = __float2half_rn(kx[e] * 0.125f);
              if (j0 + e < j1) sts16(sH + ((j0 + e) * 16 + d) * 2, __half_as_ushort(hv));
            }
          } else if (w == 2) {
            float n2 = 0.f;
#pragma unroll
            for (int d = 0; d < 16; d++) { const float kx = ldsf(sT + (lane * 17 + d) * 4); n2 = fmaf(kx, kx, n2); }
            if (!(n2 <= 3.0e38f)) n2 = 3.0e38f;
#pragma unroll
            for (int m = 16; m > 0; m >>= 1) n2 = fmaxf(n2, __shfl_xor_sync(0xffffffffu, n2, m));
            if (lane == 0) g_kvstat[blockIdx.x * 16] = n2;
          }
          bar_sync(3, 128);
          const uint32_t off = tok * 2048 + (pair >> 3) * 256 + hf * 128 + inner;
          if (tid < 64) g_kimg[off >> 4] = lds128(sH + tok * 32 + hf * 16);
          else {
            float f[8];
#pragma unroll
            for (int e = 0; e < 8; e++) f[e] = ldsf(sT + (tok * 17 + hf * 8 + e) * 4);
            g_kbf[off >> 4] = make_uint4(pack_bf16(f[0], f[1]), pack_bf16(f[2], f[3]), pack_bf16(f[4], f[5]), pack_bf16(f[6], f[7]));
          }
        } else {
          if (tid < 64) {
            float f[8];
#pragma unroll
            for (int e = 0; e < 8; e++) f[e] = ldsf(sT + (tok * 17 + hf * 8 + e) * 4);
            const uint32_t sbo = 256 * (4 * tok + (pair >> 4) + 1);
            const uint32_t off = (hf ? SM_ONES + sbo : SM_ONES - sbo) + ((pair >> 3) & 1) * 128 + inner;
            g_kimg[off >> 4] = make_uint4(pack_bf16(f[0], f[1]), pack_bf16(f[2], f[3]), pack_bf16(f[4], f[5]), pack_bf16(f[6], f[7]));
          } else if (tid < 80) {
            float vm = 0.f;
#pragma unroll 8
            for (int jj = 0; jj < 32; jj++) { float a = fabsf(ldsf(sT + (jj * 17 + tid - 64) * 4)); if (!(a <= 3.0e38f)) a = 3.0e38f; vm = fmaxf(vm, a); }
            g_kvstat[blockIdx.x * 16 + tid - 64] = vm;
          } else if (tid >= 96 && tid < 112 && pair == 0) {
            g_kimg[(SM_ONES >> 4) + tid - 96] = make_uint4(0x3F803F80u, 0x3F803F80u, 0x3F803F80u, 0x3F803F80u);
          }
        }
        fence_async();
        bar_sync(3, 128);
        if (tid == 0) { red_release(&g_kvcnt[0]); TS(23); }
      }
      float qa[64];
#pragma unroll
      for (int k = 0; k < 64; k++) qa[k] = 0.f;
      regfence(qa);
#pragma unroll 1
      for (int c = 0; c < 8; c++) {
        mbar_wait(BAR(B_WFULL + 8 + c), 0);
        const uint64_t da = mkdesc(sb + SM_K + c * 16384, 16, 1024, 1);
        const uint64_t db = mkdesc(sb + SM_RING + (c & 3) * WSLOT + 12288, 8192, 1024, 1);
        wg_fence();
#pragma unroll
        for (int k = 0; k < 4; k++) { wg_ss_n64<0, 64>(qa, da + 2 * k, db + 128 * k); wg_ss_n64<32, 64>(qa, da + 512 + 2 * k, db + 128 * k); }
        wg_commit();
        wg_wait<0>();
        if (tid == 0) { if (c < 4) mbar_arrive(BAR(B_WEMPTY + 8 + c)); mbar_arrive_both(BAR(B_XEMPTY + c)); }
      }
      regfence(qa);
      if (tid == 0) TS(24);
      uint32_t qb[32];
      float n2 = 0.f;
#pragma unroll
      for (int k = 0; k < 32; k++) qb[k] = pack_bf16(qa[2 * k], qa[2 * k + 1]);
#pragma unroll
      for (int k = 0; k < 16; k++) {
        const uint32_t a = qb[4 * (k >> 1) + (k & 1)], b = qb[4 * (k >> 1) + (k & 1) + 2];
        float s = bf_lo(a) * bf_lo(a);
        s = fmaf(bf_hi(a), bf_hi(a), s); s = fmaf(bf_lo(b), bf_lo(b), s); s = fmaf(bf_hi(b), bf_hi(b), s);
        s += __shfl_xor_sync(0xffffffffu, s, 1); s += __shfl_xor_sync(0xffffffffu, s, 2);
        if (!(s <= 3.0e38f)) s = 3.0e38f;
        n2 = fmaxf(n2, s);
      }
#pragma unroll
      for (int m = 16; m > 2; m >>= 1) n2 = fmaxf(n2, __shfl_xor_sync(0xffffffffu, n2, m));
      if (lane == 0) sts32(sb + SM_MISC + 4 * (M_RED + w), __float_as_uint(n2));
      mbar_wait(BAR(B_KSTAT), 0);
      bar_sync(3, 128);
      const float qn2 = fmaxf(fmaxf(ldsf(sb + SM_MISC + 4 * M_RED), ldsf(sb + SM_MISC + 4 * (M_RED + 1))),
                              fmaxf(ldsf(sb + SM_MISC + 4 * (M_RED + 2)), ldsf(sb + SM_MISC + 4 * (M_RED + 3))));
      const float kn2 = ldsf(sb + SM_MISC + 4 * M_KN2);
      constexpr float SC = QSCALE * 0.125f;
      const bool fast = lds32(sb + SM_MISC + 4 * M_VOK) && qn2 <= 4.0e8f && kn2 <= 4.0e6f && qn2 * kn2 * (SC * SC) <= BOUND * BOUND;
#pragma unroll
      for (int tq = 0; tq < 8; tq++) {
        uint32_t r[4];
#pragma unroll
        for (int e = 0; e < 4; e++) {
          const uint32_t v = qb[(tq & 1) * 16 + (tq >> 1) * 4 + e];
          r[e] = fast ? pack_f16(bf_lo(v) * QSCALE, bf_hi(v) * QSCALE) : v;
        }
        sts128(sb + SM_Q + tq * 2048 + tid * 16, r[0], r[1], r[2], r[3]);
      }
      if (tid == 0) { sts32(sb + SM_MISC + 4 * M_FAST, fast ? 1u : 0u); mbar_arrive(BAR(B_DEC)); }
    }
    bar_sync(5, 512);
    if (tid == 0) TS(25 + wg);
#pragma unroll 1
    for (int c = 0; c < 8; c++) mbar_wait(BAR(B_KVFULL + c), 0);
    if (tid == 0) TS(28 + wg);
    const uint64_t dk0 = mkdesc(sb + SM_K, 128, 256, 0);
    const uint64_t dv0 = mkdesc(sb + SM_ONES - 256, 128, 256, 0);
    const uint64_t vstep = prm.vstep;
    float o[12], s[32];
    uint32_t q[4], p0[16], p1[16];
    if (lds32(sb + SM_MISC + 4 * M_FAST)) {
      const uint32_t mlo = prm.mlo, mhi = prm.mhi;
      uint64_t dk = dk0, dv = dv0;
#define STEP(PIN, POUT) { wg_fence(); issue_qk(s, q, dk); dk += 128; wg_commit(); issue_pv(o, PIN, dv, vstep); wg_commit(); \
                          wg_wait<1>(); regfence(s); softmax_step(s, POUT, mlo, mhi); wg_wait<0>(); }
#pragma unroll 1
      for (int sg = wg * 8; sg < wg * 8 + 8; sg++) {
        const int tau = sg / 3, seg = sg - tau * 3;
        int n2 = seg == 1 ? 6 : 5;
#pragma unroll
        for (int k = 0; k < NP / 2; k++) s[k] = MAGIC_C;
        if (sg == wg * 8 || seg == 0) {
          const int j0 = seg == 0 ? 0 : (seg == 1 ? 10 : 22);
          dk = dk0 + 128 * j0;
          dv = dv0 + VSTEP * (4 * j0);
          const uint4 qv = lds128(sb + SM_Q + tau * 2048 + tid * 16);
          q[0] = qv.x; q[1] = qv.y; q[2] = qv.z; q[3] = qv.w;
#pragma unroll
          for (int k = 0; k < 12; k++) o[k] = 0.f;
          regfence(o); regfence(s);
          wg_fence(); issue_qk(s, q, dk); dk += 128; wg_commit();
          wg_wait<0>(); regfence(s);
          softmax_step(s, p0, mlo, mhi);
          STEP(p0, p1);
          n2--;
        }
        regfence(s);
#pragma unroll 1
        for (; n2 > 0; n2--) { STEP(p1, p0); STEP(p0, p1); }
        if (sg == wg * 8 + 7 || seg == 2) {
          wg_fence(); issue_pv(o, p1, dv, vstep); wg_commit();
          wg_wait<0>(); regfence(o);
          if (sg == 8 || sg == 17) {
            float4* pp = g_part + (blockIdx.x * 2 + (wg - 1)) * 384 + tid;
            pp[0] = make_float4(o[0], o[1], o[2], o[3]); pp[128] = make_float4(o[4], o[5], o[6], o[7]); pp[256] = make_float4(o[8], o[9], o[10], o[11]);
            __threadfence_block();
            bar_arrive(5 + wg, 256);
          } else {
            if (sg == 7 || sg == 15) {
              bar_sync(6 + wg, 256);
              const float4* pp = g_part + (blockIdx.x * 2 + wg) * 384 + tid;
              const float4 a = pp[0], b = pp[128], c = pp[256];
              o[0] += a.x; o[1] += a.y; o[2] += a.z; o[3] += a.w; o[4] += b.x; o[6] += b.z; o[8] += c.x; o[9] += c.y; o[10] += c.z; o[11] += c.w;
            }
            store_o_tile(o, bi, bj, tau, tid, sb);
          }
        }
      }
#undef STEP
    } else {
      mbar_wait(BAR(B_KFB), 0);
      constexpr float SC = 0.25f * 1.4426950408889634f;
#pragma unroll 1
      for (int tau = wg * 3; tau < wg * 3 + 3 && tau < 8; tau++) {
        const uint4 qv = lds128(sb + SM_Q + tau * 2048 + tid * 16);
        float m0 = -INFINITY, m1 = -INFINITY;
#pragma unroll
        for (int k = 0; k < 12; k++) o[k] = 0.f;
        uint64_t dv = dv0;
#pragma unroll 1
        for (int j = 0; j < 32; j++) {
          regfence(s);
          wg_fence(); wg_qkb_n64<0, 0, 32>(s, qv.x, qv.y, qv.z, qv.w, dk0 + 128 * j); wg_commit();
          wg_wait<0>(); regfence(s);
          float x0 = m0, x1 = m1;
#pragma unroll
          for (int k = 0; k < 32; k++) { s[k] *= SC; if (k & 2) x1 = fmaxf(x1, s[k]); else x0 = fmaxf(x0, s[k]); }
          x0 = fmaxf(x0, __shfl_xor_sync(0xffffffffu, x0, 1)); x0 = fmaxf(x0, __shfl_xor_sync(0xffffffffu, x0, 2));
          x1 = fmaxf(x1, __shfl_xor_sync(0xffffffffu, x1, 1)); x1 = fmaxf(x1, __shfl_xor_sync(0xffffffffu, x1, 2));
          const float c0 = ex2(m0 - x0), c1 = ex2(m1 - x1);
          m0 = x0; m1 = x1;
#pragma unroll
          for (int k = 0; k < 12; k++) o[k] *= (k & 2) ? c1 : c0;
#pragma unroll
          for (int k = 0; k < 16; k++) { const float m = (k & 1) ? m1 : m0; p0[k] = exp_mufu(s[2 * k] - m, s[2 * k + 1] - m); }
          regfence(o);
          wg_fence(); issue_pv(o, p0, dv, vstep); wg_commit();
          wg_wait<0>(); regfence(o);
        }
        store_o_tile(o, bi, bj, tau, tid, sb);
      }
    }
    fence_async();
    bar_sync(1 + wg, 128);
    if (tid == 0) { red_release(&g_ocnt[bi * 32]); TS(31 + wg); }
  }
  __syncwarp();
  asm volatile("barrier.cluster.arrive.relaxed;" ::: "memory");
  asm volatile("barrier.cluster.wait;" ::: "memory");
}

typedef CUresult (*EncodeFn)(CUtensorMap*, CUtensorMapDataType, cuuint32_t, void*, const cuuint64_t*, const cuuint64_t*,
                             const cuuint32_t*, const cuuint32_t*, CUtensorMapInterleave, CUtensorMapSwizzle,
                             CUtensorMapL2promotion, CUtensorMapFloatOOBfill);

void make_map(EncodeFn enc, CUtensorMap* tm, const void* base, uint64_t cols, uint64_t rows, uint32_t bc, uint32_t br, CUtensorMapSwizzle sw) {
  cuuint64_t gd[2] = {cols, rows};
  cuuint64_t gs[1] = {cols * 2};
  cuuint32_t bd[2] = {bc, br};
  cuuint32_t es[2] = {1, 1};
  enc(tm, CU_TENSOR_MAP_DATA_TYPE_BFLOAT16, 2, const_cast<void*>(base), gd, gs, bd, es, CU_TENSOR_MAP_INTERLEAVE_NONE, sw,
      CU_TENSOR_MAP_L2_PROMOTION_L2_128B, CU_TENSOR_MAP_FLOAT_OOB_FILL_NONE);
}

}

extern "C" void kernel_launch(void* const* d_in, const int* in_sizes, int n_in, void* d_out, int out_size) {
  (void)in_sizes; (void)n_in; (void)out_size;
  static EncodeFn enc = nullptr;
  if (!enc) {
    void* fn = nullptr;
    cudaDriverEntryPointQueryResult qr;
    cudaGetDriverEntryPoint("cuTensorMapEncodeTiled", &fn, cudaEnableDefault, &qr);
    enc = (EncodeFn)fn;
    cudaFuncSetAttribute(fused_kernel, cudaFuncAttributeMaxDynamicSharedMemorySize, SMEM_BYTES);
  }
  CUtensorMap tx, tq, tk, tv, tin, tsp, tout, to;
  make_map(enc, &tx, d_in[0], 512, 2048, 64, 64, CU_TENSOR_MAP_SWIZZLE_128B);
  make_map(enc, &tq, d_in[1], 512, 512, 64, 64, CU_TENSOR_MAP_SWIZZLE_128B);
  make_map(enc, &tk, d_in[2], 16, 512, 16, 256, CU_TENSOR_MAP_SWIZZLE_32B);
  make_map(enc, &tv, d_in[3], 16, 512, 16, 256, CU_TENSOR_MAP_SWIZZLE_32B);
  make_map(enc, &to, d_in[4], 512, 512, 64, 64, CU_TENSOR_MAP_SWIZZLE_128B);
  make_map(enc, &tin, d_in[6], 1376, 512, 32, 64, CU_TENSOR_MAP_SWIZZLE_64B);
  make_map(enc, &tsp, d_in[7], 2048, 2048, 64, 64, CU_TENSOR_MAP_SWIZZLE_128B);
  make_map(enc, &tout, d_in[9], 512, 688, 64, 64, CU_TENSOR_MAP_SWIZZLE_128B);
  Params prm;
  prm.gate_w = (const __nv_bfloat16*)d_in[10];
  prm.b_sp = (const __nv_bfloat16*)d_in[8];
  prm.w_sp = (const __nv_bfloat16*)d_in[7];
  prm.w_out = (const __nv_bfloat16*)d_in[9];
  prm.wo = (const __nv_bfloat16*)d_in[4];
  prm.w_in = (const __nv_bfloat16*)d_in[6];
  prm.wq = (const __nv_bfloat16*)d_in[1];
  prm.vstep = VSTEP;
  prm.mlo = 0x007F007Fu;
  prm.mhi = 0xFF80FF80u;
  prm.out = (__nv_bfloat16*)d_out;
  fused_kernel<<<NCTA, NTHREADS, SMEM_BYTES>>>(tx, tq, tk, tv, tin, tsp, tout, to, prm);
}
```

```cpp
#include <cuda_runtime.h>
#include <cuda.h>
#include <cuda_bf16.h>
#include <cuda_fp16.h>
#include <stdint.h>

namespace {

constexpr int NCTA = 128;
constexpr int NTHREADS = 640;
constexpr int NP = 40;
constexpr int NM = 64 - NP;
constexpr int SPIN_LIMIT = 1 << 18;

constexpr uint32_t SM_K = 0;
constexpr uint32_t SM_ONES = 98304;
constexpr uint32_t KV_BYTES = 131328;
constexpr uint32_t SM_BAR = 131328;
constexpr uint32_t SM_RING = 132096;
constexpr uint32_t RSTAGE = 27648;
constexpr uint32_t WSLOT = 20480;
constexpr uint32_t SM_Q = 215040;
constexpr uint32_t SM_G = 231424;
constexpr uint32_t SM_MISC = 231936;
constexpr uint32_t SMEM_BYTES = 232448;

constexpr int B_XFULL = 0, B_XEMPTY = 8, B_WFULL = 16, B_WEMPTY = 32, B_KVFULL = 44, B_OFULL = 52, B_RFULL = 60,
              B_REMPTY = 63, B_KFB = 66, B_KSTAT = 67, B_DEC = 68, B_WOFULL = 69, B_EPOCH = 70, B_WKV = 71, B_STAT = 72, B_ZOK = 74, B_COUNT = 80;
constexpr int M_EPOCH = 0, M_KN2 = 1, M_VOK = 2, M_FAST = 3, M_RED = 4;

__device__ uint4 g_kimg[KV_BYTES / 16];
__device__ uint4 g_kbf[65536 / 16];
__device__ float g_kvstat[NCTA * 16];
__device__ float2 g_lnstat[16 * 8 * 128];
__device__ uint4 g_z2n[8 * 32 * 11264 / 16];
__device__ uint4 g_z1[NCTA * 11 * 128];
__device__ uint4 g_u[16 * 11 * 1024];
__device__ uint4 g_o[16 * 8 * 1024];
__device__ float4 g_part[NCTA * 2 * 3 * 128];
__device__ unsigned g_ticket;
__device__ unsigned g_kvcnt[32];
__device__ unsigned g_statcnt[32 * 32];
__device__ unsigned g_zflag[8 * 32];
__device__ unsigned g_ucnt[16 * 32];
__device__ unsigned g_ocnt[16 * 32];
#define TS(k) do { } while (0)

__device__ __forceinline__ void mbar_init(uint32_t a, uint32_t c) { asm volatile("mbarrier.init.shared::cta.b64 [%0], %1;" ::"r"(a), "r"(c) : "memory"); }
__device__ __forceinline__ void mbar_expect(uint32_t a, uint32_t b) { asm volatile("mbarrier.arrive.expect_tx.shared::cta.b64 _, [%0], %1;" ::"r"(a), "r"(b) : "memory"); }
__device__ __forceinline__ void mbar_arrive(uint32_t a) { asm volatile("mbarrier.arrive.shared::cta.b64 _, [%0];" ::"r"(a) : "memory"); }
__device__ __forceinline__ void mbar_arrive_both(uint32_t a) {
  asm volatile("{\n.reg .b32 ra;\nmapa.shared::cluster.u32 ra, %0, 0;\nmbarrier.arrive.shared::cluster.b64 _, [ra];\n"
               "mapa.shared::cluster.u32 ra, %0, 1;\nmbarrier.arrive.shared::cluster.b64 _, [ra];\n}" ::"r"(a) : "memory");
}
__device__ __forceinline__ void mbar_wait(uint32_t a, uint32_t ph) {
  uint32_t ok;
#pragma unroll 1
  for (int n = 0; n < SPIN_LIMIT; n++) {
    asm volatile("{\n.reg .pred p;\nmbarrier.try_wait.parity.shared::cta.b64 p, [%1], %2;\nselp.u32 %0, 1, 0, p;\n}" : "=r"(ok) : "r"(a), "r"(ph) : "memory");
    if (ok) break;
  }
}
__device__ __forceinline__ void tma2d(uint32_t dst, const CUtensorMap* tm, int c0, int c1, uint32_t bar) {
  asm volatile("cp.async.bulk.tensor.2d.shared::cluster.global.mbarrier::complete_tx::bytes [%0], [%1, {%3, %4}], [%2];"
               ::"r"(dst), "l"(tm), "r"(bar), "r"(c0), "r"(c1) : "memory");
}
__device__ __forceinline__ void tma2d_mc(uint32_t dst, const CUtensorMap* tm, int c0, int c1, uint32_t bar) {
  asm volatile("cp.async.bulk.tensor.2d.shared::cluster.global.mbarrier::complete_tx::bytes.multicast::cluster [%0], [%1, {%3, %4}], [%2], %5;"
               ::"r"(dst), "l"(tm), "r"(bar), "r"(c0), "r"(c1), "h"((uint16_t)3) : "memory");
}
__device__ __forceinline__ void tma2d_pf(const CUtensorMap* tm, int c0, int c1) {
  asm volatile("cp.async.bulk.prefetch.tensor.2d.L2.global [%0, {%1, %2}];" ::"l"(tm), "r"(c0), "r"(c1) : "memory");
}
__device__ __forceinline__ void bulk(uint32_t dst, const void* src, uint32_t bytes, uint32_t bar) {
  asm volatile("cp.async.bulk.shared::cluster.global.mbarrier::complete_tx::bytes [%0], [%1], %2, [%3];"
               ::"r"(dst), "l"(src), "r"(bytes), "r"(bar) : "memory");
}
__device__ __forceinline__ void bulk_mc(uint32_t dst, const void* src, uint32_t bytes, uint32_t bar) {
  asm volatile("cp.async.bulk.shared::cluster.global.mbarrier::complete_tx::bytes.multicast::cluster [%0], [%1], %2, [%3], %4;"
               ::"r"(dst), "l"(src), "r"(bytes), "r"(bar), "h"((uint16_t)3) : "memory");
}
__device__ __forceinline__ void l2_prefetch(const void* src, uint32_t bytes) { asm volatile("cp.async.bulk.prefetch.L2.global [%0], %1;" ::"l"(src), "r"(bytes) : "memory"); }
__device__ __forceinline__ void fence_async() { asm volatile("fence.proxy.async.global;" ::: "memory"); }
__device__ __forceinline__ void fence_async_smem() { asm volatile("fence.proxy.async.shared::cta;" ::: "memory"); }
__device__ __forceinline__ void bar_sync(int id, int n) { asm volatile("bar.sync %0, %1;" ::"r"(id), "r"(n) : "memory"); }
__device__ __forceinline__ void bar_arrive(int id, int n) { asm volatile("bar.arrive %0, %1;" ::"r"(id), "r"(n) : "memory"); }
__device__ __forceinline__ void red_release(unsigned* p) { asm volatile("red.release.gpu.global.add.u32 [%0], 1;" ::"l"(p) : "memory"); }
__device__ __forceinline__ void st_release(unsigned* p, unsigned v) { asm volatile("st.release.gpu.global.u32 [%0], %1;" ::"l"(p), "r"(v) : "memory"); }
__device__ __forceinline__ unsigned ld_acquire(const unsigned* p) { unsigned v; asm volatile("ld.acquire.gpu.global.u32 %0, [%1];" : "=r"(v) : "l"(p) : "memory"); return v; }
__device__ __forceinline__ void wait_ge(const unsigned* p, unsigned target) {
#pragma unroll 1
  for (int n = 0; n < SPIN_LIMIT; n++) {
    if ((int)(ld_acquire(p) - target) >= 0) break;
    __nanosleep(20);
  }
}
__device__ __forceinline__ void wg_fence() { asm volatile("wgmma.fence.sync.aligned;" ::: "memory"); }
__device__ __forceinline__ void wg_commit() { asm volatile("wgmma.commit_group.sync.aligned;" ::: "memory"); }
template <int N> __device__ __forceinline__ void wg_wait() { asm volatile("wgmma.wait_group.sync.aligned %0;" ::"n"(N) : "memory"); }
template <int n> __device__ __forceinline__ void regfence(float (&d)[n]) {
#pragma unroll
  for (int i = 0; i < n; i++) asm volatile("" : "+f"(d[i])::"memory");
}
__device__ __forceinline__ uint64_t mkdesc(uint32_t addr, uint32_t lbo, uint32_t sbo, int swz) {
  return (uint64_t)((addr & 0x3FFFF) >> 4) | ((uint64_t)(lbo >> 4) << 16) | ((uint64_t)(sbo >> 4) << 32) | ((uint64_t)swz << 62);
}
__device__ __forceinline__ uint32_t pack_bf16(float lo, float hi) { uint32_t r; asm("cvt.rn.bf16x2.f32 %0, %1, %2;" : "=r"(r) : "f"(hi), "f"(lo)); return r; }
__device__ __forceinline__ uint32_t pack_f16(float lo, float hi) { uint32_t r; asm("cvt.rn.f16x2.f32 %0, %1, %2;" : "=r"(r) : "f"(hi), "f"(lo)); return r; }
__device__ __forceinline__ float bf_lo(uint32_t v) { return __uint_as_float(v << 16); }
__device__ __forceinline__ float bf_hi(uint32_t v) { return __uint_as_float(v & 0xFFFF0000u); }
__device__ __forceinline__ float ex2(float x) { float r; asm("ex2.approx.ftz.f32 %0, %1;" : "=f"(r) : "f"(x)); return r; }
__device__ __forceinline__ float gelu_tanh(float x) {
  float u = x * fmaf(x * x, 0.0356774081f, 0.7978845608f), t;
  asm("tanh.approx.f32 %0, %1;" : "=f"(t) : "f"(u));
  float h = 0.5f * x;
  return fmaf(h, t, h);
}
__device__ __forceinline__ void sts32(uint32_t a, uint32_t v) { asm volatile("st.shared.u32 [%0], %1;" ::"r"(a), "r"(v) : "memory"); }
__device__ __forceinline__ void sts16(uint32_t a, uint16_t v) { asm volatile("st.shared.u16 [%0], %1;" ::"r"(a), "h"(v) : "memory"); }
__device__ __forceinline__ void sts128(uint32_t a, uint32_t x, uint32_t y, uint32_t z, uint32_t w) { asm volatile("st.shared.v4.u32 [%0], {%1,%2,%3,%4};" ::"r"(a), "r"(x), "r"(y), "r"(z), "r"(w) : "memory"); }
__device__ __forceinline__ uint32_t lds32(uint32_t a) { uint32_t v; asm volatile("ld.shared.u32 %0, [%1];" : "=r"(v) : "r"(a) : "memory"); return v; }
__device__ __forceinline__ float ldsf(uint32_t a) { return __uint_as_float(lds32(a)); }
__device__ __forceinline__ uint4 lds128(uint32_t a) { uint4 v; asm volatile("ld.shared.v4.u32 {%0,%1,%2,%3}, [%4];" : "=r"(v.x), "=r"(v.y), "=r"(v.z), "=r"(v.w) : "r"(a) : "memory"); return v; }

template<int OFF, int TOT> __device__ __forceinline__ void wg_ss_n88(float (&d)[TOT], uint64_t da, uint64_t db) {
  asm volatile("wgmma.mma_async.sync.aligned.m64n88k16.f32.bf16.bf16 {%0, %1, %2, %3, %4, %5, %6, %7, %8, %9, %10, %11, %12, %13, %14, %15, %16, %17, %18, %19, %20, %21, %22, %23, %24, %25, %26, %27, %28, %29, %30, %31, %32, %33, %34, %35, %36, %37, %38, %39, %40, %41, %42, %43}, %44, %45, 1, 1, 1, 0, 1;"
    : "+f"(d[OFF+0]), "+f"(d[OFF+1]), "+f"(d[OFF+2]), "+f"(d[OFF+3]), "+f"(d[OFF+4]), "+f"(d[OFF+5]), "+f"(d[OFF+6]), "+f"(d[OFF+7]),
      "+f"(d[OFF+8]), "+f"(d[OFF+9]), "+f"(d[OFF+10]), "+f"(d[OFF+11]), "+f"(d[OFF+12]), "+f"(d[OFF+13]), "+f"(d[OFF+14]), "+f"(d[OFF+15]),
      "+f"(d[OFF+16]), "+f"(d[OFF+17]), "+f"(d[OFF+18]), "+f"(d[OFF+19]), "+f"(d[OFF+20]), "+f"(d[OFF+21]), "+f"(d[OFF+22]), "+f"(d[OFF+23]),
      "+f"(d[OFF+24]), "+f"(d[OFF+25]), "+f"(d[OFF+26]), "+f"(d[OFF+27]), "+f"(d[OFF+28]), "+f"(d[OFF+29]), "+f"(d[OFF+30]), "+f"(d[OFF+31]),
      "+f"(d[OFF+32]), "+f"(d[OFF+33]), "+f"(d[OFF+34]), "+f"(d[OFF+35]), "+f"(d[OFF+36]), "+f"(d[OFF+37]), "+f"(d[OFF+38]), "+f"(d[OFF+39]),
      "+f"(d[OFF+40]), "+f"(d[OFF+41]), "+f"(d[OFF+42]), "+f"(d[OFF+43])
    : "l"(da), "l"(db));
}
template<int OFF, int TOT> __device__ __forceinline__ void wg_ss_n64(float (&d)[TOT], uint64_t da, uint64_t db) {
  asm volatile("wgmma.mma_async.sync.aligned.m64n64k16.f32.bf16.bf16 {%0, %1, %2, %3, %4, %5, %6, %7, %8, %9, %10, %11, %12, %13, %14, %15, %16, %17, %18, %19, %20, %21, %22, %23, %24, %25, %26, %27, %28, %29, %30, %31}, %32, %33, 1, 1, 1, 0, 1;"
    : "+f"(d[OFF+0]), "+f"(d[OFF+1]), "+f"(d[OFF+2]), "+f"(d[OFF+3]), "+f"(d[OFF+4]), "+f"(d[OFF+5]), "+f"(d[OFF+6]), "+f"(d[OFF+7]),
      "+f"(d[OFF+8]), "+f"(d[OFF+9]), "+f"(d[OFF+10]), "+f"(d[OFF+11]), "+f"(d[OFF+12]), "+f"(d[OFF+13]), "+f"(d[OFF+14]), "+f"(d[OFF+15]),
      "+f"(d[OFF+16]), "+f"(d[OFF+17]), "+f"(d[OFF+18]), "+f"(d[OFF+19]), "+f"(d[OFF+20]), "+f"(d[OFF+21]), "+f"(d[OFF+22]), "+f"(d[OFF+23]),
      "+f"(d[OFF+24]), "+f"(d[OFF+25]), "+f"(d[OFF+26]), "+f"(d[OFF+27]), "+f"(d[OFF+28]), "+f"(d[OFF+29]), "+f"(d[OFF+30]), "+f"(d[OFF+31])
    : "l"(da), "l"(db));
}
template<int OFF, int TOT> __device__ __forceinline__ void wg_ss_n32t(float (&d)[TOT], uint64_t da, uint64_t db) {
  asm volatile("wgmma.mma_async.sync.aligned.m64n32k16.f32.bf16.bf16 {%0, %1, %2, %3, %4, %5, %6, %7, %8, %9, %10, %11, %12, %13, %14, %15}, %16, %17, 1, 1, 1, 1, 0;"
    : "+f"(d[OFF+0]), "+f"(d[OFF+1]), "+f"(d[OFF+2]), "+f"(d[OFF+3]), "+f"(d[OFF+4]), "+f"(d[OFF+5]), "+f"(d[OFF+6]), "+f"(d[OFF+7]),
      "+f"(d[OFF+8]), "+f"(d[OFF+9]), "+f"(d[OFF+10]), "+f"(d[OFF+11]), "+f"(d[OFF+12]), "+f"(d[OFF+13]), "+f"(d[OFF+14]), "+f"(d[OFF+15])
    : "l"(da), "l"(db));
}
template<int SCD, int OFF, int TOT> __device__ __forceinline__ void wg_qk_n16(float (&d)[TOT], uint32_t a0, uint32_t a1, uint32_t a2, uint32_t a3, uint64_t db) {
  asm volatile("wgmma.mma_async.sync.aligned.m64n16k16.f32.f16.f16 {%0, %1, %2, %3, %4, %5, %6, %7}, {%8,%9,%10,%11}, %12, %13, 1, 1, 0;"
    : "+f"(d[OFF+0]), "+f"(d[OFF+1]), "+f"(d[OFF+2]), "+f"(d[OFF+3]), "+f"(d[OFF+4]), "+f"(d[OFF+5]), "+f"(d[OFF+6]), "+f"(d[OFF+7])
    : "r"(a0), "r"(a1), "r"(a2), "r"(a3), "l"(db), "n"(SCD));
}
template<int SCD, int OFF, int TOT> __device__ __forceinline__ void wg_qk_n24(float (&d)[TOT], uint32_t a0, uint32_t a1, uint32_t a2, uint32_t a3, uint64_t db) {
  asm volatile("wgmma.mma_async.sync.aligned.m64n24k16.f32.f16.f16 {%0, %1, %2, %3, %4, %5, %6, %7, %8, %9, %10, %11}, {%12,%13,%14,%15}, %16, %17, 1, 1, 0;"
    : "+f"(d[OFF+0]), "+f"(d[OFF+1]), "+f"(d[OFF+2]), "+f"(d[OFF+3]), "+f"(d[OFF+4]), "+f"(d[OFF+5]), "+f"(d[OFF+6]), "+f"(d[OFF+7]),
      "+f"(d[OFF+8]), "+f"(d[OFF+9]), "+f"(d[OFF+10]), "+f"(d[OFF+11])
    : "r"(a0), "r"(a1), "r"(a2), "r"(a3), "l"(db), "n"(SCD));
}
template<int SCD, int OFF, int TOT> __device__ __forceinline__ void wg_qk_n32(float (&d)[TOT], uint32_t a0, uint32_t a1, uint32_t a2, uint32_t a3, uint64_t db) {
  asm volatile("wgmma.mma_async.sync.aligned.m64n32k16.f32.f16.f16 {%0, %1, %2, %3, %4, %5, %6, %7, %8, %9, %10, %11, %12, %13, %14, %15}, {%16,%17,%18,%19}, %20, %21, 1, 1, 0;"
    : "+f"(d[OFF+0]), "+f"(d[OFF+1]), "+f"(d[OFF+2]), "+f"(d[OFF+3]), "+f"(d[OFF+4]), "+f"(d[OFF+5]), "+f"(d[OFF+6]), "+f"(d[OFF+7]),
      "+f"(d[OFF+8]), "+f"(d[OFF+9]), "+f"(d[OFF+10]), "+f"(d[OFF+11]), "+f"(d[OFF+12]), "+f"(d[OFF+13]), "+f"(d[OFF+14]), "+f"(d[OFF+15])
    : "r"(a0), "r"(a1), "r"(a2), "r"(a3), "l"(db), "n"(SCD));
}
template<int SCD, int OFF, int TOT> __device__ __forceinline__ void wg_qk_n40(float (&d)[TOT], uint32_t a0, uint32_t a1, uint32_t a2, uint32_t a3, uint64_t db) {
  asm volatile("wgmma.mma_async.sync.aligned.m64n40k16.f32.f16.f16 {%0, %1, %2, %3, %4, %5, %6, %7, %8, %9, %10, %11, %12, %13, %14, %15, %16, %17, %18, %19}, {%20,%21,%22,%23}, %24, %25, 1, 1, 0;"
    : "+f"(d[OFF+0]), "+f"(d[OFF+1]), "+f"(d[OFF+2]), "+f"(d[OFF+3]), "+f"(d[OFF+4]), "+f"(d[OFF+5]), "+f"(d[OFF+6]), "+f"(d[OFF+7]),
      "+f"(d[OFF+8]), "+f"(d[OFF+9]), "+f"(d[OFF+10]), "+f"(d[OFF+11]), "+f"(d[OFF+12]), "+f"(d[OFF+13]), "+f"(d[OFF+14]), "+f"(d[OFF+15]),
      "+f"(d[OFF+16]), "+f"(d[OFF+17]), "+f"(d[OFF+18]), "+f"(d[OFF+19])
    : "r"(a0), "r"(a1), "r"(a2), "r"(a3), "l"(db), "n"(SCD));
}
template<int SCD, int OFF, int TOT> __device__ __forceinline__ void wg_qk_n48(float (&d)[TOT], uint32_t a0, uint32_t a1, uint32_t a2, uint32_t a3, uint64_t db) {
  asm volatile("wgmma.mma_async.sync.aligned.m64n48k16.f32.f16.f16 {%0, %1, %2, %3, %4, %5, %6, %7, %8, %9, %10, %11, %12, %13, %14, %15, %16, %17, %18, %19, %20, %21, %22, %23}, {%24,%25,%26,%27}, %28, %29, 1, 1, 0;"
    : "+f"(d[OFF+0]), "+f"(d[OFF+1]), "+f"(d[OFF+2]), "+f"(d[OFF+3]), "+f"(d[OFF+4]), "+f"(d[OFF+5]), "+f"(d[OFF+6]), "+f"(d[OFF+7]),
      "+f"(d[OFF+8]), "+f"(d[OFF+9]), "+f"(d[OFF+10]), "+f"(d[OFF+11]), "+f"(d[OFF+12]), "+f"(d[OFF+13]), "+f"(d[OFF+14]), "+f"(d[OFF+15]),
      "+f"(d[OFF+16]), "+f"(d[OFF+17]), "+f"(d[OFF+18]), "+f"(d[OFF+19]), "+f"(d[OFF+20]), "+f"(d[OFF+21]), "+f"(d[OFF+22]), "+f"(d[OFF+23])
    : "r"(a0), "r"(a1), "r"(a2), "r"(a3), "l"(db), "n"(SCD));
}
template<int SCD, int OFF, int TOT> __device__ __forceinline__ void wg_pv_n24(float (&d)[TOT], uint32_t a0, uint32_t a1, uint32_t a2, uint32_t a3, uint64_t db) {
  asm volatile("wgmma.mma_async.sync.aligned.m64n24k16.f32.bf16.bf16 {%0, %1, %2, %3, %4, %5, %6, %7, %8, %9, %10, %11}, {%12,%13,%14,%15}, %16, %17, 1, 1, 1;"
    : "+f"(d[OFF+0]), "+f"(d[OFF+1]), "+f"(d[OFF+2]), "+f"(d[OFF+3]), "+f"(d[OFF+4]), "+f"(d[OFF+5]), "+f"(d[OFF+6]), "+f"(d[OFF+7]),
      "+f"(d[OFF+8]), "+f"(d[OFF+9]), "+f"(d[OFF+10]), "+f"(d[OFF+11])
    : "r"(a0), "r"(a1), "r"(a2), "r"(a3), "l"(db), "n"(SCD));
}
template<int SCD, int OFF, int TOT> __device__ __forceinline__ void wg_qkb_n64(float (&d)[TOT], uint32_t a0, uint32_t a1, uint32_t a2, uint32_t a3, uint64_t db) {
  asm volatile("wgmma.mma_async.sync.aligned.m64n64k16.f32.bf16.bf16 {%0, %1, %2, %3, %4, %5, %6, %7, %8, %9, %10, %11, %12, %13, %14, %15, %16, %17, %18, %19, %20, %21, %22, %23, %24, %25, %26, %27, %28, %29, %30, %31}, {%32,%33,%34,%35}, %36, %37, 1, 1, 0;"
    : "+f"(d[OFF+0]), "+f"(d[OFF+1]), "+f"(d[OFF+2]), "+f"(d[OFF+3]), "+f"(d[OFF+4]), "+f"(d[OFF+5]), "+f"(d[OFF+6]), "+f"(d[OFF+7]),
      "+f"(d[OFF+8]), "+f"(d[OFF+9]), "+f"(d[OFF+10]), "+f"(d[OFF+11]), "+f"(d[OFF+12]), "+f"(d[OFF+13]), "+f"(d[OFF+14]), "+f"(d[OFF+15]),
      "+f"(d[OFF+16]), "+f"(d[OFF+17]), "+f"(d[OFF+18]), "+f"(d[OFF+19]), "+f"(d[OFF+20]), "+f"(d[OFF+21]), "+f"(d[OFF+22]), "+f"(d[OFF+23]),
      "+f"(d[OFF+24]), "+f"(d[OFF+25]), "+f"(d[OFF+26]), "+f"(d[OFF+27]), "+f"(d[OFF+28]), "+f"(d[OFF+29]), "+f"(d[OFF+30]), "+f"(d[OFF+31])
    : "r"(a0), "r"(a1), "r"(a2), "r"(a3), "l"(db), "n"(SCD));
}
template<int N, int SCD, int OFF, int TOT> __device__ __forceinline__ void wg_qk(float (&d)[TOT], const uint32_t (&q)[4], uint64_t db) {
  if constexpr (N == 16) wg_qk_n16<SCD, OFF, TOT>(d, q[0], q[1], q[2], q[3], db);
  if constexpr (N == 24) wg_qk_n24<SCD, OFF, TOT>(d, q[0], q[1], q[2], q[3], db);
  if constexpr (N == 32) wg_qk_n32<SCD, OFF, TOT>(d, q[0], q[1], q[2], q[3], db);
  if constexpr (N == 40) wg_qk_n40<SCD, OFF, TOT>(d, q[0], q[1], q[2], q[3], db);
  if constexpr (N == 48) wg_qk_n48<SCD, OFF, TOT>(d, q[0], q[1], q[2], q[3], db);
}

__device__ __forceinline__ uint32_t exp_mufu(float a, float b) { return pack_bf16(ex2(a), ex2(b)); }
__device__ __forceinline__ uint32_t exp_poly(float a, float b, uint32_t mlo, uint32_t mhi) {
  uint32_t u = __byte_perm(__float_as_uint(a), __float_as_uint(b), 0x6521), mh, e, p;
  asm("lop3.b32 %0, %1, %2, 0x3F003F00, 0xEA;" : "=r"(mh) : "r"(u), "r"(mlo));
  asm("lop3.b32 %0, %1, %2, 0x00020002, 0xEA;" : "=r"(e) : "r"(u), "r"(mhi));
  asm("fma.rn.bf16x2 %0, %1, %2, %3;" : "=r"(p) : "r"(u), "r"(mh), "r"(e));
  return p;
}
constexpr float MAGIC_C = 48948.0625f;
constexpr float QSCALE = 0.25f * 1.4426950408889634f * 8.f;
constexpr float BOUND = 80.f;

__device__ __forceinline__ void softmax_step(const float (&s)[32], uint32_t (&p)[16], uint32_t mlo, uint32_t mhi) {
  constexpr int PP = NP / 4;
  int ip = 0, im = PP;
#pragma unroll
  for (int i = 0; i < 16; i++) {
    if (((i + 1) * PP / 16) > (i * PP / 16)) { p[ip] = exp_poly(s[2 * ip], s[2 * ip + 1], mlo, mhi); ip++; }
    else { p[im] = exp_mufu(s[2 * im], s[2 * im + 1]); im++; }
  }
}
constexpr uint64_t VSTEP = ((uint64_t)16 << 32) - 16;
__device__ __forceinline__ void issue_qk(float (&s)[32], const uint32_t (&q)[4], uint64_t dk) {
  wg_qk<NM, 0, NP / 2, 32>(s, q, dk + NP * 2);
  wg_qk<NP, 1, 0, 32>(s, q, dk);
}
__device__ __forceinline__ void issue_pv(float (&o)[12], const uint32_t (&p)[16], uint64_t& dv, uint64_t vstep) {
#pragma unroll
  for (int c = 0; c < 4; c++) { wg_pv_n24<1, 0, 12>(o, p[4 * c], p[4 * c + 1], p[4 * c + 2], p[4 * c + 3], dv); dv += vstep; }
}

struct Params {
  const __nv_bfloat16* gate_w;
  const __nv_bfloat16* b_sp;
  const __nv_bfloat16* w_sp;
  const __nv_bfloat16* w_out;
  const __nv_bfloat16* wo;
  const __nv_bfloat16* w_in;
  const __nv_bfloat16* wq;
  uint64_t vstep;
  uint32_t mlo, mhi;
  __nv_bfloat16* out;
};

__device__ __forceinline__ void store_o_tile(const float (&o)[12], int bi, int bj, int tau, int tid, uint32_t sb) {
  const int half = tau & 1, hh = tau >> 1, w = tid >> 5, g = (tid & 31) >> 2;
  const int r0 = half * 64 + w * 16 + g;
  const float f0 = __fdividef(ldsf(sb + SM_G + r0 * 4), o[4]), f1 = __fdividef(ldsf(sb + SM_G + (r0 + 8) * 4), o[6]);
  uint32_t* dst = reinterpret_cast<uint32_t*>(g_o) + (bi * 8 + bj) * 4096 + (half * 8 + w * 2) * 256 + hh * 64 + (tid & 31);
  dst[0] = pack_bf16(o[0] * f0, o[1] * f0);
  dst[32] = pack_bf16(o[8] * f0, o[9] * f0);
  dst[256] = pack_bf16(o[2] * f1, o[3] * f1);
  dst[288] = pack_bf16(o[10] * f1, o[11] * f1);
}

__global__ void __cluster_dims__(2, 1, 1) __launch_bounds__(NTHREADS, 1)
fused_kernel(const __grid_constant__ CUtensorMap tm_x, const __grid_constant__ CUtensorMap tm_wq,
             const __grid_constant__ CUtensorMap tm_wk, const __grid_constant__ CUtensorMap tm_wv,
             const __grid_constant__ CUtensorMap tm_win, const __grid_constant__ CUtensorMap tm_wsp,
             const __grid_constant__ CUtensorMap tm_wout, const __grid_constant__ CUtensorMap tm_wo, const Params prm) {
  extern __shared__ __align__(1024) uint8_t smem_raw[];
  const uint32_t sb = (uint32_t)__cvta_generic_to_shared(smem_raw);
  const int wg = __shfl_sync(0xffffffffu, (int)(threadIdx.x >> 7), 0);
  const int tid = threadIdx.x & 127;
  const int lane = threadIdx.x & 31;
  const int bi = blockIdx.x >> 3, bj = blockIdx.x & 7, rank = bj & 1;
  auto BAR = [&](int k) { return sb + SM_BAR + 8u * k; };

  const int warp = __shfl_sync(0xffffffffu, (int)(threadIdx.x >> 5), 0);
  if (lane == 0) {
    if (warp == 16) {
      asm volatile("prefetch.tensormap [%0];" ::"l"(&tm_x) : "memory");
    } else if (warp == 18) {
      asm volatile("prefetch.tensormap [%0];" ::"l"(rank ? &tm_wv : &tm_wk) : "memory");
      asm volatile("prefetch.tensormap [%0];" ::"l"(&tm_win) : "memory");
    } else if (warp == 19) {
      l2_prefetch(reinterpret_cast<const uint8_t*>(prm.w_in) + blockIdx.x * 11008, 11008);
      l2_prefetch(reinterpret_cast<const uint8_t*>(prm.wq) + blockIdx.x * 4096, 4096);
    } else if (warp < 16) {
#pragma unroll
      for (int r = 0; r < 5; r++) {
        const int k = warp + 16 * r;
        uint32_t cnt = 1;
        if (k >= B_XEMPTY && k < B_XEMPTY + 8) cnt = 4;
        if (k >= B_WEMPTY && k < B_WEMPTY + 12) cnt = 2;
        if (k >= B_REMPTY && k < B_REMPTY + 3) cnt = 2;
        mbar_init(BAR(k), cnt);
      }
      asm volatile("fence.mbarrier_init.release.cluster;" ::: "memory");
    }
  }
  if (threadIdx.x == 0) TS(34);
  __syncthreads();
  if (threadIdx.x == 0) TS(35);
  asm volatile("barrier.cluster.arrive.relaxed.aligned;" ::: "memory");
  if (warp != 18) asm volatile("barrier.cluster.wait.acquire.aligned;" ::: "memory");

  if (wg == 4) {
    asm volatile("setmaxnreg.dec.sync.aligned.u32 24;");
    const int pw = warp - 16;
    if (pw == 2) {
      if (lane == 0) {
        mbar_expect(BAR(B_WKV), 16384);
        tma2d(sb + SM_Q, rank ? &tm_wv : &tm_wk, 0, 0, BAR(B_WKV));
        tma2d(sb + SM_Q + 8192, rank ? &tm_wv : &tm_wk, 0, 256, BAR(B_WKV));
#pragma unroll 1
        for (int f = 0; f < 16; f++) {
          if (f == 4) { TS(37); asm volatile("prefetch.tensormap [%0];" ::"l"(&tm_wq) : "memory"); }
          if (f >= 4) mbar_wait(BAR(B_WEMPTY + f - 4), 0);
          const uint32_t slot = sb + SM_RING + (f & 3) * WSLOT, bar = BAR(B_WFULL + f);
          const int k0 = (f & 7) * 64, c0 = (f < 8 ? 688 : 0) + 88 * bj;
          mbar_expect(bar, f < 8 ? 12288 : 12288 + 8192);
          if (f >= 8) tma2d(slot + 12288, &tm_wq, 64 * bj, k0, bar);
          tma2d(slot, &tm_win, c0, k0, bar);
          tma2d(slot + 4096, &tm_win, c0 + 32, k0, bar);
          tma2d(slot + 8192, &tm_win, c0 + 64, k0, bar);
        }
        TS(1);
      }
      __syncwarp();
      asm volatile("barrier.cluster.wait.acquire.aligned;" ::: "memory");
    } else if (pw == 3) {
      mbar_wait(BAR(B_EPOCH), 0);
      const unsigned ep1 = lds32(sb + SM_MISC + 4 * M_EPOCH) + 1;
      bool d0 = false, d1 = false, d2 = false;
#pragma unroll 1
      for (int n = 0; n < SPIN_LIMIT && !(d0 && d1 && d2); n++) {
        const bool z = (int)(ld_acquire(&g_zflag[bj * 32 + lane]) - ep1) >= 0;
        const bool t = (int)(ld_acquire(&g_statcnt[(bi * 2 + (lane & 1)) * 32]) - ep1 * 8) >= 0;
        const unsigned tm = __ballot_sync(0xffffffffu, t);
        const bool za = __all_sync(0xffffffffu, z);
        if (!d0 && (tm & 1)) { d0 = true; if (lane == 0) mbar_arrive(BAR(B_STAT)); }
        if (!d1 && (tm & 2)) { d1 = true; if (lane == 0) mbar_arrive(BAR(B_STAT + 1)); }
        if (!d2 && za) { d2 = true; if (lane == 0) mbar_arrive(BAR(B_ZOK)); }
      }
    } else if (pw == 0) {
      if (lane == 0) {
        TS(0);
#pragma unroll 1
        for (int c = 0; c < 8; c++) {
          mbar_expect(BAR(B_XFULL + c), 16384);
          tma2d_mc(sb + SM_K + c * 16384 + rank * 8192, &tm_x, c * 64, bi * 128 + rank * 64, BAR(B_XFULL + c));
        }
        TS(36);
        asm volatile("prefetch.tensormap [%0];" ::"l"(&tm_wsp) : "memory");
        asm volatile("prefetch.tensormap [%0];" ::"l"(&tm_wout) : "memory");
        asm volatile("prefetch.tensormap [%0];" ::"l"(&tm_wo) : "memory");
        mbar_wait(BAR(B_XEMPTY), 0);
        tma2d_pf(&tm_wsp, (bj >> 1) * 64, bi * 128 + rank * 64);
        tma2d_pf(&tm_wsp, (bj >> 1) * 64 + 256, bi * 128 + rank * 64);
        mbar_wait(BAR(B_XEMPTY + 7), 0);
        mbar_wait(BAR(B_ZOK), 0);
        const unsigned ep1 = lds32(sb + SM_MISC + 4 * M_EPOCH) + 1;
        fence_async();
        TS(2);
        int st = 0, ph = 1;
#pragma unroll 1
        for (int n = 0; n < 43; n++) {
          const uint32_t stg = sb + SM_RING + st * RSTAGE, bar = BAR(B_RFULL + st);
          if (n >= 3) mbar_wait(BAR(B_REMPTY + st), ph);
          if (n < 32) {
            mbar_expect(bar, 16384 + 11264);
            tma2d_mc(stg + rank * 8192, &tm_wsp, n * 64, bi * 128 + rank * 64, bar);
            if ((n & 3) == (bj >> 1) && n < 24) tma2d_pf(&tm_wsp, (n + 8) * 64, bi * 128 + rank * 64);
            if (n == 16) {
              l2_prefetch(reinterpret_cast<const uint8_t*>(prm.w_out) + blockIdx.x * 5504, 5504);
              l2_prefetch(reinterpret_cast<const uint8_t*>(prm.wo) + blockIdx.x * 4096, 4096);
            }
            bulk(stg + 16384, reinterpret_cast<const uint8_t*>(g_z2n) + (bj * 32 + n) * 11264, 11264, bar);
          } else {
            const int c = n - 32;
            mbar_expect(bar, 16384 + 8192);
            tma2d(stg + 16384, &tm_wout, 64 * bj, c * 64, bar);
            if (c == 0) { wait_ge(&g_ucnt[bi * 32], ep1 * 8); fence_async(); TS(3); }
            bulk_mc(stg + rank * 8192, reinterpret_cast<const uint8_t*>(g_u) + (bi * 11 + c) * 16384 + rank * 8192, 8192, bar);
          }
          if (++st == 3) { st = 0; ph ^= 1; }
        }
#pragma unroll 1
        for (int n = 0; n < 3; n++) {
          mbar_wait(BAR(B_REMPTY + st), ph);
          if (++st == 3) { st = 0; ph ^= 1; }
        }
        mbar_expect(BAR(B_WOFULL), 65536);
#pragma unroll 1
        for (int c = 0; c < 8; c++) tma2d(sb + SM_RING + c * 8192, &tm_wo, 64 * bj, c * 64, BAR(B_WOFULL));
        TS(4);
        wait_ge(&g_ocnt[bi * 32], ep1 * 24);
        fence_async();
        TS(5);
#pragma unroll 1
        for (int c = 0; c < 8; c++) {
          mbar_expect(BAR(B_OFULL + c), 16384);
          bulk_mc(sb + SM_K + c * 16384 + rank * 8192, reinterpret_cast<const uint8_t*>(g_o) + (bi * 8 + c) * 16384 + rank * 8192, 8192, BAR(B_OFULL + c));
        }
      }
    } else {
      unsigned ep = 0;
      if (lane == 0) {
        ep = atomicAdd(&g_ticket, 1u) / NCTA;
        sts32(sb + SM_MISC + 4 * M_EPOCH, ep);
        mbar_arrive(BAR(B_EPOCH));
        TS(71);
        wait_ge(&g_kvcnt[0], (ep + 1) * NCTA);
        TS(6);
      }
      __syncwarp();
      float kn2 = fmaxf(__ldcg(&g_kvstat[(4 * lane) * 16]), __ldcg(&g_kvstat[(4 * lane + 2) * 16]));
      float4 vq = make_float4(0.f, 0.f, 0.f, 0.f);
#pragma unroll
      for (int h = 0; h < 2; h++) {
        float4 a[4];
#pragma unroll
        for (int p = 0; p < 4; p++) a[p] = __ldcg(reinterpret_cast<const float4*>(g_kvstat) + (2 * ((lane >> 2) * 8 + h * 4 + p) + 1) * 4 + (lane & 3));
#pragma unroll
        for (int p = 0; p < 4; p++) { vq.x = fmaxf(vq.x, a[p].x); vq.y = fmaxf(vq.y, a[p].y); vq.z = fmaxf(vq.z, a[p].z); vq.w = fmaxf(vq.w, a[p].w); }
      }
#pragma unroll
      for (int m = 16; m > 2; m >>= 1) {
        vq.x = fmaxf(vq.x, __shfl_xor_sync(0xffffffffu, vq.x, m)); vq.y = fmaxf(vq.y, __shfl_xor_sync(0xffffffffu, vq.y, m));
        vq.z = fmaxf(vq.z, __shfl_xor_sync(0xffffffffu, vq.z, m)); vq.w = fmaxf(vq.w, __shfl_xor_sync(0xffffffffu, vq.w, m));
      }
      const float vlo = fminf(fminf(vq.x, vq.y), fminf(vq.z, vq.w)), vhi = fmaxf(fmaxf(vq.x, vq.y), fmaxf(vq.z, vq.w));
#pragma unroll
      for (int m = 16; m > 0; m >>= 1) kn2 = fmaxf(kn2, __shfl_xor_sync(0xffffffffu, kn2, m));
      const bool vok = __all_sync(0xffffffffu, vlo >= 9.5367431640625e-07f && vhi <= 1073741824.f);
      if (lane == 0) {
        sts32(sb + SM_MISC + 4 * M_KN2, __float_as_uint(kn2));
        sts32(sb + SM_MISC + 4 * M_VOK, vok ? 1u : 0u);
        mbar_arrive(BAR(B_KSTAT));
        TS(70);
        fence_async();
#pragma unroll 1
        for (int c = 0; c < 8; c++) {
          const uint32_t bytes = c == 7 ? 16640 : 16384, hb = bytes / 2, off = c * 16384 + rank * hb;
          mbar_wait(BAR(B_XEMPTY + c), 0);
          mbar_expect(BAR(B_KVFULL + c), bytes);
          bulk_mc(sb + SM_K + off, reinterpret_cast<const uint8_t*>(g_kimg) + off, hb, BAR(B_KVFULL + c));
        }
        TS(7);
        mbar_wait(BAR(B_DEC), 0);
        if (!lds32(sb + SM_MISC + 4 * M_FAST)) {
          for (int c = 0; c < 4; c++) mbar_wait(BAR(B_KVFULL + c), 0);
          mbar_expect(BAR(B_KFB), 65536);
          for (int c = 0; c < 4; c++) bulk(sb + SM_K + c * 16384, reinterpret_cast<const uint8_t*>(g_kbf) + c * 16384, 16384, BAR(B_KFB));
        }
      }
    }
  } else if (wg == 3) {
    asm volatile("setmaxnreg.inc.sync.aligned.u32 120;");
    const int w = tid >> 5, g = lane >> 2, t4 = lane & 3;
    {
      float a0 = 0.f, a1 = 0.f, a2 = 0.f, a3 = 0.f;
      uint4* sW = reinterpret_cast<uint4*>(smem_raw + SM_RING + 4 * WSLOT);
      if (tid < 64) sW[tid] = __ldg(reinterpret_cast<const uint4*>(prm.gate_w) + tid);
      bar_sync(4, 128);
#pragma unroll 1
      for (int c = 0; c < 8; c++) {
        mbar_wait(BAR(B_XFULL + c), 0);
        if (tid == 0) TS(40 + c);
        const uint4* xr = reinterpret_cast<const uint4*>(smem_raw + SM_K + c * 16384 + tid * 128);
#pragma unroll
        for (int v = 0; v < 8; v++) {
          const uint4 xv = xr[v ^ (tid & 7)], gv = sW[c * 8 + v];
          a0 = fmaf(bf_lo(xv.x), bf_lo(gv.x), a0); a1 = fmaf(bf_hi(xv.x), bf_hi(gv.x), a1);
          a2 = fmaf(bf_lo(xv.y), bf_lo(gv.y), a2); a3 = fmaf(bf_hi(xv.y), bf_hi(gv.y), a3);
          a0 = fmaf(bf_lo(xv.z), bf_lo(gv.z), a0); a1 = fmaf(bf_hi(xv.z), bf_hi(gv.z), a1);
          a2 = fmaf(bf_lo(xv.w), bf_lo(gv.w), a2); a3 = fmaf(bf_hi(xv.w), bf_hi(gv.w), a3);
        }
      }
      sts32(sb + SM_G + tid * 4, __float_as_uint(__fdividef(1.f, 1.f + __expf(-((a0 + a1) + (a2 + a3))))));
      fence_async_smem();
      bar_sync(4, 128);
      bar_arrive(5, 512);
    }
    if (tid == 0) TS(8);
    float acc[88];
    {
#pragma unroll
      for (int k = 0; k < 88; k++) acc[k] = 0.f;
      regfence(acc);
#pragma unroll 1
      for (int c = 0; c < 8; c++) {
        mbar_wait(BAR(B_WFULL + 8 + c), 0);
        if (tid == 0) TS(56 + c);
        const uint64_t da = mkdesc(sb + SM_K + c * 16384, 16, 1024, 1);
        const uint64_t db = mkdesc(sb + SM_RING + (c & 3) * WSLOT, 4096, 512, 2);
        wg_fence();
#pragma unroll
        for (int k = 0; k < 4; k++) { wg_ss_n88<0, 88>(acc, da + 2 * k, db + 64 * k); wg_ss_n88<44, 88>(acc, da + 512 + 2 * k, db + 64 * k); }
        wg_commit();
        wg_wait<0>();
        if (tid == 0) { if (c < 4) mbar_arrive(BAR(B_WEMPTY + 8 + c)); mbar_arrive_both(BAR(B_XEMPTY + c)); }
      }
      regfence(acc);
      if (tid == 0) TS(9);
      uint4* z1p = g_z1 + blockIdx.x * 11 * 128 + tid;
#pragma unroll
      for (int q = 0; q < 11; q++) {
        uint4 v;
        v.x = pack_bf16(gelu_tanh(acc[8 * q + 0]), gelu_tanh(acc[8 * q + 1]));
        v.y = pack_bf16(gelu_tanh(acc[8 * q + 2]), gelu_tanh(acc[8 * q + 3]));
        v.z = pack_bf16(gelu_tanh(acc[8 * q + 4]), gelu_tanh(acc[8 * q + 5]));
        v.w = pack_bf16(gelu_tanh(acc[8 * q + 6]), gelu_tanh(acc[8 * q + 7]));
        z1p[q * 128] = v;
      }
    }
    if (tid == 0) TS(10);
    int st = 0, ph = 0;
    {
#pragma unroll
      for (int k = 0; k < 88; k++) acc[k] = 0.f;
      regfence(acc);
#pragma unroll 1
      for (int n = 0; n < 32; n++) {
        mbar_wait(BAR(B_RFULL + st), ph);
        const uint64_t da = mkdesc(sb + SM_RING + st * RSTAGE, 16, 1024, 1);
        const uint64_t db = mkdesc(sb + SM_RING + st * RSTAGE + 16384, 1408, 128, 0);
#pragma unroll
        for (int k = 0; k < 4; k++) {
          wg_fence();
          wg_ss_n88<0, 88>(acc, da + 2 * k, db + 176 * k);
          wg_ss_n88<44, 88>(acc, da + 512 + 2 * k, db + 176 * k);
          wg_commit();
          wg_wait<0>();
        }
        if (tid == 0) mbar_arrive_both(BAR(B_REMPTY + st));
        if (++st == 3) { st = 0; ph ^= 1; }
      }
      regfence(acc);
      if (tid == 0) TS(11);
      float bs[4], og[4];
#pragma unroll
      for (int r = 0; r < 4; r++) {
        const int row = (r >> 1) * 64 + w * 16 + (r & 1) * 8 + g;
        bs[r] = __bfloat162float(prm.b_sp[bi * 128 + row]);
        og[r] = 1.f - ldsf(sb + SM_G + row * 4);
      }
      const uint4* z1p = g_z1 + blockIdx.x * 11 * 128 + tid;
      uint32_t* up = reinterpret_cast<uint32_t*>(g_u) + bi * 11 * 4096 + w * 512 + lane;
#pragma unroll
      for (int q = 0; q < 11; q++) {
        const uint4 zv = z1p[q * 128];
        const uint32_t zz[4] = {zv.x, zv.y, zv.z, zv.w};
#pragma unroll
        for (int e = 0; e < 4; e++) {
          const int k = 8 * q + 2 * e, hf = k / 44, c8 = (k % 44) / 4, r8 = ((k % 44) >> 1) & 1, r = hf * 2 + r8;
          const int cb = 11 * bj + c8;
          uint32_t v = pack_bf16(bf_lo(zz[e]) * (acc[k] + bs[r]) * og[r], bf_hi(zz[e]) * (acc[k + 1] + bs[r]) * og[r]);
          if (c8 >= 9 && bj == 7) v = 0;
          up[(cb >> 3) * 4096 + (hf * 8 + r8) * 256 + (cb & 7) * 32] = v;
        }
      }
      fence_async();
      bar_sync(4, 128);
      if (tid == 0) red_release(&g_ucnt[bi * 32]);
    }
    if (tid == 0) TS(12);
    {
      float oc[64];
#pragma unroll
      for (int k = 0; k < 64; k++) oc[k] = 0.f;
      regfence(oc);
#pragma unroll 1
      for (int n = 0; n < 11; n++) {
        mbar_wait(BAR(B_RFULL + st), ph);
        const uint64_t da = mkdesc(sb + SM_RING + st * RSTAGE, 128, 1024, 0);
        const uint64_t db = mkdesc(sb + SM_RING + st * RSTAGE + 16384, 8192, 1024, 1);
#pragma unroll
        for (int k = 0; k < 4; k++) {
          wg_fence();
          wg_ss_n64<0, 64>(oc, da + 16 * k, db + 128 * k);
          wg_ss_n64<32, 64>(oc, da + 512 + 16 * k, db + 128 * k);
          wg_commit();
          wg_wait<0>();
        }
        if (tid == 0) mbar_arrive_both(BAR(B_REMPTY + st));
        if (++st == 3) { st = 0; ph ^= 1; }
      }
      if (tid == 0) TS(13);
      mbar_wait(BAR(B_WOFULL), 0);
#pragma unroll 1
      for (int c = 0; c < 8; c++) {
        mbar_wait(BAR(B_OFULL + c), 0);
        const uint64_t da = mkdesc(sb + SM_K + c * 16384, 128, 1024, 0);
        const uint64_t db = mkdesc(sb + SM_RING + c * 8192, 8192, 1024, 1);
        wg_fence();
#pragma unroll
        for (int k = 0; k < 4; k++) { wg_ss_n64<0, 64>(oc, da + 16 * k, db + 128 * k); wg_ss_n64<32, 64>(oc, da + 512 + 16 * k, db + 128 * k); }
        wg_commit();
      }
      wg_wait<0>();
      regfence(oc);
      if (tid == 0) TS(14);
      uint32_t* op = reinterpret_cast<uint32_t*>(prm.out) + (bi * 128 + w * 16 + g) * 256 + bj * 32 + t4;
#pragma unroll
      for (int k = 0; k < 64; k += 2) {
        const int hf = k / 32, c8 = (k % 32) / 4, r8 = (k >> 1) & 1;
        op[(hf * 64 + r8 * 8) * 256 + c8 * 4] = pack_bf16(oc[k], oc[k + 1]);
      }
      if (tid == 0) TS(15);
    }
  } else {
    asm volatile("setmaxnreg.inc.sync.aligned.u32 112;");
    const int w = tid >> 5, g = lane >> 2, t4 = lane & 3;
    if (wg < 2) {
      float acc[44];
#pragma unroll
      for (int k = 0; k < 44; k++) acc[k] = 0.f;
      regfence(acc);
#pragma unroll 1
      for (int c = 0; c < 8; c++) {
        mbar_wait(BAR(B_XFULL + c), 0);
        mbar_wait(BAR(B_WFULL + c), 0);
        if (threadIdx.x == 0) TS(48 + c);
        const uint64_t da = mkdesc(sb + SM_K + c * 16384 + wg * 8192, 16, 1024, 1);
        const uint64_t db = mkdesc(sb + SM_RING + (c & 3) * WSLOT, 4096, 512, 2);
        wg_fence();
#pragma unroll
        for (int k = 0; k < 4; k++) wg_ss_n88<0, 44>(acc, da + 2 * k, db + 64 * k);
        wg_commit();
        wg_wait<0>();
        if (tid == 0) mbar_arrive(BAR(B_WEMPTY + c));
      }
      regfence(acc);
      if (tid == 0) TS(16 + wg);
      const bool last = bj == 7;
      float s0 = 0.f, s1 = 0.f;
#pragma unroll
      for (int k = 0; k < 44; k++) {
        acc[k] = gelu_tanh(acc[k]);
        if (k & 2) s1 += acc[k]; else s0 += acc[k];
      }
      s0 += __shfl_xor_sync(0xffffffffu, s0, 1); s0 += __shfl_xor_sync(0xffffffffu, s0, 2);
      s1 += __shfl_xor_sync(0xffffffffu, s1, 1); s1 += __shfl_xor_sync(0xffffffffu, s1, 2);
      const float inv_n = last ? (1.f / 72.f) : (1.f / 88.f);
      const float m0 = s0 * inv_n, m1 = s1 * inv_n;
      float v0 = 0.f, v1 = 0.f;
#pragma unroll
      for (int k = 0; k < 44; k++) {
        float d = acc[k] - ((k & 2) ? m1 : m0);
        if (k >= 36 && last) d = 0.f;
        if (k & 2) v1 = fmaf(d, d, v1); else v0 = fmaf(d, d, v0);
      }
      v0 += __shfl_xor_sync(0xffffffffu, v0, 1); v0 += __shfl_xor_sync(0xffffffffu, v0, 2);
      v1 += __shfl_xor_sync(0xffffffffu, v1, 1); v1 += __shfl_xor_sync(0xffffffffu, v1, 2);
      const int r0 = wg * 64 + w * 16 + g;
      if (threadIdx.x == 0) TS(67);
      if (t4 == 0) {
        g_lnstat[(bi * 8 + bj) * 128 + r0] = make_float2(m0, v0);
        g_lnstat[(bi * 8 + bj) * 128 + r0 + 8] = make_float2(m1, v1);
      }
      bar_sync(1 + wg, 128);
      mbar_wait(BAR(B_EPOCH), 0);
      const unsigned ep1 = lds32(sb + SM_MISC + 4 * M_EPOCH) + 1;
      if (tid == 0) { red_release(&g_statcnt[(bi * 2 + wg) * 32]); TS(18 + wg); }
      mbar_wait(BAR(B_STAT + wg), 0);
      if (threadIdx.x == 0) TS(68);
      float mean[2], rstd[2];
#pragma unroll
      for (int r = 0; r < 2; r++) {
        const float2 a = __ldcg(&g_lnstat[(bi * 8 + 2 * t4) * 128 + r0 + 8 * r]);
        const float2 b = __ldcg(&g_lnstat[(bi * 8 + 2 * t4 + 1) * 128 + r0 + 8 * r]);
        const float nb = t4 == 3 ? 72.f : 88.f;
        float sm = fmaf(a.x, 88.f, b.x * nb);
        sm += __shfl_xor_sync(0xffffffffu, sm, 1); sm += __shfl_xor_sync(0xffffffffu, sm, 2);
        const float mu = sm * (1.f / 688.f);
        const float da = a.x - mu, db = b.x - mu;
        float m2 = a.y + b.y + 88.f * da * da + nb * db * db;
        m2 += __shfl_xor_sync(0xffffffffu, m2, 1); m2 += __shfl_xor_sync(0xffffffffu, m2, 2);
        mean[r] = mu;
        rstd[r] = rsqrtf(fmaf(m2, 1.f / 688.f, 1e-5f));
      }
      uint32_t* zp = reinterpret_cast<uint32_t*>(g_z2n) + (bj * 32 + bi * 2 + wg) * 2816 + w * 704 + lane;
#pragma unroll
      for (int k = 0; k < 44; k += 2) {
        const int r = (k >> 1) & 1, c8 = k >> 2;
        uint32_t v = pack_bf16((acc[k] - mean[r]) * rstd[r], (acc[k + 1] - mean[r]) * rstd[r]);
        if (c8 >= 9 && last) v = 0;
        zp[r * 352 + c8 * 32] = v;
      }
      if (threadIdx.x == 0) TS(69);
      fence_async();
      bar_sync(1 + wg, 128);
      if (tid == 0) { st_release(&g_zflag[bj * 32 + bi * 2 + wg], ep1); TS(20 + wg); }
    } else {
      const int pair = bi * 4 + (bj >> 1);
      {
        float kv[16];
#pragma unroll
        for (int k = 0; k < 16; k++) kv[k] = 0.f;
        regfence(kv);
        mbar_wait(BAR(B_WKV), 0);
#pragma unroll 1
        for (int c = 0; c < 8; c++) {
          mbar_wait(BAR(B_XFULL + c), 0);
          const uint64_t da = mkdesc(sb + SM_Q + c * 2048, 0, 256, 3);
          const uint64_t db = mkdesc(sb + SM_K + c * 16384 + (bj >> 1) * 4096, 16, 1024, 1);
          wg_fence();
#pragma unroll
          for (int k = 0; k < 4; k++) wg_ss_n32t<0, 16>(kv, da + 32 * k, db + 2 * k);
          wg_commit();
        }
        wg_wait<0>();
        regfence(kv);
        if (tid == 0) TS(22);
        const uint32_t sT = sb + SM_Q, sH = sb + SM_Q + 4096;
        bar_sync(3, 128);
        if (w == 0) {
#pragma unroll
          for (int k = 0; k < 16; k++) {
            const int tok = (k >> 2) * 8 + 2 * t4 + (k & 1), d = g + ((k >> 1) & 1) * 8;
            sts32(sT + (tok * 17 + d) * 4, __float_as_uint(__bfloat162float(__float2bfloat16_rn(kv[k]))));
          }
        }
        bar_sync(3, 128);
        if (tid == 0) TS(64);
        const int tok = (tid & 63) >> 1, hf = tid & 1;
        const uint32_t inner = (pair & 7) * 16;
        if (rank == 0) {
          if (tid < 48) {
            const int d = tid & 15, sg = tid >> 4, j0 = sg == 0 ? 0 : (sg == 1 ? 10 : 22), j1 = sg == 0 ? 10 : (sg == 1 ? 22 : 32);
            float kx[12], run = 0.f;
#pragma unroll
            for (int e = 0; e < 12; e++) kx[e] = ldsf(sT + (min(j0 + e, 31) * 17 + d) * 4);
#pragma unroll
            for (int e = 0; e < 12; e++) {
              __half hv;
              if (pair < NP) { hv = __float2half_rn(fmaf(kx[e], 16.f, -run)); run += __half2float(hv); }
              else hv = __float2half_rn(kx[e] * 0.125f);
              if (j0 + e < j1) sts16(sH + ((j0 + e) * 16 + d) * 2, __half_as_ushort(hv));
            }
          } else if (w == 2) {
            float n2 = 0.f;
#pragma unroll
            for (int d = 0; d < 16; d++) { const float kx = ldsf(sT + (lane * 17 + d) * 4); n2 = fmaf(kx, kx, n2); }
            if (!(n2 <= 3.0e38f)) n2 = 3.0e38f;
#pragma unroll
            for (int m = 16; m > 0; m >>= 1) n2 = fmaxf(n2, __shfl_xor_sync(0xffffffffu, n2, m));
            if (lane < 16) g_kvstat[blockIdx.x * 16 + lane] = n2;
          }
          bar_sync(3, 128);
          const uint32_t off = tok * 2048 + (pair >> 3) * 256 + hf * 128 + inner;
          if (tid < 64) g_kimg[off >> 4] = lds128(sH + tok * 32 + hf * 16);
          else {
            float f[8];
#pragma unroll
            for (int e = 0; e < 8; e++) f[e] = ldsf(sT + (tok * 17 + hf * 8 + e) * 4);
            g_kbf[off >> 4] = make_uint4(pack_bf16(f[0], f[1]), pack_bf16(f[2], f[3]), pack_bf16(f[4], f[5]), pack_bf16(f[6], f[7]));
          }
        } else {
          if (tid < 64) {
            float f[8];
#pragma unroll
            for (int e = 0; e < 8; e++) f[e] = ldsf(sT + (tok * 17 + hf * 8 + e) * 4);
            const uint32_t sbo = 256 * (4 * tok + (pair >> 4) + 1);
            const uint32_t off = (hf ? SM_ONES + sbo : SM_ONES - sbo) + ((pair >> 3) & 1) * 128 + inner;
            g_kimg[off >> 4] = make_uint4(pack_bf16(f[0], f[1]), pack_bf16(f[2], f[3]), pack_bf16(f[4], f[5]), pack_bf16(f[6], f[7]));
          } else if (tid < 80) {
            float vm = 0.f;
#pragma unroll 8
            for (int jj = 0; jj < 32; jj++) { float a = fabsf(ldsf(sT + (jj * 17 + tid - 64) * 4)); if (!(a <= 3.0e38f)) a = 3.0e38f; vm = fmaxf(vm, a); }
            g_kvstat[blockIdx.x * 16 + tid - 64] = vm;
          } else if (tid >= 96 && tid < 112 && pair == 0) {
            g_kimg[(SM_ONES >> 4) + tid - 96] = make_uint4(0x3F803F80u, 0x3F803F80u, 0x3F803F80u, 0x3F803F80u);
          }
        }
        if (tid == 0) TS(65);
        fence_async();
        bar_sync(3, 128);
        if (tid == 0) { TS(66); red_release(&g_kvcnt[0]); TS(23); }
      }
      float qa[64];
#pragma unroll
      for (int k = 0; k < 64; k++) qa[k] = 0.f;
      regfence(qa);
#pragma unroll 1
      for (int c = 0; c < 8; c++) {
        mbar_wait(BAR(B_WFULL + 8 + c), 0);
        const uint64_t da = mkdesc(sb + SM_K + c * 16384, 16, 1024, 1);
        const uint64_t db = mkdesc(sb + SM_RING + (c & 3) * WSLOT + 12288, 8192, 1024, 1);
        wg_fence();
#pragma unroll
        for (int k = 0; k < 4; k++) { wg_ss_n64<0, 64>(qa, da + 2 * k, db + 128 * k); wg_ss_n64<32, 64>(qa, da + 512 + 2 * k, db + 128 * k); }
        wg_commit();
        wg_wait<0>();
        if (tid == 0) { if (c < 4) mbar_arrive(BAR(B_WEMPTY + 8 + c)); mbar_arrive_both(BAR(B_XEMPTY + c)); }
      }
      regfence(qa);
      if (tid == 0) TS(24);
      uint32_t qb[32];
      float n2 = 0.f;
#pragma unroll
      for (int k = 0; k < 32; k++) qb[k] = pack_bf16(qa[2 * k], qa[2 * k + 1]);
#pragma unroll
      for (int k = 0; k < 16; k++) {
        const uint32_t a = qb[4 * (k >> 1) + (k & 1)], b = qb[4 * (k >> 1) + (k & 1) + 2];
        float s = bf_lo(a) * bf_lo(a);
        s = fmaf(bf_hi(a), bf_hi(a), s); s = fmaf(bf_lo(b), bf_lo(b), s); s = fmaf(bf_hi(b), bf_hi(b), s);
        s += __shfl_xor_sync(0xffffffffu, s, 1); s += __shfl_xor_sync(0xffffffffu, s, 2);
        if (!(s <= 3.0e38f)) s = 3.0e38f;
        n2 = fmaxf(n2, s);
      }
#pragma unroll
      for (int m = 16; m > 2; m >>= 1) n2 = fmaxf(n2, __shfl_xor_sync(0xffffffffu, n2, m));
      if (lane == 0) sts32(sb + SM_MISC + 4 * (M_RED + w), __float_as_uint(n2));
      if (tid == 0) TS(72);
      mbar_wait(BAR(B_KSTAT), 0);
      bar_sync(3, 128);
      const float qn2 = fmaxf(fmaxf(ldsf(sb + SM_MISC + 4 * M_RED), ldsf(sb + SM_MISC + 4 * (M_RED + 1))),
                              fmaxf(ldsf(sb + SM_MISC + 4 * (M_RED + 2)), ldsf(sb + SM_MISC + 4 * (M_RED + 3))));
      const float kn2 = ldsf(sb + SM_MISC + 4 * M_KN2);
      constexpr float SC = QSCALE * 0.125f;
      const bool fast = lds32(sb + SM_MISC + 4 * M_VOK) && qn2 <= 4.0e8f && kn2 <= 4.0e6f && qn2 * kn2 * (SC * SC) <= BOUND * BOUND;
#pragma unroll
      for (int tq = 0; tq < 8; tq++) {
        uint32_t r[4];
#pragma unroll
        for (int e = 0; e < 4; e++) {
          const uint32_t v = qb[(tq & 1) * 16 + (tq >> 1) * 4 + e];
          r[e] = fast ? pack_f16(bf_lo(v) * QSCALE, bf_hi(v) * QSCALE) : v;
        }
        sts128(sb + SM_Q + tq * 2048 + tid * 16, r[0], r[1], r[2], r[3]);
      }
      if (tid == 0) { sts32(sb + SM_MISC + 4 * M_FAST, fast ? 1u : 0u); mbar_arrive(BAR(B_DEC)); }
    }
    bar_sync(5, 512);
    if (tid == 0) TS(25 + wg);
#pragma unroll 1
    for (int c = 0; c < 8; c++) mbar_wait(BAR(B_KVFULL + c), 0);
    if (tid == 0) TS(28 + wg);
    const uint64_t dk0 = mkdesc(sb + SM_K, 128, 256, 0);
    const uint64_t dv0 = mkdesc(sb + SM_ONES - 256, 128, 256, 0);
    const uint64_t vstep = prm.vstep;
    float o[12], s[32];
    uint32_t q[4], p0[16], p1[16];
    if (lds32(sb + SM_MISC + 4 * M_FAST)) {
      const uint32_t mlo = prm.mlo, mhi = prm.mhi;
      uint64_t dk = dk0, dv = dv0;
#define STEP(PIN, POUT) { wg_fence(); issue_qk(s, q, dk); dk += 128; wg_commit(); issue_pv(o, PIN, dv, vstep); wg_commit(); \
                          wg_wait<1>(); regfence(s); softmax_step(s, POUT, mlo, mhi); wg_wait<0>(); }
#pragma unroll 1
      for (int sg = wg * 8; sg < wg * 8 + 8; sg++) {
        const int tau = sg / 3, seg = sg - tau * 3;
        int n2 = seg == 1 ? 6 : 5;
#pragma unroll
        for (int k = 0; k < NP / 2; k++) s[k] = MAGIC_C;
        if (sg == wg * 8 || seg == 0) {
          const int j0 = seg == 0 ? 0 : (seg == 1 ? 10 : 22);
          dk = dk0 + 128 * j0;
          dv = dv0 + VSTEP * (4 * j0);
          const uint4 qv = lds128(sb + SM_Q + tau * 2048 + tid * 16);
          q[0] = qv.x; q[1] = qv.y; q[2] = qv.z; q[3] = qv.w;
#pragma unroll
          for (int k = 0; k < 12; k++) o[k] = 0.f;
          regfence(o); regfence(s);
          wg_fence(); issue_qk(s, q, dk); dk += 128; wg_commit();
          wg_wait<0>(); regfence(s);
          softmax_step(s, p0, mlo, mhi);
          STEP(p0, p1);
          n2--;
        }
        regfence(s);
#pragma unroll 1
        for (; n2 > 0; n2--) { STEP(p1, p0); STEP(p0, p1); }
        if (sg == wg * 8 + 7 || seg == 2) {
          wg_fence(); issue_pv(o, p1, dv, vstep); wg_commit();
          wg_wait<0>(); regfence(o);
          if (sg == 8 || sg == 17) {
            float4* pp = g_part + (blockIdx.x * 2 + (wg - 1)) * 384 + tid;
            pp[0] = make_float4(o[0], o[1], o[2], o[3]); pp[128] = make_float4(o[4], o[5], o[6], o[7]); pp[256] = make_float4(o[8], o[9], o[10], o[11]);
            __threadfence_block();
            bar_arrive(5 + wg, 256);
          } else {
            if (sg == 7 || sg == 15) {
              bar_sync(6 + wg, 256);
              const float4* pp = g_part + (blockIdx.x * 2 + wg) * 384 + tid;
              const float4 a = pp[0], b = pp[128], c = pp[256];
              o[0] += a.x; o[1] += a.y; o[2] += a.z; o[3] += a.w; o[4] += b.x; o[6] += b.z; o[8] += c.x; o[9] += c.y; o[10] += c.z; o[11] += c.w;
            }
            store_o_tile(o, bi, bj, tau, tid, sb);
          }
        }
      }
#undef STEP
    } else {
      mbar_wait(BAR(B_KFB), 0);
      constexpr float SC = 0.25f * 1.4426950408889634f;
#pragma unroll 1
      for (int tau = wg * 3; tau < wg * 3 + 3 && tau < 8; tau++) {
        const uint4 qv = lds128(sb + SM_Q + tau * 2048 + tid * 16);
        float m0 = -INFINITY, m1 = -INFINITY;
#pragma unroll
        for (int k = 0; k < 12; k++) o[k] = 0.f;
        uint64_t dv = dv0;
#pragma unroll 1
        for (int j = 0; j < 32; j++) {
          regfence(s);
          wg_fence(); wg_qkb_n64<0, 0, 32>(s, qv.x, qv.y, qv.z, qv.w, dk0 + 128 * j); wg_commit();
          wg_wait<0>(); regfence(s);
          float x0 = m0, x1 = m1;
#pragma unroll
          for (int k = 0; k < 32; k++) { s[k] *= SC; if (k & 2) x1 = fmaxf(x1, s[k]); else x0 = fmaxf(x0, s[k]); }
          x0 = fmaxf(x0, __shfl_xor_sync(0xffffffffu, x0, 1)); x0 = fmaxf(x0, __shfl_xor_sync(0xffffffffu, x0, 2));
          x1 = fmaxf(x1, __shfl_xor_sync(0xffffffffu, x1, 1)); x1 = fmaxf(x1, __shfl_xor_sync(0xffffffffu, x1, 2));
          const float c0 = ex2(m0 - x0), c1 = ex2(m1 - x1);
          m0 = x0; m1 = x1;
#pragma unroll
          for (int k = 0; k < 12; k++) o[k] *= (k & 2) ? c1 : c0;
#pragma unroll
          for (int k = 0; k < 16; k++) { const float m = (k & 1) ? m1 : m0; p0[k] = exp_mufu(s[2 * k] - m, s[2 * k + 1] - m); }
          regfence(o);
          wg_fence(); issue_pv(o, p0, dv, vstep); wg_commit();
          wg_wait<0>(); regfence(o);
        }
        store_o_tile(o, bi, bj, tau, tid, sb);
      }
    }
    fence_async();
    bar_sync(1 + wg, 128);
    if (tid == 0) { red_release(&g_ocnt[bi * 32]); TS(31 + wg); }
  }
  __syncwarp();
  asm volatile("barrier.cluster.arrive.relaxed;" ::: "memory");
  asm volatile("barrier.cluster.wait;" ::: "memory");
}

typedef CUresult (*EncodeFn)(CUtensorMap*, CUtensorMapDataType, cuuint32_t, void*, const cuuint64_t*, const cuuint64_t*,
                             const cuuint32_t*, const cuuint32_t*, CUtensorMapInterleave, CUtensorMapSwizzle,
                             CUtensorMapL2promotion, CUtensorMapFloatOOBfill);

void make_map(EncodeFn enc, CUtensorMap* tm, const void* base, uint64_t cols, uint64_t rows, uint32_t bc, uint32_t br, CUtensorMapSwizzle sw) {
  cuuint64_t gd[2] = {cols, rows};
  cuuint64_t gs[1] = {cols * 2};
  cuuint32_t bd[2] = {bc, br};
  cuuint32_t es[2] = {1, 1};
  enc(tm, CU_TENSOR_MAP_DATA_TYPE_BFLOAT16, 2, const_cast<void*>(base), gd, gs, bd, es, CU_TENSOR_MAP_INTERLEAVE_NONE, sw,
      CU_TENSOR_MAP_L2_PROMOTION_L2_128B, CU_TENSOR_MAP_FLOAT_OOB_FILL_NONE);
}

}

extern "C" void kernel_launch(void* const* d_in, const int* in_sizes, int n_in, void* d_out, int out_size) {
  (void)in_sizes; (void)n_in; (void)out_size;
  static EncodeFn enc = nullptr;
  if (!enc) {
    void* fn = nullptr;
    cudaDriverEntryPointQueryResult qr;
    cudaGetDriverEntryPoint("cuTensorMapEncodeTiled", &fn, cudaEnableDefault, &qr);
    enc = (EncodeFn)fn;
    cudaFuncSetAttribute(fused_kernel, cudaFuncAttributeMaxDynamicSharedMemorySize, SMEM_BYTES);
  }
  CUtensorMap tx, tq, tk, tv, tin, tsp, tout, to;
  make_map(enc, &tx, d_in[0], 512, 2048, 64, 64, CU_TENSOR_MAP_SWIZZLE_128B);
  make_map(enc, &tq, d_in[1], 512, 512, 64, 64, CU_TENSOR_MAP_SWIZZLE_128B);
  make_map(enc, &tk, d_in[2], 16, 512, 16, 256, CU_TENSOR_MAP_SWIZZLE_32B);
  make_map(enc, &tv, d_in[3], 16, 512, 16, 256, CU_TENSOR_MAP_SWIZZLE_32B);
  make_map(enc, &to, d_in[4], 512, 512, 64, 64, CU_TENSOR_MAP_SWIZZLE_128B);
  make_map(enc, &tin, d_in[6], 1376, 512, 32, 64, CU_TENSOR_MAP_SWIZZLE_64B);
  make_map(enc, &tsp, d_in[7], 2048, 2048, 64, 64, CU_TENSOR_MAP_SWIZZLE_128B);
  make_map(enc, &tout, d_in[9], 512, 688, 64, 64, CU_TENSOR_MAP_SWIZZLE_128B);
  Params prm;
  prm.gate_w = (const __nv_bfloat16*)d_in[10];
  prm.b_sp = (const __nv_bfloat16*)d_in[8];
  prm.w_sp = (const __nv_bfloat16*)d_in[7];
  prm.w_out = (const __nv_bfloat16*)d_in[9];
  prm.wo = (const __nv_bfloat16*)d_in[4];
  prm.w_in = (const __nv_bfloat16*)d_in[6];
  prm.wq = (const __nv_bfloat16*)d_in[1];
  prm.vstep = VSTEP;
  prm.mlo = 0x007F007Fu;
  prm.mhi = 0xFF80FF80u;
  prm.out = (__nv_bfloat16*)d_out;
  fused_kernel<<<NCTA, NTHREADS, SMEM_BYTES>>>(tx, tq, tk, tv, tin, tsp, tout, to, prm);
}
```

```cpp
#include <cuda_runtime.h>
#include <cuda.h>
#include <cuda_bf16.h>
#include <cuda_fp16.h>
#include <stdint.h>

namespace {

constexpr int NCTA = 128;
constexpr int NTHREADS = 640;
constexpr int NP = 40;
constexpr int NM = 64 - NP;
constexpr int SPIN_LIMIT = 1 << 18;

constexpr uint32_t SM_K = 0;
constexpr uint32_t SM_ONES = 98304;
constexpr uint32_t KV_BYTES = 131328;
constexpr uint32_t SM_BAR = 131328;
constexpr uint32_t SM_RING = 132096;
constexpr uint32_t RSTAGE = 27648;
constexpr uint32_t WSLOT = 20480;
constexpr uint32_t SM_Q = 215040;
constexpr uint32_t SM_G = 231424;
constexpr uint32_t SM_MISC = 231936;
constexpr uint32_t SMEM_BYTES = 232448;

constexpr int B_XFULL = 0, B_XEMPTY = 8, B_WFULL = 16, B_WEMPTY = 32, B_KVFULL = 44, B_OFULL = 52, B_RFULL = 60,
              B_REMPTY = 63, B_KFB = 66, B_KSTAT = 67, B_DEC = 68, B_WOFULL = 69, B_EPOCH = 70, B_ZOK = 71, B_Z1OK = 72;
constexpr int M_EPOCH = 0, M_KN2 = 1, M_VOK = 2, M_FAST = 3, M_RED = 4;

__device__ uint4 g_kimg[KV_BYTES / 16];
__device__ uint4 g_kbf[65536 / 16];
__device__ unsigned long long g_kvmax[32];
__device__ uint4 g_lnstat[16 * 8 * 128];
__device__ float g_gate[2048];
__device__ uint4 g_z2n[8 * 32 * 11264 / 16];
__device__ uint4 g_z1[16 * 88 * 128];
__device__ uint4 g_u[16 * 11 * 1024];
__device__ uint4 g_o[16 * 8 * 1024];
__device__ float4 g_part[NCTA * 2 * 3 * 128];
__device__ unsigned g_ticket;
__device__ unsigned g_kvcnt[32];
__device__ unsigned g_zcnt[32];
__device__ unsigned g_z1cnt[16 * 32];
__device__ unsigned g_ucnt[16 * 32];
__device__ unsigned g_ocnt[16 * 32];
#define TS(k) do { } while (0)

__device__ __forceinline__ void mbar_init(uint32_t a, uint32_t c) { asm volatile("mbarrier.init.shared::cta.b64 [%0], %1;" ::"r"(a), "r"(c) : "memory"); }
__device__ __forceinline__ void mbar_expect(uint32_t a, uint32_t b) { asm volatile("mbarrier.arrive.expect_tx.shared::cta.b64 _, [%0], %1;" ::"r"(a), "r"(b) : "memory"); }
__device__ __forceinline__ void mbar_arrive(uint32_t a) { asm volatile("mbarrier.arrive.shared::cta.b64 _, [%0];" ::"r"(a) : "memory"); }
__device__ __forceinline__ void mbar_arrive_both(uint32_t a) {
  asm volatile("{\n.reg .b32 ra;\nmapa.shared::cluster.u32 ra, %0, 0;\nmbarrier.arrive.shared::cluster.b64 _, [ra];\n"
               "mapa.shared::cluster.u32 ra, %0, 1;\nmbarrier.arrive.shared::cluster.b64 _, [ra];\n}" ::"r"(a) : "memory");
}
__device__ __forceinline__ void mbar_wait(uint32_t a, uint32_t ph) {
  uint32_t ok;
#pragma unroll 1
  for (int n = 0; n < SPIN_LIMIT; n++) {
    asm volatile("{\n.reg .pred p;\nmbarrier.try_wait.parity.shared::cta.b64 p, [%1], %2;\nselp.u32 %0, 1, 0, p;\n}" : "=r"(ok) : "r"(a), "r"(ph) : "memory");
    if (ok) break;
  }
}
__device__ __forceinline__ void tma2d(uint32_t dst, const CUtensorMap* tm, int c0, int c1, uint32_t bar) {
  asm volatile("cp.async.bulk.tensor.2d.shared::cluster.global.mbarrier::complete_tx::bytes [%0], [%1, {%3, %4}], [%2];"
               ::"r"(dst), "l"(tm), "r"(bar), "r"(c0), "r"(c1) : "memory");
}
__device__ __forceinline__ void tma2d_mc(uint32_t dst, const CUtensorMap* tm, int c0, int c1, uint32_t bar) {
  asm volatile("cp.async.bulk.tensor.2d.shared::cluster.global.mbarrier::complete_tx::bytes.multicast::cluster [%0], [%1, {%3, %4}], [%2], %5;"
               ::"r"(dst), "l"(tm), "r"(bar), "r"(c0), "r"(c1), "h"((uint16_t)3) : "memory");
}
__device__ __forceinline__ void tma2d_pf(const CUtensorMap* tm, int c0, int c1) {
  asm volatile("cp.async.bulk.prefetch.tensor.2d.L2.global [%0, {%1, %2}];" ::"l"(tm), "r"(c0), "r"(c1) : "memory");
}
__device__ __forceinline__ void bulk(uint32_t dst, const void* src, uint32_t bytes, uint32_t bar) {
  asm volatile("cp.async.bulk.shared::cluster.global.mbarrier::complete_tx::bytes [%0], [%1], %2, [%3];"
               ::"r"(dst), "l"(src), "r"(bytes), "r"(bar) : "memory");
}
__device__ __forceinline__ void bulk_mc(uint32_t dst, const void* src, uint32_t bytes, uint32_t bar) {
  asm volatile("cp.async.bulk.shared::cluster.global.mbarrier::complete_tx::bytes.multicast::cluster [%0], [%1], %2, [%3], %4;"
               ::"r"(dst), "l"(src), "r"(bytes), "r"(bar), "h"((uint16_t)3) : "memory");
}
__device__ __forceinline__ void l2_prefetch(const void* src, uint32_t bytes) { asm volatile("cp.async.bulk.prefetch.L2.global [%0], %1;" ::"l"(src), "r"(bytes) : "memory"); }
__device__ __forceinline__ void fence_async() { asm volatile("fence.proxy.async.global;" ::: "memory"); }
__device__ __forceinline__ void fence_async_smem() { asm volatile("fence.proxy.async.shared::cta;" ::: "memory"); }
__device__ __forceinline__ void bar_sync(int id, int n) { asm volatile("bar.sync %0, %1;" ::"r"(id), "r"(n) : "memory"); }
__device__ __forceinline__ void bar_arrive(int id, int n) { asm volatile("bar.arrive %0, %1;" ::"r"(id), "r"(n) : "memory"); }
__device__ __forceinline__ void red_release(unsigned* p) { asm volatile("red.release.gpu.global.add.u32 [%0], 1;" ::"l"(p) : "memory"); }
__device__ __forceinline__ void red_relaxed(unsigned* p) { asm volatile("red.relaxed.gpu.global.add.u32 [%0], 1;" ::"l"(p) : "memory"); }
__device__ __forceinline__ uint32_t ld_back(const void* p) { uint32_t v; asm volatile("ld.relaxed.gpu.global.u32 %0, [%1];" : "=r"(v) : "l"(p) : "memory"); return v; }
__device__ __forceinline__ void consume(uint32_t v, uint32_t sb) { if (v == 0xDEADBEEFu) asm volatile("st.shared.u32 [%0], %1;" ::"r"(sb + SM_MISC + 60), "r"(v) : "memory"); }
__device__ __forceinline__ void st_release(unsigned* p, unsigned v) { asm volatile("st.release.gpu.global.u32 [%0], %1;" ::"l"(p), "r"(v) : "memory"); }
__device__ __forceinline__ unsigned ld_acquire(const unsigned* p) { unsigned v; asm volatile("ld.acquire.gpu.global.u32 %0, [%1];" : "=r"(v) : "l"(p) : "memory"); return v; }
__device__ __forceinline__ void wait_ge(const unsigned* p, unsigned target) {
#pragma unroll 1
  for (int n = 0; n < SPIN_LIMIT; n++) {
    if ((int)(ld_acquire(p) - target) >= 0) break;
    __nanosleep(20);
  }
}
__device__ __forceinline__ void wg_fence() { asm volatile("wgmma.fence.sync.aligned;" ::: "memory"); }
__device__ __forceinline__ void wg_commit() { asm volatile("wgmma.commit_group.sync.aligned;" ::: "memory"); }
template <int N> __device__ __forceinline__ void wg_wait() { asm volatile("wgmma.wait_group.sync.aligned %0;" ::"n"(N) : "memory"); }
template <int n> __device__ __forceinline__ void regfence(float (&d)[n]) {
#pragma unroll
  for (int i = 0; i < n; i++) asm volatile("" : "+f"(d[i])::"memory");
}
__device__ __forceinline__ uint64_t mkdesc(uint32_t addr, uint32_t lbo, uint32_t sbo, int swz) {
  return (uint64_t)((addr & 0x3FFFF) >> 4) | ((uint64_t)(lbo >> 4) << 16) | ((uint64_t)(sbo >> 4) << 32) | ((uint64_t)swz << 62);
}
__device__ __forceinline__ uint32_t pack_bf16(float lo, float hi) { uint32_t r; asm("cvt.rn.bf16x2.f32 %0, %1, %2;" : "=r"(r) : "f"(hi), "f"(lo)); return r; }
__device__ __forceinline__ uint32_t pack_f16(float lo, float hi) { uint32_t r; asm("cvt.rn.f16x2.f32 %0, %1, %2;" : "=r"(r) : "f"(hi), "f"(lo)); return r; }
__device__ __forceinline__ float bf_lo(uint32_t v) { return __uint_as_float(v << 16); }
__device__ __forceinline__ float bf_hi(uint32_t v) { return __uint_as_float(v & 0xFFFF0000u); }
__device__ __forceinline__ float ex2(float x) { float r; asm("ex2.approx.ftz.f32 %0, %1;" : "=f"(r) : "f"(x)); return r; }
__device__ __forceinline__ float gelu_tanh(float x) {
  float u = x * fmaf(x * x, 0.0356774081f, 0.7978845608f), t;
  asm("tanh.approx.f32 %0, %1;" : "=f"(t) : "f"(u));
  float h = 0.5f * x;
  return fmaf(h, t, h);
}
__device__ __forceinline__ void sts32(uint32_t a, uint32_t v) { asm volatile("st.shared.u32 [%0], %1;" ::"r"(a), "r"(v) : "memory"); }
__device__ __forceinline__ void sts16(uint32_t a, uint16_t v) { asm volatile("st.shared.u16 [%0], %1;" ::"r"(a), "h"(v) : "memory"); }
__device__ __forceinline__ void sts128(uint32_t a, uint32_t x, uint32_t y, uint32_t z, uint32_t w) { asm volatile("st.shared.v4.u32 [%0], {%1,%2,%3,%4};" ::"r"(a), "r"(x), "r"(y), "r"(z), "r"(w) : "memory"); }
__device__ __forceinline__ uint32_t lds32(uint32_t a) { uint32_t v; asm volatile("ld.shared.u32 %0, [%1];" : "=r"(v) : "r"(a) : "memory"); return v; }
__device__ __forceinline__ float ldsf(uint32_t a) { return __uint_as_float(lds32(a)); }
__device__ __forceinline__ uint4 lds128(uint32_t a) { uint4 v; asm volatile("ld.shared.v4.u32 {%0,%1,%2,%3}, [%4];" : "=r"(v.x), "=r"(v.y), "=r"(v.z), "=r"(v.w) : "r"(a) : "memory"); return v; }

template<int OFF, int TOT> __device__ __forceinline__ void wg_ss_n88(float (&d)[TOT], uint64_t da, uint64_t db) {
  asm volatile("wgmma.mma_async.sync.aligned.m64n88k16.f32.bf16.bf16 {%0, %1, %2, %3, %4, %5, %6, %7, %8, %9, %10, %11, %12, %13, %14, %15, %16, %17, %18, %19, %20, %21, %22, %23, %24, %25, %26, %27, %28, %29, %30, %31, %32, %33, %34, %35, %36, %37, %38, %39, %40, %41, %42, %43}, %44, %45, 1, 1, 1, 0, 1;"
    : "+f"(d[OFF+0]), "+f"(d[OFF+1]), "+f"(d[OFF+2]), "+f"(d[OFF+3]), "+f"(d[OFF+4]), "+f"(d[OFF+5]), "+f"(d[OFF+6]), "+f"(d[OFF+7]),
      "+f"(d[OFF+8]), "+f"(d[OFF+9]), "+f"(d[OFF+10]), "+f"(d[OFF+11]), "+f"(d[OFF+12]), "+f"(d[OFF+13]), "+f"(d[OFF+14]), "+f"(d[OFF+15]),
      "+f"(d[OFF+16]), "+f"(d[OFF+17]), "+f"(d[OFF+18]), "+f"(d[OFF+19]), "+f"(d[OFF+20]), "+f"(d[OFF+21]), "+f"(d[OFF+22]), "+f"(d[OFF+23]),
      "+f"(d[OFF+24]), "+f"(d[OFF+25]), "+f"(d[OFF+26]), "+f"(d[OFF+27]), "+f"(d[OFF+28]), "+f"(d[OFF+29]), "+f"(d[OFF+30]), "+f"(d[OFF+31]),
      "+f"(d[OFF+32]), "+f"(d[OFF+33]), "+f"(d[OFF+34]), "+f"(d[OFF+35]), "+f"(d[OFF+36]), "+f"(d[OFF+37]), "+f"(d[OFF+38]), "+f"(d[OFF+39]),
      "+f"(d[OFF+40]), "+f"(d[OFF+41]), "+f"(d[OFF+42]), "+f"(d[OFF+43])
    : "l"(da), "l"(db));
}
template<int OFF, int TOT> __device__ __forceinline__ void wg_ss_n96(float (&d)[TOT], uint64_t da, uint64_t db) {
  asm volatile("wgmma.mma_async.sync.aligned.m64n96k16.f32.bf16.bf16 {%0, %1, %2, %3, %4, %5, %6, %7, %8, %9, %10, %11, %12, %13, %14, %15, %16, %17, %18, %19, %20, %21, %22, %23, %24, %25, %26, %27, %28, %29, %30, %31, %32, %33, %34, %35, %36, %37, %38, %39, %40, %41, %42, %43, %44, %45, %46, %47}, %48, %49, 1, 1, 1, 0, 1;"
    : "+f"(d[OFF+0]), "+f"(d[OFF+1]), "+f"(d[OFF+2]), "+f"(d[OFF+3]), "+f"(d[OFF+4]), "+f"(d[OFF+5]), "+f"(d[OFF+6]), "+f"(d[OFF+7]),
      "+f"(d[OFF+8]), "+f"(d[OFF+9]), "+f"(d[OFF+10]), "+f"(d[OFF+11]), "+f"(d[OFF+12]), "+f"(d[OFF+13]), "+f"(d[OFF+14]), "+f"(d[OFF+15]),
      "+f"(d[OFF+16]), "+f"(d[OFF+17]), "+f"(d[OFF+18]), "+f"(d[OFF+19]), "+f"(d[OFF+20]), "+f"(d[OFF+21]), "+f"(d[OFF+22]), "+f"(d[OFF+23]),
      "+f"(d[OFF+24]), "+f"(d[OFF+25]), "+f"(d[OFF+26]), "+f"(d[OFF+27]), "+f"(d[OFF+28]), "+f"(d[OFF+29]), "+f"(d[OFF+30]), "+f"(d[OFF+31]),
      "+f"(d[OFF+32]), "+f"(d[OFF+33]), "+f"(d[OFF+34]), "+f"(d[OFF+35]), "+f"(d[OFF+36]), "+f"(d[OFF+37]), "+f"(d[OFF+38]), "+f"(d[OFF+39]),
      "+f"(d[OFF+40]), "+f"(d[OFF+41]), "+f"(d[OFF+42]), "+f"(d[OFF+43]), "+f"(d[OFF+44]), "+f"(d[OFF+45]), "+f"(d[OFF+46]), "+f"(d[OFF+47])
    : "l"(da), "l"(db));
}
template<int OFF, int TOT> __device__ __forceinline__ void wg_ss_n64(float (&d)[TOT], uint64_t da, uint64_t db) {
  asm volatile("wgmma.mma_async.sync.aligned.m64n64k16.f32.bf16.bf16 {%0, %1, %2, %3, %4, %5, %6, %7, %8, %9, %10, %11, %12, %13, %14, %15, %16, %17, %18, %19, %20, %21, %22, %23, %24, %25, %26, %27, %28, %29, %30, %31}, %32, %33, 1, 1, 1, 0, 1;"
    : "+f"(d[OFF+0]), "+f"(d[OFF+1]), "+f"(d[OFF+2]), "+f"(d[OFF+3]), "+f"(d[OFF+4]), "+f"(d[OFF+5]), "+f"(d[OFF+6]), "+f"(d[OFF+7]),
      "+f"(d[OFF+8]), "+f"(d[OFF+9]), "+f"(d[OFF+10]), "+f"(d[OFF+11]), "+f"(d[OFF+12]), "+f"(d[OFF+13]), "+f"(d[OFF+14]), "+f"(d[OFF+15]),
      "+f"(d[OFF+16]), "+f"(d[OFF+17]), "+f"(d[OFF+18]), "+f"(d[OFF+19]), "+f"(d[OFF+20]), "+f"(d[OFF+21]), "+f"(d[OFF+22]), "+f"(d[OFF+23]),
      "+f"(d[OFF+24]), "+f"(d[OFF+25]), "+f"(d[OFF+26]), "+f"(d[OFF+27]), "+f"(d[OFF+28]), "+f"(d[OFF+29]), "+f"(d[OFF+30]), "+f"(d[OFF+31])
    : "l"(da), "l"(db));
}
template<int OFF, int TOT> __device__ __forceinline__ void wg_ss_n32t(float (&d)[TOT], uint64_t da, uint64_t db) {
  asm volatile("wgmma.mma_async.sync.aligned.m64n32k16.f32.bf16.bf16 {%0, %1, %2, %3, %4, %5, %6, %7, %8, %9, %10, %11, %12, %13, %14, %15}, %16, %17, 1, 1, 1, 1, 0;"
    : "+f"(d[OFF+0]), "+f"(d[OFF+1]), "+f"(d[OFF+2]), "+f"(d[OFF+3]), "+f"(d[OFF+4]), "+f"(d[OFF+5]), "+f"(d[OFF+6]), "+f"(d[OFF+7]),
      "+f"(d[OFF+8]), "+f"(d[OFF+9]), "+f"(d[OFF+10]), "+f"(d[OFF+11]), "+f"(d[OFF+12]), "+f"(d[OFF+13]), "+f"(d[OFF+14]), "+f"(d[OFF+15])
    : "l"(da), "l"(db));
}
template<int SCD, int OFF, int TOT> __device__ __forceinline__ void wg_qk_n16(float (&d)[TOT], uint32_t a0, uint32_t a1, uint32_t a2, uint32_t a3, uint64_t db) {
  asm volatile("wgmma.mma_async.sync.aligned.m64n16k16.f32.f16.f16 {%0, %1, %2, %3, %4, %5, %6, %7}, {%8,%9,%10,%11}, %12, %13, 1, 1, 0;"
    : "+f"(d[OFF+0]), "+f"(d[OFF+1]), "+f"(d[OFF+2]), "+f"(d[OFF+3]), "+f"(d[OFF+4]), "+f"(d[OFF+5]), "+f"(d[OFF+6]), "+f"(d[OFF+7])
    : "r"(a0), "r"(a1), "r"(a2), "r"(a3), "l"(db), "n"(SCD));
}
template<int SCD, int OFF, int TOT> __device__ __forceinline__ void wg_qk_n24(float (&d)[TOT], uint32_t a0, uint32_t a1, uint32_t a2, uint32_t a3, uint64_t db) {
  asm volatile("wgmma.mma_async.sync.aligned.m64n24k16.f32.f16.f16 {%0, %1, %2, %3, %4, %5, %6, %7, %8, %9, %10, %11}, {%12,%13,%14,%15}, %16, %17, 1, 1, 0;"
    : "+f"(d[OFF+0]), "+f"(d[OFF+1]), "+f"(d[OFF+2]), "+f"(d[OFF+3]), "+f"(d[OFF+4]), "+f"(d[OFF+5]), "+f"(d[OFF+6]), "+f"(d[OFF+7]),
      "+f"(d[OFF+8]), "+f"(d[OFF+9]), "+f"(d[OFF+10]), "+f"(d[OFF+11])
    : "r"(a0), "r"(a1), "r"(a2), "r"(a3), "l"(db), "n"(SCD));
}
template<int SCD, int OFF, int TOT> __device__ __forceinline__ void wg_qk_n32(float (&d)[TOT], uint32_t a0, uint32_t a1, uint32_t a2, uint32_t a3, uint64_t db) {
  asm volatile("wgmma.mma_async.sync.aligned.m64n32k16.f32.f16.f16 {%0, %1, %2, %3, %4, %5, %6, %7, %8, %9, %10, %11, %12, %13, %14, %15}, {%16,%17,%18,%19}, %20, %21, 1, 1, 0;"
    : "+f"(d[OFF+0]), "+f"(d[OFF+1]), "+f"(d[OFF+2]), "+f"(d[OFF+3]), "+f"(d[OFF+4]), "+f"(d[OFF+5]), "+f"(d[OFF+6]), "+f"(d[OFF+7]),
      "+f"(d[OFF+8]), "+f"(d[OFF+9]), "+f"(d[OFF+10]), "+f"(d[OFF+11]), "+f"(d[OFF+12]), "+f"(d[OFF+13]), "+f"(d[OFF+14]), "+f"(d[OFF+15])
    : "r"(a0), "r"(a1), "r"(a2), "r"(a3), "l"(db), "n"(SCD));
}
template<int SCD, int OFF, int TOT> __device__ __forceinline__ void wg_qk_n40(float (&d)[TOT], uint32_t a0, uint32_t a1, uint32_t a2, uint32_t a3, uint64_t db) {
  asm volatile("wgmma.mma_async.sync.aligned.m64n40k16.f32.f16.f16 {%0, %1, %2, %3, %4, %5, %6, %7, %8, %9, %10, %11, %12, %13, %14, %15, %16, %17, %18, %19}, {%20,%21,%22,%23}, %24, %25, 1, 1, 0;"
    : "+f"(d[OFF+0]), "+f"(d[OFF+1]), "+f"(d[OFF+2]), "+f"(d[OFF+3]), "+f"(d[OFF+4]), "+f"(d[OFF+5]), "+f"(d[OFF+6]), "+f"(d[OFF+7]),
      "+f"(d[OFF+8]), "+f"(d[OFF+9]), "+f"(d[OFF+10]), "+f"(d[OFF+11]), "+f"(d[OFF+12]), "+f"(d[OFF+13]), "+f"(d[OFF+14]), "+f"(d[OFF+15]),
      "+f"(d[OFF+16]), "+f"(d[OFF+17]), "+f"(d[OFF+18]), "+f"(d[OFF+19])
    : "r"(a0), "r"(a1), "r"(a2), "r"(a3), "l"(db), "n"(SCD));
}
template<int SCD, int OFF, int TOT> __device__ __forceinline__ void wg_qk_n48(float (&d)[TOT], uint32_t a0, uint32_t a1, uint32_t a2, uint32_t a3, uint64_t db) {
  asm volatile("wgmma.mma_async.sync.aligned.m64n48k16.f32.f16.f16 {%0, %1, %2, %3, %4, %5, %6, %7, %8, %9, %10, %11, %12, %13, %14, %15, %16, %17, %18, %19, %20, %21, %22, %23}, {%24,%25,%26,%27}, %28, %29, 1, 1, 0;"
    : "+f"(d[OFF+0]), "+f"(d[OFF+1]), "+f"(d[OFF+2]), "+f"(d[OFF+3]), "+f"(d[OFF+4]), "+f"(d[OFF+5]), "+f"(d[OFF+6]), "+f"(d[OFF+7]),
      "+f"(d[OFF+8]), "+f"(d[OFF+9]), "+f"(d[OFF+10]), "+f"(d[OFF+11]), "+f"(d[OFF+12]), "+f"(d[OFF+13]), "+f"(d[OFF+14]), "+f"(d[OFF+15]),
      "+f"(d[OFF+16]), "+f"(d[OFF+17]), "+f"(d[OFF+18]), "+f"(d[OFF+19]), "+f"(d[OFF+20]), "+f"(d[OFF+21]), "+f"(d[OFF+22]), "+f"(d[OFF+23])
    : "r"(a0), "r"(a1), "r"(a2), "r"(a3), "l"(db), "n"(SCD));
}
template<int SCD, int OFF, int TOT> __device__ __forceinline__ void wg_pv_n24(float (&d)[TOT], uint32_t a0, uint32_t a1, uint32_t a2, uint32_t a3, uint64_t db) {
  asm volatile("wgmma.mma_async.sync.aligned.m64n24k16.f32.bf16.bf16 {%0, %1, %2, %3, %4, %5, %6, %7, %8, %9, %10, %11}, {%12,%13,%14,%15}, %16, %17, 1, 1, 1;"
    : "+f"(d[OFF+0]), "+f"(d[OFF+1]), "+f"(d[OFF+2]), "+f"(d[OFF+3]), "+f"(d[OFF+4]), "+f"(d[OFF+5]), "+f"(d[OFF+6]), "+f"(d[OFF+7]),
      "+f"(d[OFF+8]), "+f"(d[OFF+9]), "+f"(d[OFF+10]), "+f"(d[OFF+11])
    : "r"(a0), "r"(a1), "r"(a2), "r"(a3), "l"(db), "n"(SCD));
}
template<int SCD, int OFF, int TOT> __device__ __forceinline__ void wg_qkb_n64(float (&d)[TOT], uint32_t a0, uint32_t a1, uint32_t a2, uint32_t a3, uint64_t db) {
  asm volatile("wgmma.mma_async.sync.aligned.m64n64k16.f32.bf16.bf16 {%0, %1, %2, %3, %4, %5, %6, %7, %8, %9, %10, %11, %12, %13, %14, %15, %16, %17, %18, %19, %20, %21, %22, %23, %24, %25, %26, %27, %28, %29, %30, %31}, {%32,%33,%34,%35}, %36, %37, 1, 1, 0;"
    : "+f"(d[OFF+0]), "+f"(d[OFF+1]), "+f"(d[OFF+2]), "+f"(d[OFF+3]), "+f"(d[OFF+4]), "+f"(d[OFF+5]), "+f"(d[OFF+6]), "+f"(d[OFF+7]),
      "+f"(d[OFF+8]), "+f"(d[OFF+9]), "+f"(d[OFF+10]), "+f"(d[OFF+11]), "+f"(d[OFF+12]), "+f"(d[OFF+13]), "+f"(d[OFF+14]), "+f"(d[OFF+15]),
      "+f"(d[OFF+16]), "+f"(d[OFF+17]), "+f"(d[OFF+18]), "+f"(d[OFF+19]), "+f"(d[OFF+20]), "+f"(d[OFF+21]), "+f"(d[OFF+22]), "+f"(d[OFF+23]),
      "+f"(d[OFF+24]), "+f"(d[OFF+25]), "+f"(d[OFF+26]), "+f"(d[OFF+27]), "+f"(d[OFF+28]), "+f"(d[OFF+29]), "+f"(d[OFF+30]), "+f"(d[OFF+31])
    : "r"(a0), "r"(a1), "r"(a2), "r"(a3), "l"(db), "n"(SCD));
}
template<int N, int SCD, int OFF, int TOT> __device__ __forceinline__ void wg_qk(float (&d)[TOT], const uint32_t (&q)[4], uint64_t db) {
  if constexpr (N == 16) wg_qk_n16<SCD, OFF, TOT>(d, q[0], q[1], q[2], q[3], db);
  if constexpr (N == 24) wg_qk_n24<SCD, OFF, TOT>(d, q[0], q[1], q[2], q[3], db);
  if constexpr (N == 32) wg_qk_n32<SCD, OFF, TOT>(d, q[0], q[1], q[2], q[3], db);
  if constexpr (N == 40) wg_qk_n40<SCD, OFF, TOT>(d, q[0], q[1], q[2], q[3], db);
  if constexpr (N == 48) wg_qk_n48<SCD, OFF, TOT>(d, q[0], q[1], q[2], q[3], db);
}

__device__ __forceinline__ uint32_t exp_mufu(float a, float b) { return pack_bf16(ex2(a), ex2(b)); }
__device__ __forceinline__ uint32_t exp_poly(float a, float b, uint32_t mlo, uint32_t mhi) {
  uint32_t u = __byte_perm(__float_as_uint(a), __float_as_uint(b), 0x6521), mh, e, p;
  asm("lop3.b32 %0, %1, %2, 0x3F003F00, 0xEA;" : "=r"(mh) : "r"(u), "r"(mlo));
  asm("lop3.b32 %0, %1, %2, 0x00020002, 0xEA;" : "=r"(e) : "r"(u), "r"(mhi));
  asm("fma.rn.bf16x2 %0, %1, %2, %3;" : "=r"(p) : "r"(u), "r"(mh), "r"(e));
  return p;
}
constexpr float MAGIC_C = 48948.0625f;
constexpr float QSCALE = 0.25f * 1.4426950408889634f * 8.f;
constexpr float BOUND = 80.f;

__device__ __forceinline__ void softmax_step(const float (&s)[32], uint32_t (&p)[16], uint32_t mlo, uint32_t mhi) {
  constexpr int PP = NP / 4;
  int ip = 0, im = PP;
#pragma unroll
  for (int i = 0; i < 16; i++) {
    if (((i + 1) * PP / 16) > (i * PP / 16)) { p[ip] = exp_poly(s[2 * ip], s[2 * ip + 1], mlo, mhi); ip++; }
    else { p[im] = exp_mufu(s[2 * im], s[2 * im + 1]); im++; }
  }
}
constexpr uint64_t VSTEP = ((uint64_t)16 << 32) - 16;
__device__ __forceinline__ void issue_qk(float (&s)[32], const uint32_t (&q)[4], uint64_t dk) {
  wg_qk<NM, 0, NP / 2, 32>(s, q, dk + NP * 2);
  wg_qk<NP, 1, 0, 32>(s, q, dk);
}
__device__ __forceinline__ void issue_pv(float (&o)[12], const uint32_t (&p)[16], uint64_t& dv, uint64_t vstep) {
#pragma unroll
  for (int c = 0; c < 4; c++) { wg_pv_n24<1, 0, 12>(o, p[4 * c], p[4 * c + 1], p[4 * c + 2], p[4 * c + 3], dv); dv += vstep; }
}

struct Params {
  const __nv_bfloat16* gate_w;
  const __nv_bfloat16* b_sp;
  const __nv_bfloat16* w_sp;
  const __nv_bfloat16* w_out;
  const __nv_bfloat16* wo;
  const __nv_bfloat16* w_in;
  const __nv_bfloat16* wq;
  const __nv_bfloat16* wk;
  const __nv_bfloat16* wv;
  uint64_t vstep;
  uint32_t mlo, mhi;
  __nv_bfloat16* out;
};

__device__ __forceinline__ uint32_t store_o_tile(const float (&o)[12], int bi, int bj, int tau, int tid, uint32_t sb) {
  const int half = tau & 1, hh = tau >> 1, w = tid >> 5, g = (tid & 31) >> 2;
  const int r0 = half * 64 + w * 16 + g;
  const float f0 = __fdividef(ldsf(sb + SM_G + r0 * 4), o[4]), f1 = __fdividef(ldsf(sb + SM_G + (r0 + 8) * 4), o[6]);
  uint32_t* dst = reinterpret_cast<uint32_t*>(g_o) + (bi * 8 + bj) * 4096 + (half * 8 + w * 2) * 256 + hh * 64 + (tid & 31);
  dst[0] = pack_bf16(o[0] * f0, o[1] * f0);
  dst[32] = pack_bf16(o[8] * f0, o[9] * f0);
  dst[256] = pack_bf16(o[2] * f1, o[3] * f1);
  dst[288] = pack_bf16(o[10] * f1, o[11] * f1);
  const int l = tid & 31;
  return ld_back(dst - l + ((l >> 3) & 1) * 256 + (l & 7) * 8);
}

__device__ __forceinline__ void phase1_q_z1(uint32_t sb, int half, int ai, int aj, int tid
) {
  const int w = tid >> 5, lane = tid & 31;
  auto BAR = [&](int k) { return sb + SM_BAR + 8u * k; };
  float qa[32], za[48];
#pragma unroll
  for (int k = 0; k < 32; k++) qa[k] = 0.f;
#pragma unroll
  for (int k = 0; k < 48; k++) za[k] = 0.f;
  regfence(qa); regfence(za);
#pragma unroll 1
  for (int c = 0; c < 8; c++) {
    mbar_wait(BAR(B_WFULL + 8 + c), 0);
    if (tid == 0 && half) TS(56 + c);
    const uint64_t da = mkdesc(sb + SM_K + c * 16384 + half * 8192, 16, 1024, 1);
    const uint64_t dz = mkdesc(sb + SM_RING + (c & 3) * WSLOT, 4096, 512, 2);
    const uint64_t dq = mkdesc(sb + SM_RING + (c & 3) * WSLOT + 12288, 8192, 1024, 1);
    wg_fence();
#pragma unroll
    for (int k = 0; k < 4; k++) { wg_ss_n64<0, 32>(qa, da + 2 * k, dq + 128 * k); wg_ss_n96<0, 48>(za, da + 2 * k, dz + 64 * k); }
    wg_commit();
    wg_wait<0>();
    if (tid == 0) { if (c < 4) mbar_arrive_both(BAR(B_WEMPTY + 8 + c)); mbar_arrive_both(BAR(B_XEMPTY + c)); }
  }
  regfence(qa); regfence(za);
  if (tid == 0) TS(half ? 9 : 24);
  uint32_t qb[16];
  float n2 = 0.f;
#pragma unroll
  for (int k = 0; k < 16; k++) qb[k] = pack_bf16(qa[2 * k], qa[2 * k + 1]);
#pragma unroll
  for (int k = 0; k < 8; k++) {
    const uint32_t a = qb[4 * (k >> 1) + (k & 1)], b = qb[4 * (k >> 1) + (k & 1) + 2];
    float s = bf_lo(a) * bf_lo(a);
    s = fmaf(bf_hi(a), bf_hi(a), s); s = fmaf(bf_lo(b), bf_lo(b), s); s = fmaf(bf_hi(b), bf_hi(b), s);
    s += __shfl_xor_sync(0xffffffffu, s, 1); s += __shfl_xor_sync(0xffffffffu, s, 2);
    if (!(s <= 3.0e38f)) s = 3.0e38f;
    n2 = fmaxf(n2, s);
  }
  n2 = __uint_as_float(__reduce_max_sync(0xffffffffu, __float_as_uint(n2)));
  if (lane == 0) sts32(sb + SM_MISC + 4 * (M_RED + half * 4 + w), __float_as_uint(n2));
  if (tid == 0 && !half) TS(72);
  mbar_wait(BAR(B_KSTAT), 0);
  bar_sync(8, 256);
  const uint4 ra = lds128(sb + SM_MISC + 4 * M_RED), rb = lds128(sb + SM_MISC + 4 * M_RED + 16);
  const float qn2 = __uint_as_float(max(max(max(ra.x, ra.y), max(ra.z, ra.w)), max(max(rb.x, rb.y), max(rb.z, rb.w))));
  const float kn2 = ldsf(sb + SM_MISC + 4 * M_KN2);
  constexpr float SC = QSCALE * 0.125f;
  const bool fast = lds32(sb + SM_MISC + 4 * M_VOK) && qn2 <= 4.0e8f && kn2 <= 4.0e6f && qn2 * kn2 * (SC * SC) <= BOUND * BOUND;
#pragma unroll
  for (int hh = 0; hh < 4; hh++) {
    uint32_t r[4];
#pragma unroll
    for (int e = 0; e < 4; e++) {
      const uint32_t v = qb[hh * 4 + e];
      r[e] = fast ? pack_f16(bf_lo(v) * QSCALE, bf_hi(v) * QSCALE) : v;
    }
    sts128(sb + SM_Q + (2 * hh + half) * 2048 + tid * 16, r[0], r[1], r[2], r[3]);
  }
  if (tid == 0 && !half) { sts32(sb + SM_MISC + 4 * M_FAST, fast ? 1u : 0u); mbar_arrive(BAR(B_DEC)); }
  bar_arrive(5, 512);
  if (half) bar_arrive(9, 256);
  const int fb0 = aj < 2 ? 8 * aj : 12 * aj - 8, nb = aj < 2 ? 8 : (aj == 7 ? 10 : 12);
  uint32_t* zp = reinterpret_cast<uint32_t*>(g_z1) + ((ai * 88 + fb0) * 16 + half * 8 + w * 2) * 32;
#pragma unroll
  for (int k = 0; k < 48; k += 2) {
    const uint32_t v = pack_bf16(gelu_tanh(za[k]), gelu_tanh(za[k + 1]));
    if ((k >> 2) < nb) zp[(k >> 2) * 512 + ((k >> 1) & 1) * 32 + lane] = v;
  }
  uint32_t chk = 0;
#pragma unroll
  for (int r = 0; r < 3; r++) {
    const int it = lane + 32 * r, c8 = it >> 3;
    if (c8 < nb) chk ^= ld_back(zp + c8 * 512 + (it & 7) * 8);
  }
  if (half && aj == 0) chk ^= ld_back(&g_gate[ai * 128 + tid]);
  consume(chk, sb);
  bar_sync(3 + half, 128);
  if (tid == 0) { red_relaxed(&g_z1cnt[ai * 32]); if (half) TS(10); }
}
#define TSARG

__global__ void __cluster_dims__(2, 1, 1) __launch_bounds__(NTHREADS, 1)
fused_kernel(const __grid_constant__ CUtensorMap tm_x, const __grid_constant__ CUtensorMap tm_wq,
             const __grid_constant__ CUtensorMap tm_win, const __grid_constant__ CUtensorMap tm_wsp,
             const __grid_constant__ CUtensorMap tm_wout, const __grid_constant__ CUtensorMap tm_wo, const Params prm) {
  extern __shared__ __align__(1024) uint8_t smem_raw[];
  const uint32_t sb = (uint32_t)__cvta_generic_to_shared(smem_raw);
  const int wg = __shfl_sync(0xffffffffu, (int)(threadIdx.x >> 7), 0);
  const int tid = threadIdx.x & 127;
  const int lane = threadIdx.x & 31;
  const int rank = blockIdx.x & 1;
  const int ai = (blockIdx.x >> 4) * 2 + rank, aj = (blockIdx.x >> 1) & 7;
  const int bi = blockIdx.x >> 3, bj = blockIdx.x & 7;
  auto BAR = [&](int k) { return sb + SM_BAR + 8u * k; };

  const int warp = __shfl_sync(0xffffffffu, (int)(threadIdx.x >> 5), 0);
  if (lane == 0) {
    if (warp == 16) {
      asm volatile("prefetch.tensormap [%0];" ::"l"(&tm_x) : "memory");
    } else if (warp == 18) {
      asm volatile("prefetch.tensormap [%0];" ::"l"(&tm_win) : "memory");
    } else if (warp == 19) {
      l2_prefetch(reinterpret_cast<const uint8_t*>(prm.w_in) + blockIdx.x * 11008, 11008);
      l2_prefetch(reinterpret_cast<const uint8_t*>(prm.wq) + blockIdx.x * 4096, 4096);
    } else if (warp < 16) {
#pragma unroll
      for (int r = 0; r < 5; r++) {
        const int k = warp + 16 * r;
        uint32_t cnt = 1;
        if (k >= B_XEMPTY && k < B_XEMPTY + 8) cnt = 4;
        if (k >= B_WEMPTY && k < B_WEMPTY + 12) cnt = 4;
        if (k >= B_REMPTY && k < B_REMPTY + 3) cnt = 2;
        mbar_init(BAR(k), cnt);
      }
      asm volatile("fence.mbarrier_init.release.cluster;" ::: "memory");
    }
  }
  if (threadIdx.x == 0) TS(34);
  __syncthreads();
  if (threadIdx.x == 0) TS(35);
  asm volatile("barrier.cluster.arrive.relaxed.aligned;" ::: "memory");
  if (warp != 16) asm volatile("barrier.cluster.wait.acquire.aligned;" ::: "memory");

  if (wg == 4) {
    asm volatile("setmaxnreg.dec.sync.aligned.u32 24;");
    const int pw = warp - 16;
    if (pw == 2) {
      if (lane == 0) {
#pragma unroll 1
        for (int f = 0; f < 16; f++) {
          if (f == 4) { TS(37); asm volatile("prefetch.tensormap [%0];" ::"l"(&tm_wq) : "memory"); }
          if (f >= 4) mbar_wait(BAR(B_WEMPTY + f - 4), 0);
          const uint32_t slot = sb + SM_RING + (f & 3) * WSLOT, bar = BAR(B_WFULL + f);
          const int k0 = (f & 7) * 64 + rank * 32;
          const bool three = f < 8 ? aj < 6 : aj >= 2;
          const int c0 = 32 * (f < 8 ? (aj < 6 ? 21 + 3 * aj : 27 + 2 * aj) : (aj < 2 ? 2 * aj : 3 * aj - 2));
          mbar_expect(bar, (three ? 12288 : 8192) + (f < 8 ? 0 : 8192));
          if (f >= 8) tma2d_mc(slot + 12288 + rank * 4096, &tm_wq, 64 * aj, k0, bar);
          tma2d_mc(slot + rank * 2048, &tm_win, c0, k0, bar);
          tma2d_mc(slot + 4096 + rank * 2048, &tm_win, c0 + 32, k0, bar);
          if (three) tma2d_mc(slot + 8192 + rank * 2048, &tm_win, c0 + 64, k0, bar);
        }
        TS(1);
      }
    } else if (pw == 3) {
      mbar_wait(BAR(B_EPOCH), 0);
      const unsigned ep1 = lds32(sb + SM_MISC + 4 * M_EPOCH) + 1;
      wait_ge(&g_zcnt[lane], ep1 * 8);
      __syncwarp();
      if (lane == 0) {
        mbar_arrive(BAR(B_ZOK));
        wait_ge(&g_z1cnt[bi * 32], ep1 * 16);
        mbar_arrive(BAR(B_Z1OK));
      }
    } else if (pw == 0) {
      if (lane == 0) {
        TS(0);
#pragma unroll 1
        for (int c = 0; c < 8; c++) {
          mbar_expect(BAR(B_XFULL + c), 16384);
          tma2d(sb + SM_K + c * 16384, &tm_x, c * 64, ai * 128, BAR(B_XFULL + c));
        }
        TS(36);
      }
      __syncwarp();
      asm volatile("barrier.cluster.wait.acquire.aligned;" ::: "memory");
      if (lane == 0) {
        asm volatile("prefetch.tensormap [%0];" ::"l"(&tm_wsp) : "memory");
        asm volatile("prefetch.tensormap [%0];" ::"l"(&tm_wout) : "memory");
        asm volatile("prefetch.tensormap [%0];" ::"l"(&tm_wo) : "memory");
        mbar_wait(BAR(B_XEMPTY), 0);
        tma2d_pf(&tm_wsp, (bj >> 1) * 64, bi * 128 + rank * 64);
        tma2d_pf(&tm_wsp, (bj >> 1) * 64 + 256, bi * 128 + rank * 64);
        mbar_wait(BAR(B_XEMPTY + 7), 0);
        mbar_wait(BAR(B_ZOK), 0);
        const unsigned ep1 = lds32(sb + SM_MISC + 4 * M_EPOCH) + 1;
        fence_async();
        TS(2);
        int st = 0, ph = 1;
#pragma unroll 1
        for (int n = 0; n < 43; n++) {
          const uint32_t stg = sb + SM_RING + st * RSTAGE, bar = BAR(B_RFULL + st);
          if (n >= 3) mbar_wait(BAR(B_REMPTY + st), ph);
          if (n < 32) {
            mbar_expect(bar, 16384 + 11264);
            tma2d_mc(stg + rank * 8192, &tm_wsp, n * 64, bi * 128 + rank * 64, bar);
            if ((n & 3) == (bj >> 1) && n < 24) tma2d_pf(&tm_wsp, (n + 8) * 64, bi * 128 + rank * 64);
            if (n == 16) {
              l2_prefetch(reinterpret_cast<const uint8_t*>(prm.w_out) + blockIdx.x * 5504, 5504);
              l2_prefetch(reinterpret_cast<const uint8_t*>(prm.wo) + blockIdx.x * 4096, 4096);
            }
            bulk(stg + 16384, reinterpret_cast<const uint8_t*>(g_z2n) + (bj * 32 + n) * 11264, 11264, bar);
          } else {
            const int c = n - 32;
            mbar_expect(bar, 16384 + 8192);
            tma2d(stg + 16384, &tm_wout, 64 * bj, c * 64, bar);
            if (c == 0) { wait_ge(&g_ucnt[bi * 32], ep1 * 8); fence_async(); TS(3); }
            bulk_mc(stg + rank * 8192, reinterpret_cast<const uint8_t*>(g_u) + (bi * 11 + c) * 16384 + rank * 8192, 8192, bar);
          }
          if (++st == 3) { st = 0; ph ^= 1; }
        }
#pragma unroll 1
        for (int n = 0; n < 3; n++) {
          mbar_wait(BAR(B_REMPTY + st), ph);
          if (++st == 3) { st = 0; ph ^= 1; }
        }
        mbar_expect(BAR(B_WOFULL), 65536);
#pragma unroll 1
        for (int c = 0; c < 8; c++) tma2d(sb + SM_RING + c * 8192, &tm_wo, 64 * bj, c * 64, BAR(B_WOFULL));
        TS(4);
        wait_ge(&g_ocnt[bi * 32], ep1 * 24);
        fence_async();
        TS(5);
#pragma unroll 1
        for (int c = 0; c < 8; c++) {
          mbar_expect(BAR(B_OFULL + c), 16384);
          bulk_mc(sb + SM_K + c * 16384 + rank * 8192, reinterpret_cast<const uint8_t*>(g_o) + (bi * 8 + c) * 16384 + rank * 8192, 8192, BAR(B_OFULL + c));
        }
      }
    } else {
      unsigned ep = 0;
      if (lane == 0) {
        ep = atomicAdd(&g_ticket, 1u) / NCTA;
        sts32(sb + SM_MISC + 4 * M_EPOCH, ep);
        mbar_arrive(BAR(B_EPOCH));
        TS(71);
        wait_ge(&g_kvcnt[0], (ep + 1) * NCTA);
        TS(6);
      }
      __syncwarp();
      unsigned long long mx;
      asm volatile("ld.relaxed.gpu.global.u64 %0, [%1];" : "=l"(mx) : "l"(&g_kvmax[lane & 15]) : "memory");
      const float vm = __uint_as_float((uint32_t)mx);
      asm volatile("ld.relaxed.gpu.global.u64 %0, [%1];" : "=l"(mx) : "l"(&g_kvmax[16]) : "memory");
      const float kn2 = __uint_as_float((uint32_t)mx);
      const bool vok = __all_sync(0xffffffffu, vm >= 9.5367431640625e-07f && vm <= 1073741824.f);
      if (lane == 0) {
        sts32(sb + SM_MISC + 4 * M_KN2, __float_as_uint(kn2));
        sts32(sb + SM_MISC + 4 * M_VOK, vok ? 1u : 0u);
        mbar_arrive(BAR(B_KSTAT));
        TS(70);
        fence_async();
#pragma unroll 1
        for (int c = 0; c < 8; c++) {
          const uint32_t bytes = c == 7 ? 16640 : 16384, hb = bytes / 2, off = c * 16384 + rank * hb;
          mbar_wait(BAR(B_XEMPTY + c), 0);
          mbar_expect(BAR(B_KVFULL + c), bytes);
          bulk_mc(sb + SM_K + off, reinterpret_cast<const uint8_t*>(g_kimg) + off, hb, BAR(B_KVFULL + c));
        }
        TS(7);
        mbar_wait(BAR(B_DEC), 0);
        if (!lds32(sb + SM_MISC + 4 * M_FAST)) {
          for (int c = 0; c < 4; c++) mbar_wait(BAR(B_KVFULL + c), 0);
          mbar_expect(BAR(B_KFB), 65536);
          for (int c = 0; c < 4; c++) bulk(sb + SM_K + c * 16384, reinterpret_cast<const uint8_t*>(g_kbf) + c * 16384, 16384, BAR(B_KFB));
        }
      }
    }
  } else if (wg == 3) {
    asm volatile("setmaxnreg.inc.sync.aligned.u32 120;");
    const int w = tid >> 5, g = lane >> 2, t4 = lane & 3;
    {
      float a0 = 0.f, a1 = 0.f, a2 = 0.f, a3 = 0.f;
      uint4* sW = reinterpret_cast<uint4*>(smem_raw + SM_RING + 4 * WSLOT);
      if (tid < 64) sW[tid] = __ldg(reinterpret_cast<const uint4*>(prm.gate_w) + tid);
      bar_sync(4, 128);
#pragma unroll 1
      for (int c = 0; c < 8; c++) {
        mbar_wait(BAR(B_XFULL + c), 0);
        if (tid == 0) TS(40 + c);
        const uint4* xr = reinterpret_cast<const uint4*>(smem_raw + SM_K + c * 16384 + tid * 128);
#pragma unroll
        for (int v = 0; v < 8; v++) {
          const uint4 xv = xr[v ^ (tid & 7)], gv = sW[c * 8 + v];
          a0 = fmaf(bf_lo(xv.x), bf_lo(gv.x), a0); a1 = fmaf(bf_hi(xv.x), bf_hi(gv.x), a1);
          a2 = fmaf(bf_lo(xv.y), bf_lo(gv.y), a2); a3 = fmaf(bf_hi(xv.y), bf_hi(gv.y), a3);
          a0 = fmaf(bf_lo(xv.z), bf_lo(gv.z), a0); a1 = fmaf(bf_hi(xv.z), bf_hi(gv.z), a1);
          a2 = fmaf(bf_lo(xv.w), bf_lo(gv.w), a2); a3 = fmaf(bf_hi(xv.w), bf_hi(gv.w), a3);
        }
      }
      const float gt = __fdividef(1.f, 1.f + __expf(-((a0 + a1) + (a2 + a3))));
      sts32(sb + SM_G + tid * 4, __float_as_uint(gt));
      if (aj == 0) g_gate[ai * 128 + tid] = gt;
      fence_async_smem();
      bar_sync(4, 128);
    }
    if (tid == 0) TS(8);
    phase1_q_z1(sb, 1, ai, aj, tid TSARG);
    float acc[88];
    int st = 0, ph = 0;
    {
#pragma unroll
      for (int k = 0; k < 88; k++) acc[k] = 0.f;
      regfence(acc);
#pragma unroll 1
      for (int n = 0; n < 32; n++) {
        mbar_wait(BAR(B_RFULL + st), ph);
        const uint64_t da = mkdesc(sb + SM_RING + st * RSTAGE, 16, 1024, 1);
        const uint64_t db = mkdesc(sb + SM_RING + st * RSTAGE + 16384, 1408, 128, 0);
#pragma unroll
        for (int k = 0; k < 4; k++) {
          wg_fence();
          wg_ss_n88<0, 88>(acc, da + 2 * k, db + 176 * k);
          wg_ss_n88<44, 88>(acc, da + 512 + 2 * k, db + 176 * k);
          wg_commit();
          wg_wait<0>();
        }
        if (tid == 0) mbar_arrive_both(BAR(B_REMPTY + st));
        if (++st == 3) { st = 0; ph ^= 1; }
      }
      regfence(acc);
      if (tid == 0) TS(11);
      mbar_wait(BAR(B_Z1OK), 0);
      float bs[4], og[4];
#pragma unroll
      for (int r = 0; r < 4; r++) {
        const int row = bi * 128 + (r >> 1) * 64 + w * 16 + (r & 1) * 8 + g;
        bs[r] = __bfloat162float(prm.b_sp[row]);
        og[r] = 1.f - __ldcg(&g_gate[row]);
      }
      const uint32_t* z1p = reinterpret_cast<const uint32_t*>(g_z1) + ((bi * 88 + bj * 11) * 16 + w * 2) * 32 + lane;
      uint32_t* up = reinterpret_cast<uint32_t*>(g_u) + bi * 11 * 4096 + w * 512 + lane;
#pragma unroll
      for (int r = 0; r < 4; r++) {
        uint32_t zz[11];
#pragma unroll
        for (int c8 = 0; c8 < 11; c8++) zz[c8] = __ldcg(z1p + c8 * 512 + ((r >> 1) * 8 + (r & 1)) * 32);
#pragma unroll
        for (int c8 = 0; c8 < 11; c8++) {
          const int k = (r >> 1) * 44 + c8 * 4 + (r & 1) * 2, cb = 11 * bj + c8;
          uint32_t v = pack_bf16(bf_lo(zz[c8]) * (acc[k] + bs[r]) * og[r], bf_hi(zz[c8]) * (acc[k + 1] + bs[r]) * og[r]);
          if (c8 >= 9 && bj == 7) v = 0;
          up[(cb >> 3) * 4096 + ((r >> 1) * 8 + (r & 1)) * 256 + (cb & 7) * 32] = v;
        }
      }
      fence_async();
      bar_sync(4, 128);
      if (tid == 0) red_release(&g_ucnt[bi * 32]);
    }
    if (tid == 0) TS(12);
    {
      float oc[64];
#pragma unroll
      for (int k = 0; k < 64; k++) oc[k] = 0.f;
      regfence(oc);
#pragma unroll 1
      for (int n = 0; n < 11; n++) {
        mbar_wait(BAR(B_RFULL + st), ph);
        const uint64_t da = mkdesc(sb + SM_RING + st * RSTAGE, 128, 1024, 0);
        const uint64_t db = mkdesc(sb + SM_RING + st * RSTAGE + 16384, 8192, 1024, 1);
#pragma unroll
        for (int k = 0; k < 4; k++) {
          wg_fence();
          wg_ss_n64<0, 64>(oc, da + 16 * k, db + 128 * k);
          wg_ss_n64<32, 64>(oc, da + 512 + 16 * k, db + 128 * k);
          wg_commit();
          wg_wait<0>();
        }
        if (tid == 0) mbar_arrive_both(BAR(B_REMPTY + st));
        if (++st == 3) { st = 0; ph ^= 1; }
      }
      if (tid == 0) TS(13);
      mbar_wait(BAR(B_WOFULL), 0);
#pragma unroll 1
      for (int c = 0; c < 8; c++) {
        mbar_wait(BAR(B_OFULL + c), 0);
        const uint64_t da = mkdesc(sb + SM_K + c * 16384, 128, 1024, 0);
        const uint64_t db = mkdesc(sb + SM_RING + c * 8192, 8192, 1024, 1);
        wg_fence();
#pragma unroll
        for (int k = 0; k < 4; k++) { wg_ss_n64<0, 64>(oc, da + 16 * k, db + 128 * k); wg_ss_n64<32, 64>(oc, da + 512 + 16 * k, db + 128 * k); }
        wg_commit();
      }
      wg_wait<0>();
      regfence(oc);
      if (tid == 0) TS(14);
      uint32_t* op = reinterpret_cast<uint32_t*>(prm.out) + (bi * 128 + w * 16 + g) * 256 + bj * 32 + t4;
#pragma unroll
      for (int k = 0; k < 64; k += 2) {
        const int hf = k / 32, c8 = (k % 32) / 4, r8 = (k >> 1) & 1;
        op[(hf * 64 + r8 * 8) * 256 + c8 * 4] = pack_bf16(oc[k], oc[k + 1]);
      }
      if (tid == 0) TS(15);
    }
  } else {
    asm volatile("setmaxnreg.inc.sync.aligned.u32 112;");
    const int w = tid >> 5, g = lane >> 2, t4 = lane & 3;
    if (wg < 2) {
      float acc[48];
#pragma unroll
      for (int k = 0; k < 48; k++) acc[k] = 0.f;
      regfence(acc);
#pragma unroll 1
      for (int c = 0; c < 8; c++) {
        mbar_wait(BAR(B_XFULL + c), 0);
        mbar_wait(BAR(B_WFULL + c), 0);
        if (threadIdx.x == 0) TS(48 + c);
        const uint64_t da = mkdesc(sb + SM_K + c * 16384 + wg * 8192, 16, 1024, 1);
        const uint64_t db = mkdesc(sb + SM_RING + (c & 3) * WSLOT, 4096, 512, 2);
        wg_fence();
#pragma unroll
        for (int k = 0; k < 4; k++) wg_ss_n96<0, 48>(acc, da + 2 * k, db + 64 * k);
        wg_commit();
        wg_wait<0>();
        if (tid == 0) mbar_arrive_both(BAR(B_WEMPTY + c));
      }
      regfence(acc);
      if (tid == 0) TS(16 + wg);
      const bool lo_ok = aj != 0, hi_ok = aj < 6;
      float s0 = 0.f, s1 = 0.f;
#pragma unroll
      for (int k = 0; k < 48; k++) {
        float z = gelu_tanh(acc[k]);
        if (k < 8 && !lo_ok) z = 0.f;
        if (k >= 32 && !hi_ok) z = 0.f;
        acc[k] = z;
        if (k & 2) s1 += z; else s0 += z;
      }
      s0 += __shfl_xor_sync(0xffffffffu, s0, 1); s0 += __shfl_xor_sync(0xffffffffu, s0, 2);
      s1 += __shfl_xor_sync(0xffffffffu, s1, 1); s1 += __shfl_xor_sync(0xffffffffu, s1, 2);
      const float inv_n = !lo_ok ? (1.f / 80.f) : (hi_ok ? (1.f / 96.f) : (1.f / 64.f));
      const float m0 = s0 * inv_n, m1 = s1 * inv_n;
      float v0 = 0.f, v1 = 0.f;
#pragma unroll
      for (int k = 0; k < 48; k++) {
        float d = acc[k] - ((k & 2) ? m1 : m0);
        if (k < 8 && !lo_ok) d = 0.f;
        if (k >= 32 && !hi_ok) d = 0.f;
        if (k & 2) v1 = fmaf(d, d, v1); else v0 = fmaf(d, d, v0);
      }
      v0 += __shfl_xor_sync(0xffffffffu, v0, 1); v0 += __shfl_xor_sync(0xffffffffu, v0, 2);
      v1 += __shfl_xor_sync(0xffffffffu, v1, 1); v1 += __shfl_xor_sync(0xffffffffu, v1, 2);
      const int r0 = wg * 64 + w * 16 + g;
      mbar_wait(BAR(B_EPOCH), 0);
      const unsigned ep1 = lds32(sb + SM_MISC + 4 * M_EPOCH) + 1;
      if (threadIdx.x == 0) TS(67);
      if (t4 < 2) {
        const float m = t4 ? m1 : m0, v = t4 ? v1 : v0;
        asm volatile("st.relaxed.gpu.global.v2.b64 [%0], {%1, %2};" ::"l"(&g_lnstat[(ai * 8 + aj) * 128 + r0 + 8 * t4]),
                     "l"(((unsigned long long)ep1 << 32) | __float_as_uint(m)), "l"(((unsigned long long)ep1 << 32) | __float_as_uint(v)) : "memory");
      }
      float sm[4], sv[4];
      {
        const uint4* lp = &g_lnstat[(ai * 8 + 2 * t4) * 128 + r0];
#pragma unroll 1
        for (int n = 0; n < SPIN_LIMIT; n++) {
          bool ok = true;
#pragma unroll
          for (int e = 0; e < 4; e++) {
            unsigned long long a, b;
            asm volatile("ld.relaxed.gpu.global.v2.b64 {%0, %1}, [%2];" : "=l"(a), "=l"(b) : "l"(lp + (e >> 1) * 128 + (e & 1) * 8) : "memory");
            ok = ok && (uint32_t)(a >> 32) == ep1 && (uint32_t)(b >> 32) == ep1;
            sm[e] = __uint_as_float((uint32_t)a); sv[e] = __uint_as_float((uint32_t)b);
          }
          if (__all_sync(0xffffffffu, ok)) break;
        }
      }
      if (threadIdx.x == 0) TS(68);
      float mean[2], rstd[2];
      const float na = t4 == 0 ? 80.f : (t4 == 3 ? 64.f : 96.f), nb = t4 == 3 ? 64.f : 96.f;
#pragma unroll
      for (int r = 0; r < 2; r++) {
        float t = fmaf(sm[r], na, sm[2 + r] * nb);
        t += __shfl_xor_sync(0xffffffffu, t, 1); t += __shfl_xor_sync(0xffffffffu, t, 2);
        const float mu = t * (1.f / 688.f);
        const float da = sm[r] - mu, db = sm[2 + r] - mu;
        float m2 = sv[r] + sv[2 + r] + na * da * da + nb * db * db;
        m2 += __shfl_xor_sync(0xffffffffu, m2, 1); m2 += __shfl_xor_sync(0xffffffffu, m2, 2);
        mean[r] = mu;
        rstd[r] = rsqrtf(fmaf(m2, 1.f / 688.f, 1e-5f));
      }
      const int fb0 = aj < 6 ? 12 * aj - 2 : 22 + 8 * aj, c_lo = lo_ok ? 0 : 2, c_hi = hi_ok ? 12 : (aj == 7 ? 10 : 8);
      uint32_t* zp = reinterpret_cast<uint32_t*>(g_z2n) + (ai * 2 + wg) * 2816 + w * 704;
      auto zoff = [&](int c8) { const int fb = fb0 + c8, sl = (fb * 373) >> 12; return sl * (32 * 2816) + (fb - sl * 11) * 32; };
#pragma unroll
      for (int k = 0; k < 48; k += 2) {
        const int r = (k >> 1) & 1, c8 = k >> 2;
        uint32_t v = pack_bf16((acc[k] - mean[r]) * rstd[r], (acc[k + 1] - mean[r]) * rstd[r]);
        if (c8 >= 8 && !hi_ok) v = 0;
        if (c8 >= c_lo && c8 < c_hi) zp[zoff(c8) + r * 352 + lane] = v;
      }
      if (threadIdx.x == 0) TS(69);
      uint32_t chk = 0;
#pragma unroll
      for (int r = 0; r < 3; r++) {
        const int it = lane + 32 * r, c8 = it >> 3;
        if (c8 >= c_lo && c8 < c_hi) chk ^= ld_back(zp + zoff(c8) + ((it >> 2) & 1) * 352 + (it & 3) * 8);
      }
      consume(chk, sb);
      fence_async();
      bar_sync(1 + wg, 128);
      if (tid == 0) { red_relaxed(&g_zcnt[ai * 2 + wg]); TS(20 + wg); }
      bar_sync(5, 512);
    } else {
      const int slot = ai * 4 + (aj >> 1), isv = aj & 1;
      {
        const uint4* wsrc = reinterpret_cast<const uint4*>(isv ? prm.wv : prm.wk) + tid;
        uint4 wr[8];
#pragma unroll
        for (int r = 0; r < 8; r++) wr[r] = __ldg(wsrc + 128 * r);
#pragma unroll
        for (int r = 0; r < 8; r++) sts128(sb + SM_Q + r * 2048 + (tid >> 1) * 32 + (((tid ^ (tid >> 3)) & 1) << 4), wr[r].x, wr[r].y, wr[r].z, wr[r].w);
        fence_async_smem();
        bar_sync(3, 128);
        float kv[16];
#pragma unroll
        for (int k = 0; k < 16; k++) kv[k] = 0.f;
        regfence(kv);
#pragma unroll 1
        for (int c = 0; c < 8; c++) {
          mbar_wait(BAR(B_XFULL + c), 0);
          const uint64_t da = mkdesc(sb + SM_Q + c * 2048, 0, 256, 3);
          const uint64_t db = mkdesc(sb + SM_K + c * 16384 + (aj >> 1) * 4096, 16, 1024, 1);
          wg_fence();
#pragma unroll
          for (int k = 0; k < 4; k++) wg_ss_n32t<0, 16>(kv, da + 32 * k, db + 2 * k);
          wg_commit();
        }
        wg_wait<0>();
        regfence(kv);
        if (tid == 0) TS(22);
        const uint32_t sT = sb + SM_Q, sH = sb + SM_Q + 4096;
        bar_sync(3, 128);
#pragma unroll
        for (int k = 0; k < 16; k++) {
          const int tok = (k >> 2) * 8 + 2 * t4 + (k & 1), d = g + ((k >> 1) & 1) * 8;
          if ((k >> 2) == w) sts32(sT + (tok * 17 + d) * 4, __float_as_uint(__bfloat162float(__float2bfloat16_rn(kv[k]))));
        }
        mbar_wait(BAR(B_EPOCH), 0);
        const unsigned long long tag = (unsigned long long)(lds32(sb + SM_MISC + 4 * M_EPOCH) + 1) << 32;
        bar_sync(3, 128);
        if (tid == 0) TS(64);
        const int tok = (tid & 63) >> 1, hf = tid & 1;
        const uint32_t inner = (slot & 7) * 16;
        uint32_t chk = 0;
        float f[8];
#pragma unroll
        for (int e = 0; e < 8; e++) f[e] = ldsf(sT + (tok * 17 + hf * 8 + e) * 4);
        const uint4 fb = make_uint4(pack_bf16(f[0], f[1]), pack_bf16(f[2], f[3]), pack_bf16(f[4], f[5]), pack_bf16(f[6], f[7]));
        if (!isv) {
          const uint32_t off = tok * 2048 + (slot >> 3) * 256 + hf * 128 + inner;
          if (tid < 48) {
            const int d = tid & 15, sg = tid >> 4, j0 = sg == 0 ? 0 : (sg == 1 ? 10 : 22), j1 = sg == 0 ? 10 : (sg == 1 ? 22 : 32);
            float kx[12], run = 0.f;
#pragma unroll
            for (int e = 0; e < 12; e++) kx[e] = ldsf(sT + (min(j0 + e, 31) * 17 + d) * 4);
#pragma unroll
            for (int e = 0; e < 12; e++) {
              __half hv;
              if (slot < NP) { hv = __float2half_rn(fmaf(kx[e], 16.f, -run)); run += __half2float(hv); }
              else hv = __float2half_rn(kx[e] * 0.125f);
              if (j0 + e < j1) sts16(sH + ((j0 + e) * 16 + d) * 2, __half_as_ushort(hv));
            }
          } else if (tid >= 64) {
            g_kbf[off >> 4] = fb;
            float n2 = 0.f;
#pragma unroll
            for (int e = 0; e < 8; e++) n2 = fmaf(f[e], f[e], n2);
            n2 += __shfl_xor_sync(0xffffffffu, n2, 1);
            if (!(n2 <= 3.0e38f)) n2 = 3.0e38f;
            const uint32_t mx = __reduce_max_sync(0xffffffffu, __float_as_uint(n2));
            if (lane == 0) chk = (uint32_t)atomicMax(&g_kvmax[16], tag | mx);
            chk ^= ld_back(&g_kbf[off >> 4]);
          }
          bar_sync(3, 128);
          if (tid < 64) { g_kimg[off >> 4] = lds128(sH + tok * 32 + hf * 16); chk = ld_back(&g_kimg[off >> 4]); }
        } else {
          if (tid < 64) {
            const uint32_t sbo = 256 * (4 * tok + (slot >> 4) + 1);
            const uint32_t off = (hf ? SM_ONES + sbo : SM_ONES - sbo) + ((slot >> 3) & 1) * 128 + inner;
            g_kimg[off >> 4] = fb;
            chk = ld_back(&g_kimg[off >> 4]);
          } else if (tid < 80) {
            float vm = 0.f;
#pragma unroll
            for (int jj = 0; jj < 32; jj++) { float a = fabsf(ldsf(sT + (jj * 17 + tid - 64) * 4)); if (!(a <= 3.0e38f)) a = 3.0e38f; vm = fmaxf(vm, a); }
            chk = (uint32_t)atomicMax(&g_kvmax[tid - 64], tag | __float_as_uint(vm));
          } else if (tid >= 96 && tid < 112 && slot == 0) {
            g_kimg[(SM_ONES >> 4) + tid - 96] = make_uint4(0x3F803F80u, 0x3F803F80u, 0x3F803F80u, 0x3F803F80u);
            chk = ld_back(&g_kimg[(SM_ONES >> 4) + tid - 96]);
          }
        }
        if (tid == 0) TS(65);
        consume(chk, sb);
        fence_async();
        bar_sync(3, 128);
        if (tid == 0) { red_relaxed(&g_kvcnt[0]); TS(23); }
      }
      phase1_q_z1(sb, 0, ai, aj, tid TSARG);
      bar_sync(9, 256);
    }
    if (tid == 0) TS(25 + wg);
#pragma unroll 1
    for (int c = 0; c < 8; c++) mbar_wait(BAR(B_KVFULL + c), 0);
    if (tid == 0) TS(28 + wg);
    const uint64_t dk0 = mkdesc(sb + SM_K, 128, 256, 0);
    const uint64_t dv0 = mkdesc(sb + SM_ONES - 256, 128, 256, 0);
    const uint64_t vstep = prm.vstep;
    const int aw = wg == 0 ? 0 : 3 - wg;
    uint32_t chk = 0;
    float o[12], s[32];
    uint32_t q[4], p0[16], p1[16];
    if (lds32(sb + SM_MISC + 4 * M_FAST)) {
      const uint32_t mlo = prm.mlo, mhi = prm.mhi;
      uint64_t dk = dk0, dv = dv0;
#define STEP(PIN, POUT) { wg_fence(); issue_qk(s, q, dk); dk += 128; wg_commit(); issue_pv(o, PIN, dv, vstep); wg_commit(); \
                          wg_wait<1>(); regfence(s); softmax_step(s, POUT, mlo, mhi); wg_wait<0>(); }
#pragma unroll 1
      for (int sg = aw * 8; sg < aw * 8 + 8; sg++) {
        const int tau = sg / 3, seg = sg - tau * 3;
        int n2 = seg == 1 ? 6 : 5;
#pragma unroll
        for (int k = 0; k < NP / 2; k++) s[k] = MAGIC_C;
        if (sg == aw * 8 || seg == 0) {
          const int j0 = seg == 0 ? 0 : (seg == 1 ? 10 : 22);
          dk = dk0 + 128 * j0;
          dv = dv0 + VSTEP * (4 * j0);
          const uint4 qv = lds128(sb + SM_Q + tau * 2048 + tid * 16);
          q[0] = qv.x; q[1] = qv.y; q[2] = qv.z; q[3] = qv.w;
#pragma unroll
          for (int k = 0; k < 12; k++) o[k] = 0.f;
          regfence(o); regfence(s);
          wg_fence(); issue_qk(s, q, dk); dk += 128; wg_commit();
          wg_wait<0>(); regfence(s);
          softmax_step(s, p0, mlo, mhi);
          STEP(p0, p1);
          n2--;
        }
        regfence(s);
#pragma unroll 1
        for (; n2 > 0; n2--) { STEP(p1, p0); STEP(p0, p1); }
        if (sg == aw * 8 + 7 || seg == 2) {
          wg_fence(); issue_pv(o, p1, dv, vstep); wg_commit();
          wg_wait<0>(); regfence(o);
          if (sg == 8 || sg == 17) {
            float4* pp = g_part + (blockIdx.x * 2 + (aw - 1)) * 384 + tid;
            pp[0] = make_float4(o[0], o[1], o[2], o[3]); pp[128] = make_float4(o[4], o[5], o[6], o[7]); pp[256] = make_float4(o[8], o[9], o[10], o[11]);
            __threadfence_block();
            bar_arrive(5 + aw, 256);
          } else {
            if (sg == 7 || sg == 15) {
              bar_sync(6 + aw, 256);
              const float4* pp = g_part + (blockIdx.x * 2 + aw) * 384 + tid;
              const float4 a = pp[0], b = pp[128], c = pp[256];
              o[0] += a.x; o[1] += a.y; o[2] += a.z; o[3] += a.w; o[4] += b.x; o[6] += b.z; o[8] += c.x; o[9] += c.y; o[10] += c.z; o[11] += c.w;
            }
            chk ^= store_o_tile(o, ai, aj, tau, tid, sb);
          }
        }
      }
#undef STEP
    } else {
      mbar_wait(BAR(B_KFB), 0);
      constexpr float SC = 0.25f * 1.4426950408889634f;
#pragma unroll 1
      for (int tau = wg * 3; tau < wg * 3 + 3 && tau < 8; tau++) {
        const uint4 qv = lds128(sb + SM_Q + tau * 2048 + tid * 16);
        float m0 = -INFINITY, m1 = -INFINITY;
#pragma unroll
        for (int k = 0; k < 12; k++) o[k] = 0.f;
        uint64_t dv = dv0;
#pragma unroll 1
        for (int j = 0; j < 32; j++) {
          regfence(s);
          wg_fence(); wg_qkb_n64<0, 0, 32>(s, qv.x, qv.y, qv.z, qv.w, dk0 + 128 * j); wg_commit();
          wg_wait<0>(); regfence(s);
          float x0 = m0, x1 = m1;
#pragma unroll
          for (int k = 0; k < 32; k++) { s[k] *= SC; if (k & 2) x1 = fmaxf(x1, s[k]); else x0 = fmaxf(x0, s[k]); }
          x0 = fmaxf(x0, __shfl_xor_sync(0xffffffffu, x0, 1)); x0 = fmaxf(x0, __shfl_xor_sync(0xffffffffu, x0, 2));
          x1 = fmaxf(x1, __shfl_xor_sync(0xffffffffu, x1, 1)); x1 = fmaxf(x1, __shfl_xor_sync(0xffffffffu, x1, 2));
          const float c0 = ex2(m0 - x0), c1 = ex2(m1 - x1);
          m0 = x0; m1 = x1;
#pragma unroll
          for (int k = 0; k < 12; k++) o[k] *= (k & 2) ? c1 : c0;
#pragma unroll
          for (int k = 0; k < 16; k++) { const float m = (k & 1) ? m1 : m0; p0[k] = exp_mufu(s[2 * k] - m, s[2 * k + 1] - m); }
          regfence(o);
          wg_fence(); issue_pv(o, p0, dv, vstep); wg_commit();
          wg_wait<0>(); regfence(o);
        }
        chk ^= store_o_tile(o, ai, aj, tau, tid, sb);
      }
    }
    consume(chk, sb);
    fence_async();
    bar_sync(1 + wg, 128);
    if (tid == 0) { red_relaxed(&g_ocnt[ai * 32]); TS(31 + wg); }
  }
  __syncwarp();
  asm volatile("barrier.cluster.arrive.relaxed;" ::: "memory");
  asm volatile("barrier.cluster.wait;" ::: "memory");
}

typedef CUresult (*EncodeFn)(CUtensorMap*, CUtensorMapDataType, cuuint32_t, void*, const cuuint64_t*, const cuuint64_t*,
                             const cuuint32_t*, const cuuint32_t*, CUtensorMapInterleave, CUtensorMapSwizzle,
                             CUtensorMapL2promotion, CUtensorMapFloatOOBfill);

void make_map(EncodeFn enc, CUtensorMap* tm, const void* base, uint64_t cols, uint64_t rows, uint32_t bc, uint32_t br, CUtensorMapSwizzle sw) {
  cuuint64_t gd[2] = {cols, rows};
  cuuint64_t gs[1] = {cols * 2};
  cuuint32_t bd[2] = {bc, br};
  cuuint32_t es[2] = {1, 1};
  enc(tm, CU_TENSOR_MAP_DATA_TYPE_BFLOAT16, 2, const_cast<void*>(base), gd, gs, bd, es, CU_TENSOR_MAP_INTERLEAVE_NONE, sw,
      CU_TENSOR_MAP_L2_PROMOTION_L2_128B, CU_TENSOR_MAP_FLOAT_OOB_FILL_NONE);
}

}

extern "C" void kernel_launch(void* const* d_in, const int* in_sizes, int n_in, void* d_out, int out_size) {
  (void)in_sizes; (void)n_in; (void)out_size;
  static EncodeFn enc = nullptr;
  if (!enc) {
    void* fn = nullptr;
    cudaDriverEntryPointQueryResult qr;
    cudaGetDriverEntryPoint("cuTensorMapEncodeTiled", &fn, cudaEnableDefault, &qr);
    enc = (EncodeFn)fn;
    cudaFuncSetAttribute(fused_kernel, cudaFuncAttributeMaxDynamicSharedMemorySize, SMEM_BYTES);
  }
  CUtensorMap tx, tq, tin, tsp, tout, to;
  make_map(enc, &tx, d_in[0], 512, 2048, 64, 128, CU_TENSOR_MAP_SWIZZLE_128B);
  make_map(enc, &tq, d_in[1], 512, 512, 64, 32, CU_TENSOR_MAP_SWIZZLE_128B);
  make_map(enc, &to, d_in[4], 512, 512, 64, 64, CU_TENSOR_MAP_SWIZZLE_128B);
  make_map(enc, &tin, d_in[6], 1376, 512, 32, 32, CU_TENSOR_MAP_SWIZZLE_64B);
  make_map(enc, &tsp, d_in[7], 2048, 2048, 64, 64, CU_TENSOR_MAP_SWIZZLE_128B);
  make_map(enc, &tout, d_in[9], 512, 688, 64, 64, CU_TENSOR_MAP_SWIZZLE_128B);
  Params prm;
  prm.gate_w = (const __nv_bfloat16*)d_in[10];
  prm.b_sp = (const __nv_bfloat16*)d_in[8];
  prm.w_sp = (const __nv_bfloat16*)d_in[7];
  prm.w_out = (const __nv_bfloat16*)d_in[9];
  prm.wo = (const __nv_bfloat16*)d_in[4];
  prm.w_in = (const __nv_bfloat16*)d_in[6];
  prm.wq = (const __nv_bfloat16*)d_in[1];
  prm.wk = (const __nv_bfloat16*)d_in[2];
  prm.wv = (const __nv_bfloat16*)d_in[3];
  prm.vstep = VSTEP;
  prm.mlo = 0x007F007Fu;
  prm.mhi = 0xFF80FF80u;
  prm.out = (__nv_bfloat16*)d_out;
  fused_kernel<<<NCTA, NTHREADS, SMEM_BYTES>>>(tx, tq, tin, tsp, tout, to, prm);
}
```

```cpp
#include <cuda_runtime.h>
#include <cuda.h>
#include <cuda_bf16.h>
#include <cuda_fp16.h>
#include <stdint.h>

namespace {

constexpr int NCTA = 128;
constexpr int NTHREADS = 640;
constexpr int NP = 40;
constexpr int NM = 64 - NP;
constexpr int SPIN_LIMIT = 1 << 18;

constexpr uint32_t SM_K = 0;
constexpr uint32_t SM_ONES = 98304;
constexpr uint32_t KV_BYTES = 131328;
constexpr uint32_t SM_BAR = 131328;
constexpr uint32_t SM_RING = 132096;
constexpr uint32_t RSTAGE = 27648;
constexpr uint32_t WSLOT = 16384;
constexpr uint32_t SM_WKV = SM_RING + 4 * WSLOT;
constexpr uint32_t SM_GW = SM_WKV + 16384;
constexpr uint32_t SM_Q = 215040;
constexpr uint32_t SM_G = 231424;
constexpr uint32_t SM_MISC = 231936;
constexpr uint32_t SMEM_BYTES = 232448;

constexpr int B_XFULL = 0, B_XEMPTY = 8, B_WFULL = 16, B_WEMPTY = 32, B_KVFULL = 44, B_OFULL = 52, B_RFULL = 60,
              B_REMPTY = 63, B_KFB = 66, B_KSTAT = 67, B_DEC = 68, B_WOFULL = 69, B_EPOCH = 70, B_ZOK = 71, B_Z1OK = 72, B_ATT = 73, B_QRDY = 74;
constexpr int M_EPOCH = 0, M_KN2 = 1, M_VOK = 2, M_FAST = 3, M_KVR = 4, M_RED = 16;

__device__ uint4 g_kimg[KV_BYTES / 16];
__device__ uint4 g_kbf[65536 / 16];
__device__ unsigned long long g_kvflag[NCTA];
__device__ uint4 g_lnstat[16 * 8 * 128];
__device__ float g_gate[2048];
__device__ uint4 g_z2n[8 * 32 * 11264 / 16];
__device__ uint4 g_z1[16 * 88 * 128];
__device__ uint4 g_u[16 * 11 * 1024];
__device__ uint4 g_o[16 * 8 * 1024];
__device__ float4 g_part[NCTA * 2 * 3 * 128];
__device__ unsigned g_ticket;
__device__ unsigned g_zcnt[32 * 32];
__device__ unsigned g_z1cnt[16 * 32];
__device__ unsigned g_ucnt[16 * 32];
__device__ unsigned g_ocnt[16 * 32];
#define TS(k) do { } while (0)

__device__ __forceinline__ void mbar_init(uint32_t a, uint32_t c) { asm volatile("mbarrier.init.shared::cta.b64 [%0], %1;" ::"r"(a), "r"(c) : "memory"); }
__device__ __forceinline__ void mbar_expect(uint32_t a, uint32_t b) { asm volatile("mbarrier.arrive.expect_tx.shared::cta.b64 _, [%0], %1;" ::"r"(a), "r"(b) : "memory"); }
__device__ __forceinline__ void mbar_arrive(uint32_t a) { asm volatile("mbarrier.arrive.shared::cta.b64 _, [%0];" ::"r"(a) : "memory"); }
__device__ __forceinline__ void mbar_arrive_both(uint32_t a) {
  asm volatile("{\n.reg .b32 ra;\nmapa.shared::cluster.u32 ra, %0, 0;\nmbarrier.arrive.shared::cluster.b64 _, [ra];\n"
               "mapa.shared::cluster.u32 ra, %0, 1;\nmbarrier.arrive.shared::cluster.b64 _, [ra];\n}" ::"r"(a) : "memory");
}
__device__ __forceinline__ void mbar_wait(uint32_t a, uint32_t ph) {
  uint32_t ok;
#pragma unroll 1
  for (int n = 0; n < SPIN_LIMIT; n++) {
    asm volatile("{\n.reg .pred p;\nmbarrier.try_wait.parity.shared::cta.b64 p, [%1], %2;\nselp.u32 %0, 1, 0, p;\n}" : "=r"(ok) : "r"(a), "r"(ph) : "memory");
    if (ok) break;
  }
}
__device__ __forceinline__ void tma2d(uint32_t dst, const CUtensorMap* tm, int c0, int c1, uint32_t bar) {
  asm volatile("cp.async.bulk.tensor.2d.shared::cluster.global.mbarrier::complete_tx::bytes [%0], [%1, {%3, %4}], [%2];"
               ::"r"(dst), "l"(tm), "r"(bar), "r"(c0), "r"(c1) : "memory");
}
__device__ __forceinline__ void tma2d_mc(uint32_t dst, const CUtensorMap* tm, int c0, int c1, uint32_t bar) {
  asm volatile("cp.async.bulk.tensor.2d.shared::cluster.global.mbarrier::complete_tx::bytes.multicast::cluster [%0], [%1, {%3, %4}], [%2], %5;"
               ::"r"(dst), "l"(tm), "r"(bar), "r"(c0), "r"(c1), "h"((uint16_t)3) : "memory");
}
__device__ __forceinline__ void tma2d_pf(const CUtensorMap* tm, int c0, int c1) {
  asm volatile("cp.async.bulk.prefetch.tensor.2d.L2.global [%0, {%1, %2}];" ::"l"(tm), "r"(c0), "r"(c1) : "memory");
}
__device__ __forceinline__ void bulk(uint32_t dst, const void* src, uint32_t bytes, uint32_t bar) {
  asm volatile("cp.async.bulk.shared::cluster.global.mbarrier::complete_tx::bytes [%0], [%1], %2, [%3];"
               ::"r"(dst), "l"(src), "r"(bytes), "r"(bar) : "memory");
}
__device__ __forceinline__ void bulk_mc(uint32_t dst, const void* src, uint32_t bytes, uint32_t bar) {
  asm volatile("cp.async.bulk.shared::cluster.global.mbarrier::complete_tx::bytes.multicast::cluster [%0], [%1], %2, [%3], %4;"
               ::"r"(dst), "l"(src), "r"(bytes), "r"(bar), "h"((uint16_t)3) : "memory");
}
__device__ __forceinline__ void l2_prefetch(const void* src, uint32_t bytes) { asm volatile("cp.async.bulk.prefetch.L2.global [%0], %1;" ::"l"(src), "r"(bytes) : "memory"); }
__device__ __forceinline__ void fence_async() { asm volatile("fence.proxy.async.global;" ::: "memory"); }
__device__ __forceinline__ void fence_async_smem() { asm volatile("fence.proxy.async.shared::cta;" ::: "memory"); }
__device__ __forceinline__ void bar_sync(int id, int n) { asm volatile("bar.sync %0, %1;" ::"r"(id), "r"(n) : "memory"); }
__device__ __forceinline__ void bar_arrive(int id, int n) { asm volatile("bar.arrive %0, %1;" ::"r"(id), "r"(n) : "memory"); }
__device__ __forceinline__ void red_release(unsigned* p) { asm volatile("red.release.gpu.global.add.u32 [%0], 1;" ::"l"(p) : "memory"); }
__device__ __forceinline__ void red_relaxed(unsigned* p) { asm volatile("red.relaxed.gpu.global.add.u32 [%0], 1;" ::"l"(p) : "memory"); }
__device__ __forceinline__ uint32_t ld_back(const void* p) { uint32_t v; asm volatile("ld.relaxed.gpu.global.u32 %0, [%1];" : "=r"(v) : "l"(p) : "memory"); return v; }
__device__ __forceinline__ void consume(uint32_t v, uint32_t sb) { if (v == 0xDEADBEEFu) asm volatile("st.shared.u32 [%0], %1;" ::"r"(sb + SM_MISC + 60), "r"(v) : "memory"); }
__device__ __forceinline__ unsigned ld_acquire(const unsigned* p) { unsigned v; asm volatile("ld.acquire.gpu.global.u32 %0, [%1];" : "=r"(v) : "l"(p) : "memory"); return v; }
__device__ __forceinline__ void wait_ge(const unsigned* p, unsigned target) {
#pragma unroll 1
  for (int n = 0; n < SPIN_LIMIT; n++) {
    if ((int)(ld_acquire(p) - target) >= 0) break;
    __nanosleep(100);
  }
}
__device__ __forceinline__ void wg_fence() { asm volatile("wgmma.fence.sync.aligned;" ::: "memory"); }
__device__ __forceinline__ void wg_commit() { asm volatile("wgmma.commit_group.sync.aligned;" ::: "memory"); }
template <int N> __device__ __forceinline__ void wg_wait() { asm volatile("wgmma.wait_group.sync.aligned %0;" ::"n"(N) : "memory"); }
template <int n> __device__ __forceinline__ void regfence(float (&d)[n]) {
#pragma unroll
  for (int i = 0; i < n; i++) asm volatile("" : "+f"(d[i])::"memory");
}
__device__ __forceinline__ uint64_t mkdesc(uint32_t addr, uint32_t lbo, uint32_t sbo, int swz) {
  return (uint64_t)((addr & 0x3FFFF) >> 4) | ((uint64_t)(lbo >> 4) << 16) | ((uint64_t)(sbo >> 4) << 32) | ((uint64_t)swz << 62);
}
__device__ __forceinline__ uint32_t pack_bf16(float lo, float hi) { uint32_t r; asm("cvt.rn.bf16x2.f32 %0, %1, %2;" : "=r"(r) : "f"(hi), "f"(lo)); return r; }
__device__ __forceinline__ uint32_t pack_f16(float lo, float hi) { uint32_t r; asm("cvt.rn.f16x2.f32 %0, %1, %2;" : "=r"(r) : "f"(hi), "f"(lo)); return r; }
__device__ __forceinline__ float bf_lo(uint32_t v) { return __uint_as_float(v << 16); }
__device__ __forceinline__ float bf_hi(uint32_t v) { return __uint_as_float(v & 0xFFFF0000u); }
__device__ __forceinline__ float ex2(float x) { float r; asm("ex2.approx.ftz.f32 %0, %1;" : "=f"(r) : "f"(x)); return r; }
__device__ __forceinline__ float gelu_tanh(float x) {
  float u = x * fmaf(x * x, 0.0356774081f, 0.7978845608f), t;
  asm("tanh.approx.f32 %0, %1;" : "=f"(t) : "f"(u));
  float h = 0.5f * x;
  return fmaf(h, t, h);
}
__device__ __forceinline__ void sts32(uint32_t a, uint32_t v) { asm volatile("st.shared.u32 [%0], %1;" ::"r"(a), "r"(v) : "memory"); }
__device__ __forceinline__ void sts16(uint32_t a, uint16_t v) { asm volatile("st.shared.u16 [%0], %1;" ::"r"(a), "h"(v) : "memory"); }
__device__ __forceinline__ void sts128(uint32_t a, uint32_t x, uint32_t y, uint32_t z, uint32_t w) { asm volatile("st.shared.v4.u32 [%0], {%1,%2,%3,%4};" ::"r"(a), "r"(x), "r"(y), "r"(z), "r"(w) : "memory"); }
__device__ __forceinline__ uint32_t lds32(uint32_t a) { uint32_t v; asm volatile("ld.shared.u32 %0, [%1];" : "=r"(v) : "r"(a) : "memory"); return v; }
__device__ __forceinline__ float ldsf(uint32_t a) { return __uint_as_float(lds32(a)); }
__device__ __forceinline__ uint4 lds128(uint32_t a) { uint4 v; asm volatile("ld.shared.v4.u32 {%0,%1,%2,%3}, [%4];" : "=r"(v.x), "=r"(v.y), "=r"(v.z), "=r"(v.w) : "r"(a) : "memory"); return v; }

template<int OFF, int TOT> __device__ __forceinline__ void wg_ss_n88(float (&d)[TOT], uint64_t da, uint64_t db) {
  asm volatile("wgmma.mma_async.sync.aligned.m64n88k16.f32.bf16.bf16 {%0, %1, %2, %3, %4, %5, %6, %7, %8, %9, %10, %11, %12, %13, %14, %15, %16, %17, %18, %19, %20, %21, %22, %23, %24, %25, %26, %27, %28, %29, %30, %31, %32, %33, %34, %35, %36, %37, %38, %39, %40, %41, %42, %43}, %44, %45, 1, 1, 1, 0, 1;"
    : "+f"(d[OFF+0]), "+f"(d[OFF+1]), "+f"(d[OFF+2]), "+f"(d[OFF+3]), "+f"(d[OFF+4]), "+f"(d[OFF+5]), "+f"(d[OFF+6]), "+f"(d[OFF+7]),
      "+f"(d[OFF+8]), "+f"(d[OFF+9]), "+f"(d[OFF+10]), "+f"(d[OFF+11]), "+f"(d[OFF+12]), "+f"(d[OFF+13]), "+f"(d[OFF+14]), "+f"(d[OFF+15]),
      "+f"(d[OFF+16]), "+f"(d[OFF+17]), "+f"(d[OFF+18]), "+f"(d[OFF+19]), "+f"(d[OFF+20]), "+f"(d[OFF+21]), "+f"(d[OFF+22]), "+f"(d[OFF+23]),
      "+f"(d[OFF+24]), "+f"(d[OFF+25]), "+f"(d[OFF+26]), "+f"(d[OFF+27]), "+f"(d[OFF+28]), "+f"(d[OFF+29]), "+f"(d[OFF+30]), "+f"(d[OFF+31]),
      "+f"(d[OFF+32]), "+f"(d[OFF+33]), "+f"(d[OFF+34]), "+f"(d[OFF+35]), "+f"(d[OFF+36]), "+f"(d[OFF+37]), "+f"(d[OFF+38]), "+f"(d[OFF+39]),
      "+f"(d[OFF+40]), "+f"(d[OFF+41]), "+f"(d[OFF+42]), "+f"(d[OFF+43])
    : "l"(da), "l"(db));
}
template<int OFF, int TOT> __device__ __forceinline__ void wg_ss_n128(float (&d)[TOT], uint64_t da, uint64_t db) {
  asm volatile("wgmma.mma_async.sync.aligned.m64n128k16.f32.bf16.bf16 {%0, %1, %2, %3, %4, %5, %6, %7, %8, %9, %10, %11, %12, %13, %14, %15, %16, %17, %18, %19, %20, %21, %22, %23, %24, %25, %26, %27, %28, %29, %30, %31, %32, %33, %34, %35, %36, %37, %38, %39, %40, %41, %42, %43, %44, %45, %46, %47, %48, %49, %50, %51, %52, %53, %54, %55, %56, %57, %58, %59, %60, %61, %62, %63}, %64, %65, 1, 1, 1, 0, 1;"
    : "+f"(d[OFF+0]), "+f"(d[OFF+1]), "+f"(d[OFF+2]), "+f"(d[OFF+3]), "+f"(d[OFF+4]), "+f"(d[OFF+5]), "+f"(d[OFF+6]), "+f"(d[OFF+7]),
      "+f"(d[OFF+8]), "+f"(d[OFF+9]), "+f"(d[OFF+10]), "+f"(d[OFF+11]), "+f"(d[OFF+12]), "+f"(d[OFF+13]), "+f"(d[OFF+14]), "+f"(d[OFF+15]),
      "+f"(d[OFF+16]), "+f"(d[OFF+17]), "+f"(d[OFF+18]), "+f"(d[OFF+19]), "+f"(d[OFF+20]), "+f"(d[OFF+21]), "+f"(d[OFF+22]), "+f"(d[OFF+23]),
      "+f"(d[OFF+24]), "+f"(d[OFF+25]), "+f"(d[OFF+26]), "+f"(d[OFF+27]), "+f"(d[OFF+28]), "+f"(d[OFF+29]), "+f"(d[OFF+30]), "+f"(d[OFF+31]),
      "+f"(d[OFF+32]), "+f"(d[OFF+33]), "+f"(d[OFF+34]), "+f"(d[OFF+35]), "+f"(d[OFF+36]), "+f"(d[OFF+37]), "+f"(d[OFF+38]), "+f"(d[OFF+39]),
      "+f"(d[OFF+40]), "+f"(d[OFF+41]), "+f"(d[OFF+42]), "+f"(d[OFF+43]), "+f"(d[OFF+44]), "+f"(d[OFF+45]), "+f"(d[OFF+46]), "+f"(d[OFF+47]),
      "+f"(d[OFF+48]), "+f"(d[OFF+49]), "+f"(d[OFF+50]), "+f"(d[OFF+51]), "+f"(d[OFF+52]), "+f"(d[OFF+53]), "+f"(d[OFF+54]), "+f"(d[OFF+55]),
      "+f"(d[OFF+56]), "+f"(d[OFF+57]), "+f"(d[OFF+58]), "+f"(d[OFF+59]), "+f"(d[OFF+60]), "+f"(d[OFF+61]), "+f"(d[OFF+62]), "+f"(d[OFF+63])
    : "l"(da), "l"(db));
}
template<int OFF, int TOT> __device__ __forceinline__ void wg_ss_n64(float (&d)[TOT], uint64_t da, uint64_t db) {
  asm volatile("wgmma.mma_async.sync.aligned.m64n64k16.f32.bf16.bf16 {%0, %1, %2, %3, %4, %5, %6, %7, %8, %9, %10, %11, %12, %13, %14, %15, %16, %17, %18, %19, %20, %21, %22, %23, %24, %25, %26, %27, %28, %29, %30, %31}, %32, %33, 1, 1, 1, 0, 1;"
    : "+f"(d[OFF+0]), "+f"(d[OFF+1]), "+f"(d[OFF+2]), "+f"(d[OFF+3]), "+f"(d[OFF+4]), "+f"(d[OFF+5]), "+f"(d[OFF+6]), "+f"(d[OFF+7]),
      "+f"(d[OFF+8]), "+f"(d[OFF+9]), "+f"(d[OFF+10]), "+f"(d[OFF+11]), "+f"(d[OFF+12]), "+f"(d[OFF+13]), "+f"(d[OFF+14]), "+f"(d[OFF+15]),
      "+f"(d[OFF+16]), "+f"(d[OFF+17]), "+f"(d[OFF+18]), "+f"(d[OFF+19]), "+f"(d[OFF+20]), "+f"(d[OFF+21]), "+f"(d[OFF+22]), "+f"(d[OFF+23]),
      "+f"(d[OFF+24]), "+f"(d[OFF+25]), "+f"(d[OFF+26]), "+f"(d[OFF+27]), "+f"(d[OFF+28]), "+f"(d[OFF+29]), "+f"(d[OFF+30]), "+f"(d[OFF+31])
    : "l"(da), "l"(db));
}
template<int OFF, int TOT> __device__ __forceinline__ void wg_ss_n32t(float (&d)[TOT], uint64_t da, uint64_t db) {
  asm volatile("wgmma.mma_async.sync.aligned.m64n32k16.f32.bf16.bf16 {%0, %1, %2, %3, %4, %5, %6, %7, %8, %9, %10, %11, %12, %13, %14, %15}, %16, %17, 1, 1, 1, 1, 0;"
    : "+f"(d[OFF+0]), "+f"(d[OFF+1]), "+f"(d[OFF+2]), "+f"(d[OFF+3]), "+f"(d[OFF+4]), "+f"(d[OFF+5]), "+f"(d[OFF+6]), "+f"(d[OFF+7]),
      "+f"(d[OFF+8]), "+f"(d[OFF+9]), "+f"(d[OFF+10]), "+f"(d[OFF+11]), "+f"(d[OFF+12]), "+f"(d[OFF+13]), "+f"(d[OFF+14]), "+f"(d[OFF+15])
    : "l"(da), "l"(db));
}
template<int SCD, int OFF, int TOT> __device__ __forceinline__ void wg_qk_n16(float (&d)[TOT], uint32_t a0, uint32_t a1, uint32_t a2, uint32_t a3, uint64_t db) {
  asm volatile("wgmma.mma_async.sync.aligned.m64n16k16.f32.f16.f16 {%0, %1, %2, %3, %4, %5, %6, %7}, {%8,%9,%10,%11}, %12, %13, 1, 1, 0;"
    : "+f"(d[OFF+0]), "+f"(d[OFF+1]), "+f"(d[OFF+2]), "+f"(d[OFF+3]), "+f"(d[OFF+4]), "+f"(d[OFF+5]), "+f"(d[OFF+6]), "+f"(d[OFF+7])
    : "r"(a0), "r"(a1), "r"(a2), "r"(a3), "l"(db), "n"(SCD));
}
template<int SCD, int OFF, int TOT> __device__ __forceinline__ void wg_qk_n24(float (&d)[TOT], uint32_t a0, uint32_t a1, uint32_t a2, uint32_t a3, uint64_t db) {
  asm volatile("wgmma.mma_async.sync.aligned.m64n24k16.f32.f16.f16 {%0, %1, %2, %3, %4, %5, %6, %7, %8, %9, %10, %11}, {%12,%13,%14,%15}, %16, %17, 1, 1, 0;"
    : "+f"(d[OFF+0]), "+f"(d[OFF+1]), "+f"(d[OFF+2]), "+f"(d[OFF+3]), "+f"(d[OFF+4]), "+f"(d[OFF+5]), "+f"(d[OFF+6]), "+f"(d[OFF+7]),
      "+f"(d[OFF+8]), "+f"(d[OFF+9]), "+f"(d[OFF+10]), "+f"(d[OFF+11])
    : "r"(a0), "r"(a1), "r"(a2), "r"(a3), "l"(db), "n"(SCD));
}
template<int SCD, int OFF, int TOT> __device__ __forceinline__ void wg_qk_n32(float (&d)[TOT], uint32_t a0, uint32_t a1, uint32_t a2, uint32_t a3, uint64_t db) {
  asm volatile("wgmma.mma_async.sync.aligned.m64n32k16.f32.f16.f16 {%0, %1, %2, %3, %4, %5, %6, %7, %8, %9, %10, %11, %12, %13, %14, %15}, {%16,%17,%18,%19}, %20, %21, 1, 1, 0;"
    : "+f"(d[OFF+0]), "+f"(d[OFF+1]), "+f"(d[OFF+2]), "+f"(d[OFF+3]), "+f"(d[OFF+4]), "+f"(d[OFF+5]), "+f"(d[OFF+6]), "+f"(d[OFF+7]),
      "+f"(d[OFF+8]), "+f"(d[OFF+9]), "+f"(d[OFF+10]), "+f"(d[OFF+11]), "+f"(d[OFF+12]), "+f"(d[OFF+13]), "+f"(d[OFF+14]), "+f"(d[OFF+15])
    : "r"(a0), "r"(a1), "r"(a2), "r"(a3), "l"(db), "n"(SCD));
}
template<int SCD, int OFF, int TOT> __device__ __forceinline__ void wg_qk_n40(float (&d)[TOT], uint32_t a0, uint32_t a1, uint32_t a2, uint32_t a3, uint64_t db) {
  asm volatile("wgmma.mma_async.sync.aligned.m64n40k16.f32.f16.f16 {%0, %1, %2, %3, %4, %5, %6, %7, %8, %9, %10, %11, %12, %13, %14, %15, %16, %17, %18, %19}, {%20,%21,%22,%23}, %24, %25, 1, 1, 0;"
    : "+f"(d[OFF+0]), "+f"(d[OFF+1]), "+f"(d[OFF+2]), "+f"(d[OFF+3]), "+f"(d[OFF+4]), "+f"(d[OFF+5]), "+f"(d[OFF+6]), "+f"(d[OFF+7]),
      "+f"(d[OFF+8]), "+f"(d[OFF+9]), "+f"(d[OFF+10]), "+f"(d[OFF+11]), "+f"(d[OFF+12]), "+f"(d[OFF+13]), "+f"(d[OFF+14]), "+f"(d[OFF+15]),
      "+f"(d[OFF+16]), "+f"(d[OFF+17]), "+f"(d[OFF+18]), "+f"(d[OFF+19])
    : "r"(a0), "r"(a1), "r"(a2), "r"(a3), "l"(db), "n"(SCD));
}
template<int SCD, int OFF, int TOT> __device__ __forceinline__ void wg_qk_n48(float (&d)[TOT], uint32_t a0, uint32_t a1, uint32_t a2, uint32_t a3, uint64_t db) {
  asm volatile("wgmma.mma_async.sync.aligned.m64n48k16.f32.f16.f16 {%0, %1, %2, %3, %4, %5, %6, %7, %8, %9, %10, %11, %12, %13, %14, %15, %16, %17, %18, %19, %20, %21, %22, %23}, {%24,%25,%26,%27}, %28, %29, 1, 1, 0;"
    : "+f"(d[OFF+0]), "+f"(d[OFF+1]), "+f"(d[OFF+2]), "+f"(d[OFF+3]), "+f"(d[OFF+4]), "+f"(d[OFF+5]), "+f"(d[OFF+6]), "+f"(d[OFF+7]),
      "+f"(d[OFF+8]), "+f"(d[OFF+9]), "+f"(d[OFF+10]), "+f"(d[OFF+11]), "+f"(d[OFF+12]), "+f"(d[OFF+13]), "+f"(d[OFF+14]), "+f"(d[OFF+15]),
      "+f"(d[OFF+16]), "+f"(d[OFF+17]), "+f"(d[OFF+18]), "+f"(d[OFF+19]), "+f"(d[OFF+20]), "+f"(d[OFF+21]), "+f"(d[OFF+22]), "+f"(d[OFF+23])
    : "r"(a0), "r"(a1), "r"(a2), "r"(a3), "l"(db), "n"(SCD));
}
template<int SCD, int OFF, int TOT> __device__ __forceinline__ void wg_pv_n24(float (&d)[TOT], uint32_t a0, uint32_t a1, uint32_t a2, uint32_t a3, uint64_t db) {
  asm volatile("wgmma.mma_async.sync.aligned.m64n24k16.f32.bf16.bf16 {%0, %1, %2, %3, %4, %5, %6, %7, %8, %9, %10, %11}, {%12,%13,%14,%15}, %16, %17, 1, 1, 1;"
    : "+f"(d[OFF+0]), "+f"(d[OFF+1]), "+f"(d[OFF+2]), "+f"(d[OFF+3]), "+f"(d[OFF+4]), "+f"(d[OFF+5]), "+f"(d[OFF+6]), "+f"(d[OFF+7]),
      "+f"(d[OFF+8]), "+f"(d[OFF+9]), "+f"(d[OFF+10]), "+f"(d[OFF+11])
    : "r"(a0), "r"(a1), "r"(a2), "r"(a3), "l"(db), "n"(SCD));
}
template<int SCD, int OFF, int TOT> __device__ __forceinline__ void wg_qkb_n64(float (&d)[TOT], uint32_t a0, uint32_t a1, uint32_t a2, uint32_t a3, uint64_t db) {
  asm volatile("wgmma.mma_async.sync.aligned.m64n64k16.f32.bf16.bf16 {%0, %1, %2, %3, %4, %5, %6, %7, %8, %9, %10, %11, %12, %13, %14, %15, %16, %17, %18, %19, %20, %21, %22, %23, %24, %25, %26, %27, %28, %29, %30, %31}, {%32,%33,%34,%35}, %36, %37, 1, 1, 0;"
    : "+f"(d[OFF+0]), "+f"(d[OFF+1]), "+f"(d[OFF+2]), "+f"(d[OFF+3]), "+f"(d[OFF+4]), "+f"(d[OFF+5]), "+f"(d[OFF+6]), "+f"(d[OFF+7]),
      "+f"(d[OFF+8]), "+f"(d[OFF+9]), "+f"(d[OFF+10]), "+f"(d[OFF+11]), "+f"(d[OFF+12]), "+f"(d[OFF+13]), "+f"(d[OFF+14]), "+f"(d[OFF+15]),
      "+f"(d[OFF+16]), "+f"(d[OFF+17]), "+f"(d[OFF+18]), "+f"(d[OFF+19]), "+f"(d[OFF+20]), "+f"(d[OFF+21]), "+f"(d[OFF+22]), "+f"(d[OFF+23]),
      "+f"(d[OFF+24]), "+f"(d[OFF+25]), "+f"(d[OFF+26]), "+f"(d[OFF+27]), "+f"(d[OFF+28]), "+f"(d[OFF+29]), "+f"(d[OFF+30]), "+f"(d[OFF+31])
    : "r"(a0), "r"(a1), "r"(a2), "r"(a3), "l"(db), "n"(SCD));
}
template<int N, int SCD, int OFF, int TOT> __device__ __forceinline__ void wg_qk(float (&d)[TOT], const uint32_t (&q)[4], uint64_t db) {
  if constexpr (N == 16) wg_qk_n16<SCD, OFF, TOT>(d, q[0], q[1], q[2], q[3], db);
  if constexpr (N == 24) wg_qk_n24<SCD, OFF, TOT>(d, q[0], q[1], q[2], q[3], db);
  if constexpr (N == 32) wg_qk_n32<SCD, OFF, TOT>(d, q[0], q[1], q[2], q[3], db);
  if constexpr (N == 40) wg_qk_n40<SCD, OFF, TOT>(d, q[0], q[1], q[2], q[3], db);
  if constexpr (N == 48) wg_qk_n48<SCD, OFF, TOT>(d, q[0], q[1], q[2], q[3], db);
}

__device__ __forceinline__ uint32_t exp_mufu(float a, float b) { return pack_bf16(ex2(a), ex2(b)); }
__device__ __forceinline__ uint32_t exp_poly(float a, float b, uint32_t mlo, uint32_t mhi) {
  uint32_t u = __byte_perm(__float_as_uint(a), __float_as_uint(b), 0x6521), mh, e, p;
  asm("lop3.b32 %0, %1, %2, 0x3F003F00, 0xEA;" : "=r"(mh) : "r"(u), "r"(mlo));
  asm("lop3.b32 %0, %1, %2, 0x00020002, 0xEA;" : "=r"(e) : "r"(u), "r"(mhi));
  asm("fma.rn.bf16x2 %0, %1, %2, %3;" : "=r"(p) : "r"(u), "r"(mh), "r"(e));
  return p;
}
constexpr float MAGIC_C = 48948.0625f;
constexpr float QSCALE = 0.25f * 1.4426950408889634f * 8.f;
constexpr float BOUND = 80.f;

__device__ __forceinline__ void softmax_step(const float (&s)[32], uint32_t (&p)[16], uint32_t mlo, uint32_t mhi) {
  constexpr int PP = NP / 4;
  int ip = 0, im = PP;
#pragma unroll
  for (int i = 0; i < 16; i++) {
    if (((i + 1) * PP / 16) > (i * PP / 16)) { p[ip] = exp_poly(s[2 * ip], s[2 * ip + 1], mlo, mhi); ip++; }
    else { p[im] = exp_mufu(s[2 * im], s[2 * im + 1]); im++; }
  }
}
constexpr uint64_t VSTEP = ((uint64_t)16 << 32) - 16;
__device__ __forceinline__ void issue_qk(float (&s)[32], const uint32_t (&q)[4], uint64_t dk) {
  wg_qk<NM, 0, NP / 2, 32>(s, q, dk + NP * 2);
  wg_qk<NP, 1, 0, 32>(s, q, dk);
}
__device__ __forceinline__ void issue_pv(float (&o)[12], const uint32_t (&p)[16], uint64_t& dv, uint64_t vstep) {
#pragma unroll
  for (int c = 0; c < 4; c++) { wg_pv_n24<1, 0, 12>(o, p[4 * c], p[4 * c + 1], p[4 * c + 2], p[4 * c + 3], dv); dv += vstep; }
}

struct Params {
  const __nv_bfloat16* gate_w;
  const __nv_bfloat16* b_sp;
  const __nv_bfloat16* w_out;
  const __nv_bfloat16* wo;
  const __nv_bfloat16* w_in;
  const __nv_bfloat16* wq;
  const __nv_bfloat16* wk;
  const __nv_bfloat16* wv;
  uint64_t vstep;
  uint32_t mlo, mhi;
  __nv_bfloat16* out;
};

__device__ __forceinline__ uint32_t store_o_tile(const float (&o)[12], int bi, int bj, int tau, int tid, uint32_t sb) {
  const int half = tau & 1, hh = tau >> 1, w = tid >> 5, l = tid & 31;
  const int r0 = half * 64 + w * 16 + (l >> 2);
  const float f0 = __fdividef(ldsf(sb + SM_G + r0 * 4), o[4]), f1 = __fdividef(ldsf(sb + SM_G + (r0 + 8) * 4), o[6]);
  uint32_t* dst = reinterpret_cast<uint32_t*>(g_o) + (bi * 8 + bj) * 4096 + (half * 8 + w * 2) * 256 + hh * 64;
  dst[l] = pack_bf16(o[0] * f0, o[1] * f0);
  dst[l + 32] = pack_bf16(o[8] * f0, o[9] * f0);
  dst[l + 256] = pack_bf16(o[2] * f1, o[3] * f1);
  dst[l + 288] = pack_bf16(o[10] * f1, o[11] * f1);
  return ld_back(dst + ((l >> 3) & 1) * 256 + (l & 7) * 8);
}

__global__ void __cluster_dims__(2, 1, 1) __launch_bounds__(NTHREADS, 1)
fused_kernel(const __grid_constant__ CUtensorMap tm_x, const __grid_constant__ CUtensorMap tm_wq,
             const __grid_constant__ CUtensorMap tm_win, const __grid_constant__ CUtensorMap tm_wsp,
             const __grid_constant__ CUtensorMap tm_wout, const __grid_constant__ CUtensorMap tm_wo, const Params prm) {
  extern __shared__ __align__(1024) uint8_t smem_raw[];
  const uint32_t sb = (uint32_t)__cvta_generic_to_shared(smem_raw);
  const int warp = __shfl_sync(0xffffffffu, (int)(threadIdx.x >> 5), 0);
  const int wg = warp >> 2;
  const int tid = threadIdx.x & 127;
  const int lane = threadIdx.x & 31;
  const int rank = blockIdx.x & 1;
  const int ai = (blockIdx.x >> 4) * 2 + rank, aj = (blockIdx.x >> 1) & 7;
  const int bi = blockIdx.x >> 3, bj = blockIdx.x & 7;
  auto BAR = [&](int k) { return sb + SM_BAR + 8u * k; };

  if (lane == 0) {
    if (warp == 16) {
      asm volatile("prefetch.tensormap [%0];" ::"l"(&tm_x) : "memory");
    } else if (warp == 18) {
      asm volatile("prefetch.tensormap [%0];" ::"l"(&tm_win) : "memory");
      asm volatile("prefetch.tensormap [%0];" ::"l"(&tm_wq) : "memory");
    } else if (warp == 19) {
      l2_prefetch(reinterpret_cast<const uint8_t*>(prm.w_in) + blockIdx.x * 11008, 11008);
      l2_prefetch(reinterpret_cast<const uint8_t*>(prm.wq) + blockIdx.x * 4096, 4096);
    } else if (warp < 16) {
#pragma unroll
      for (int r = 0; r < 5; r++) {
        const int k = warp + 16 * r;
        uint32_t cnt = 1;
        if (k >= B_XEMPTY && k < B_XEMPTY + 8) cnt = 4;
        if (k >= B_WEMPTY && k < B_WEMPTY + 12) cnt = 4;
        if (k >= B_REMPTY && k < B_REMPTY + 3) cnt = 2;
        if (k == B_ATT) cnt = 6;
        if (k == B_QRDY) cnt = 16;
        if (k == B_KSTAT) cnt = 17;
        mbar_init(BAR(k), cnt);
      }
      asm volatile("fence.mbarrier_init.release.cluster;" ::: "memory");
    }
  }
  __syncthreads();
  if (threadIdx.x == 0) TS(35);
  asm volatile("barrier.cluster.arrive.relaxed.aligned;" ::: "memory");
  if (warp != 16) asm volatile("barrier.cluster.wait.acquire.aligned;" ::: "memory");

  if (wg == 4) {
    asm volatile("setmaxnreg.dec.sync.aligned.u32 24;");
    if (warp == 18) {
      if (lane == 0) {
#pragma unroll 1
        for (int f = 0; f < 16; f++) {
          if (f == 4) TS(37);
          if (f >= 4) mbar_wait(BAR(B_WEMPTY + f - 4), 0);
          const uint32_t dst = sb + SM_RING + (f & 3) * WSLOT + rank * 2048, bar = BAR(B_WFULL + f);
          const int k0 = (f & 7) * 64 + rank * 32;
          const bool three = f < 8 ? aj < 6 : aj >= 2;
          const int c0 = 32 * (f < 8 ? (aj < 6 ? 21 + 3 * aj : 27 + 2 * aj) : (aj < 2 ? 2 * aj : 3 * aj - 2));
          mbar_expect(bar, three ? 16384 : 12288);
          tma2d_mc(dst, &tm_win, c0, k0, bar);
          tma2d_mc(dst + 4096, &tm_win, c0 + 32, k0, bar);
          if (three) tma2d_mc(dst + 8192, &tm_win, c0 + 64, k0, bar);
          tma2d_mc(dst + 12288, &tm_wq, 64 * aj + (f >> 3) * 32, k0, bar);
        }
        TS(1);
      }
    } else if (warp == 19) {
      mbar_wait(BAR(B_XEMPTY + 6), 0);
      const unsigned ep1 = lds32(sb + SM_MISC + 4 * M_EPOCH) + 1;
      wait_ge(&g_zcnt[lane * 32], ep1 * 8);
      __syncwarp();
      if (lane == 0) {
        mbar_arrive(BAR(B_ZOK));
        wait_ge(&g_z1cnt[bi * 32], ep1 * 16);
        mbar_arrive(BAR(B_Z1OK));
      }
    } else if (warp == 16) {
      if (lane == 0) {
        TS(0);
#pragma unroll 1
        for (int c = 0; c < 8; c++) {
          mbar_expect(BAR(B_XFULL + c), 16384);
          tma2d(sb + SM_K + c * 16384, &tm_x, c * 64, ai * 128, BAR(B_XFULL + c));
        }
        TS(36);
      }
      __syncwarp();
      asm volatile("barrier.cluster.wait.acquire.aligned;" ::: "memory");
      if (lane == 0) {
        asm volatile("prefetch.tensormap [%0];" ::"l"(&tm_wsp) : "memory");
        asm volatile("prefetch.tensormap [%0];" ::"l"(&tm_wout) : "memory");
        asm volatile("prefetch.tensormap [%0];" ::"l"(&tm_wo) : "memory");
        const int row = bi * 128 + rank * 64;
        mbar_wait(BAR(B_XEMPTY), 0);
        tma2d_pf(&tm_wsp, (bj >> 1) * 64, row);
        tma2d_pf(&tm_wsp, (bj >> 1) * 64 + 256, row);
        mbar_wait(BAR(B_XEMPTY + 7), 0);
        mbar_wait(BAR(B_ZOK), 0);
        const unsigned ep1 = lds32(sb + SM_MISC + 4 * M_EPOCH) + 1;
        fence_async();
        TS(2);
        int st = 0, ph = 1;
#pragma unroll 1
        for (int n = 0; n < 46; n++) {
          const uint32_t stg = sb + SM_RING + st * RSTAGE, bar = BAR(B_RFULL + st);
          if (n >= 3) mbar_wait(BAR(B_REMPTY + st), ph);
          if (n < 32) {
            mbar_expect(bar, 16384 + 11264);
            tma2d_mc(stg + rank * 8192, &tm_wsp, n * 64, row, bar);
            bulk(stg + 16384, reinterpret_cast<const uint8_t*>(g_z2n) + (bj * 32 + n) * 11264, 11264, bar);
            if ((n & 3) == (bj >> 1) && n < 24) tma2d_pf(&tm_wsp, (n + 8) * 64, row);
            if (n == 16) {
              l2_prefetch(reinterpret_cast<const uint8_t*>(prm.w_out) + blockIdx.x * 5504, 5504);
              l2_prefetch(reinterpret_cast<const uint8_t*>(prm.wo) + blockIdx.x * 4096, 4096);
            }
          } else if (n < 43) {
            const int c = n - 32;
            mbar_expect(bar, 16384 + 8192);
            tma2d(stg + 16384, &tm_wout, 64 * bj, c * 64, bar);
            if (c == 0) { wait_ge(&g_ucnt[bi * 32], ep1 * 8); fence_async(); TS(3); }
            bulk_mc(stg + rank * 8192, reinterpret_cast<const uint8_t*>(g_u) + (bi * 11 + c) * 16384 + rank * 8192, 8192, bar);
          }
          if (++st == 3) { st = 0; ph ^= 1; }
        }
        mbar_expect(BAR(B_WOFULL), 65536);
#pragma unroll 1
        for (int c = 0; c < 8; c++) tma2d(sb + SM_RING + c * 8192, &tm_wo, 64 * bj, c * 64, BAR(B_WOFULL));
        TS(4);
        wait_ge(&g_ocnt[bi * 32], ep1 * 24);
        mbar_wait(BAR(B_ATT), 0);
        fence_async();
        TS(5);
#pragma unroll 1
        for (int c = 0; c < 8; c++) {
          mbar_expect(BAR(B_OFULL + c), 16384);
          bulk_mc(sb + SM_K + c * 16384 + rank * 8192, reinterpret_cast<const uint8_t*>(g_o) + (bi * 8 + c) * 16384 + rank * 8192, 8192, BAR(B_OFULL + c));
        }
      }
    } else {
      if (lane == 0) {
        sts32(sb + SM_MISC + 4 * M_EPOCH, atomicAdd(&g_ticket, 1u) / NCTA);
        mbar_arrive(BAR(B_EPOCH));
        TS(71);
      }
      __syncwarp();
      const unsigned ep1 = lds32(sb + SM_MISC + 4 * M_EPOCH) + 1;
      mbar_wait(BAR(B_WFULL + 8), 0);
      uint32_t kn = 0, vb = 0;
#pragma unroll 1
      for (int n = 0; n < SPIN_LIMIT; n++) {
        unsigned long long a, b, c, d;
        asm volatile("ld.relaxed.gpu.global.v2.b64 {%0, %1}, [%2];" : "=l"(a), "=l"(b) : "l"(&g_kvflag[2 * lane]) : "memory");
        asm volatile("ld.relaxed.gpu.global.v2.b64 {%0, %1}, [%2];" : "=l"(c), "=l"(d) : "l"(&g_kvflag[64 + 2 * lane]) : "memory");
        kn = max((uint32_t)a, (uint32_t)c); vb = (uint32_t)b | (uint32_t)d;
        if (__all_sync(0xffffffffu, (uint32_t)(a >> 32) == ep1 && (uint32_t)(b >> 32) == ep1 && (uint32_t)(c >> 32) == ep1 && (uint32_t)(d >> 32) == ep1)) break;
        __nanosleep(100);
      }
      asm volatile("fence.acquire.gpu;" ::: "memory");
      kn = __reduce_max_sync(0xffffffffu, kn);
      vb = __reduce_or_sync(0xffffffffu, vb);
      if (lane == 0) {
        TS(6);
        sts32(sb + SM_MISC + 4 * M_KN2, kn);
        sts32(sb + SM_MISC + 4 * M_VOK, vb == 0xFFFFu ? 1u : 0u);
        mbar_arrive(BAR(B_KSTAT));
        fence_async();
#pragma unroll 1
        for (int c = 0; c < 8; c++) {
          const uint32_t bytes = c == 7 ? 16640 : 16384, hb = bytes / 2, off = c * 16384 + rank * hb;
          mbar_wait(BAR(B_XEMPTY + c), 0);
          mbar_expect(BAR(B_KVFULL + c), bytes);
          bulk_mc(sb + SM_K + off, reinterpret_cast<const uint8_t*>(g_kimg) + off, hb, BAR(B_KVFULL + c));
        }
        TS(7);
        mbar_wait(BAR(B_DEC), 0);
        if (!lds32(sb + SM_MISC + 4 * M_FAST)) {
#pragma unroll 1
          for (int c = 0; c < 4; c++) mbar_wait(BAR(B_KVFULL + c), 0);
          mbar_expect(BAR(B_KFB), 65536);
          bulk(sb + SM_K, g_kbf, 65536, BAR(B_KFB));
        }
      }
    }
  } else {
    asm volatile("setmaxnreg.inc.sync.aligned.u32 112;");
    const int w = tid >> 5, g = lane >> 2, t4 = lane & 3, half = wg & 1;
    {
      float acc[64];
      if (wg == 2) {
        const int slot = ai * 4 + (aj >> 1), isv = aj & 1;
        const uint4* wsrc = reinterpret_cast<const uint4*>(isv ? prm.wv : prm.wk) + tid;
        uint4 wr[8];
#pragma unroll
        for (int r = 0; r < 8; r++) wr[r] = __ldg(wsrc + 128 * r);
#pragma unroll
        for (int r = 0; r < 8; r++) sts128(sb + SM_WKV + r * 2048 + (tid >> 1) * 32 + (((tid ^ (tid >> 3)) & 1) << 4), wr[r].x, wr[r].y, wr[r].z, wr[r].w);
        fence_async_smem();
        bar_sync(3, 128);
        float kv[16];
#pragma unroll
        for (int k = 0; k < 16; k++) kv[k] = 0.f;
        regfence(kv);
#pragma unroll 1
        for (int c = 0; c < 8; c++) {
          mbar_wait(BAR(B_XFULL + c), 0);
          const uint64_t da = mkdesc(sb + SM_WKV + c * 2048, 0, 256, 3);
          const uint64_t db = mkdesc(sb + SM_K + c * 16384 + (aj >> 1) * 4096, 16, 1024, 1);
          wg_fence();
#pragma unroll
          for (int k = 0; k < 4; k++) wg_ss_n32t<0, 16>(kv, da + 32 * k, db + 2 * k);
          wg_commit();
        }
        wg_wait<0>();
        regfence(kv);
        if (tid == 0) TS(22);
        const uint32_t sT = sb + SM_WKV, sH = sb + SM_WKV + 4096;
        bar_sync(3, 128);
        {
          const float a = w & 1 ? kv[4] : kv[0], b = w & 1 ? kv[5] : kv[1], c = w & 1 ? kv[6] : kv[2], d = w & 1 ? kv[7] : kv[3];
          const float e = w & 1 ? kv[12] : kv[8], f = w & 1 ? kv[13] : kv[9], h = w & 1 ? kv[14] : kv[10], i = w & 1 ? kv[15] : kv[11];
          const uint32_t lo = pack_bf16(w & 2 ? e : a, w & 2 ? f : b), hi = pack_bf16(w & 2 ? h : c, w & 2 ? i : d);
          const uint32_t p = sT + ((w * 8 + 2 * t4) * 17 + g) * 4;
          sts32(p, lo << 16); sts32(p + 68, lo & 0xFFFF0000u); sts32(p + 32, hi << 16); sts32(p + 100, hi & 0xFFFF0000u);
        }
        bar_sync(3, 128);
        if (tid == 0) TS(64);
        const int tok = (tid & 63) >> 1, hf = tid & 1;
        float f[8];
#pragma unroll
        for (int e = 0; e < 8; e++) f[e] = ldsf(sT + (tok * 17 + hf * 8 + e) * 4);
        uint4 val = make_uint4(pack_bf16(f[0], f[1]), pack_bf16(f[2], f[3]), pack_bf16(f[4], f[5]), pack_bf16(f[6], f[7]));
        uint32_t stat = 0;
        if (isv) {
#pragma unroll
          for (int e = 0; e < 8; e++) {
            if (fabsf(f[e]) >= 9.5367431640625e-07f) stat |= 1u << e;
            if (!(fabsf(f[e]) <= 1073741824.f)) stat |= 1u << (16 - 8 * hf);
          }
          stat = __reduce_or_sync(0xffffffffu, stat << (8 * hf));
        } else {
          float n2 = 0.f;
#pragma unroll
          for (int e = 0; e < 8; e++) n2 = fmaf(f[e], f[e], n2);
          n2 += __shfl_xor_sync(0xffffffffu, n2, 1);
          if (!(n2 <= 3.0e38f)) n2 = 3.0e38f;
          stat = __reduce_max_sync(0xffffffffu, __float_as_uint(n2));
          if (tid < 48) {
            const int d = tid & 15, sg = tid >> 4, j0 = sg == 0 ? 0 : (sg == 1 ? 10 : 22), j1 = sg == 0 ? 10 : (sg == 1 ? 22 : 32);
            const float sc = slot < NP ? 16.f : 0.125f, fb = slot < NP ? 1.f : 0.f;
            float kx[12], run = 0.f;
#pragma unroll
            for (int e = 0; e < 12; e++) kx[e] = ldsf(sT + (min(j0 + e, 31) * 17 + d) * 4);
#pragma unroll
            for (int e = 0; e < 12; e++) {
              const __half hv = __float2half_rn(fmaf(kx[e], sc, -run));
              run = fmaf(__half2float(hv), fb, run);
              if (j0 + e < j1) sts16(sH + ((j0 + e) * 16 + d) * 2, __half_as_ushort(hv));
            }
          }
        }
        if (lane == 0) sts32(sb + SM_MISC + 4 * (M_KVR + w), stat);
        bar_sync(3, 128);
        const uint32_t sbo = 256 * (4 * tok + (slot >> 4) + 1);
        uint32_t off = isv ? (hf ? SM_ONES + sbo : SM_ONES - sbo) + ((slot >> 3) & 1) * 128 : tok * 2048 + (slot >> 3) * 256 + hf * 128;
        off = (off >> 4) + (slot & 7);
        uint4* dst = (tid < 64 ? g_kimg : g_kbf) + off;
        if (!isv && tid < 64) val = lds128(sH + tok * 32 + hf * 16);
        if (isv && tid >= 64) { dst = g_kimg + (SM_ONES >> 4) + (tid & 15); val = make_uint4(0x3F803F80u, 0x3F803F80u, 0x3F803F80u, 0x3F803F80u); }
        uint32_t chk = 0;
        if (tid < 64 || !isv || (slot == 0 && tid < 80)) { *dst = val; chk = ld_back(dst); }
        mbar_wait(BAR(B_EPOCH), 0);
        consume(chk, sb);
        fence_async();
        bar_sync(3, 128);
        if (tid == 0) {
          const uint32_t s0 = lds32(sb + SM_MISC + 4 * M_KVR), s1 = lds32(sb + SM_MISC + 4 * (M_KVR + 1));
          const unsigned long long fl = ((unsigned long long)(lds32(sb + SM_MISC + 4 * M_EPOCH) + 1) << 32) | (isv ? (s0 | s1) : max(s0, s1));
          asm volatile("st.relaxed.gpu.global.b64 [%0], %1;" ::"l"(&g_kvflag[ai * 8 + aj]), "l"(fl) : "memory");
          TS(23);
        }
      } else if (wg == 3) {
        uint4* sW = reinterpret_cast<uint4*>(smem_raw + SM_GW);
        if (tid < 64) sW[tid] = __ldg(reinterpret_cast<const uint4*>(prm.gate_w) + tid);
        bar_sync(4, 128);
        const int v = tid & 7, rr = tid >> 3;
        float a[8];
#pragma unroll
        for (int p = 0; p < 8; p++) a[p] = 0.f;
#pragma unroll 1
        for (int c = 0; c < 8; c++) {
          const uint4 gv = sW[c * 8 + v];
          mbar_wait(BAR(B_XFULL + c), 0);
          if (tid == 0) TS(40 + c);
          const uint4* xr = reinterpret_cast<const uint4*>(smem_raw + SM_K + c * 16384 + rr * 128) + (v ^ (rr & 7));
#pragma unroll
          for (int p = 0; p < 8; p++) {
            const uint4 xv = xr[p * 128];
            float s = fmaf(bf_lo(xv.x), bf_lo(gv.x), a[p]), t = bf_hi(xv.x) * bf_hi(gv.x);
            s = fmaf(bf_lo(xv.y), bf_lo(gv.y), s); t = fmaf(bf_hi(xv.y), bf_hi(gv.y), t);
            s = fmaf(bf_lo(xv.z), bf_lo(gv.z), s); t = fmaf(bf_hi(xv.z), bf_hi(gv.z), t);
            s = fmaf(bf_lo(xv.w), bf_lo(gv.w), s); t = fmaf(bf_hi(xv.w), bf_hi(gv.w), t);
            a[p] = s + t;
          }
        }
        float mine = 0.f;
#pragma unroll
        for (int p = 0; p < 8; p++) {
          float s = a[p];
          s += __shfl_xor_sync(0xffffffffu, s, 1); s += __shfl_xor_sync(0xffffffffu, s, 2); s += __shfl_xor_sync(0xffffffffu, s, 4);
          if (v == p) mine = s;
        }
        const float gt = __fdividef(1.f, 1.f + __expf(-mine));
        sts32(sb + SM_G + (rr + 16 * v) * 4, __float_as_uint(gt));
        if (aj == 0) g_gate[ai * 128 + rr + 16 * v] = gt;
        fence_async_smem();
        bar_sync(4, 128);
        if (tid == 0) TS(8);
      }
#pragma unroll
      for (int k = 0; k < 64; k++) acc[k] = 0.f;
      regfence(acc);
      const int pass = wg >> 1;
#pragma unroll 1
      for (int c = 0; c < 8; c++) {
        mbar_wait(BAR(B_XFULL + c), 0);
        mbar_wait(BAR(B_WFULL + pass * 8 + c), 0);
        if (tid == 0 && half == pass) TS(48 + pass * 8 + c);
        const uint64_t da = mkdesc(sb + SM_K + c * 16384 + half * 8192, 16, 1024, 1);
        const uint64_t db = mkdesc(sb + SM_RING + (c & 3) * WSLOT, 4096, 512, 2);
        wg_fence();
#pragma unroll
        for (int k = 0; k < 4; k++) wg_ss_n128<0, 64>(acc, da + 2 * k, db + 64 * k);
        wg_commit();
        wg_wait<0>();
        if (tid == 0) {
          if (pass * 8 + c < 12) mbar_arrive_both(BAR(B_WEMPTY + pass * 8 + c));
          if (pass) mbar_arrive_both(BAR(B_XEMPTY + c));
        }
      }
      regfence(acc);
      if (tid == 0) TS(wg == 0 ? 16 : (wg == 2 ? 24 : (wg == 3 ? 9 : 95)));
      uint32_t qb[8];
      {
        float n2 = 0.f;
#pragma unroll
        for (int k = 0; k < 8; k++) qb[k] = pack_bf16(acc[48 + 2 * k], acc[49 + 2 * k]);
#pragma unroll
        for (int k = 0; k < 4; k++) {
          const uint32_t a = qb[4 * (k >> 1) + (k & 1)], b = qb[4 * (k >> 1) + (k & 1) + 2];
          float s = bf_lo(a) * bf_lo(a);
          s = fmaf(bf_hi(a), bf_hi(a), s); s = fmaf(bf_lo(b), bf_lo(b), s); s = fmaf(bf_hi(b), bf_hi(b), s);
          s += __shfl_xor_sync(0xffffffffu, s, 1); s += __shfl_xor_sync(0xffffffffu, s, 2);
          if (!(s <= 3.0e38f)) s = 3.0e38f;
          n2 = fmaxf(n2, s);
        }
        const uint32_t nmax = __reduce_max_sync(0xffffffffu, __float_as_uint(n2));
        if (lane == 0) { sts32(sb + SM_MISC + 4 * (M_RED + warp), nmax); mbar_arrive(BAR(B_KSTAT)); }
      }
      auto finish_q = [&]() {
        mbar_wait(BAR(B_KSTAT), 0);
        const float qn2 = __uint_as_float(__reduce_max_sync(0xffffffffu, lds32(sb + SM_MISC + 4 * (M_RED + (lane & 15)))));
        const float kn2 = ldsf(sb + SM_MISC + 4 * M_KN2);
        constexpr float SC = QSCALE * 0.125f;
        const bool fast = lds32(sb + SM_MISC + 4 * M_VOK) && qn2 <= 4.0e8f && kn2 <= 4.0e6f && qn2 * kn2 * (SC * SC) <= BOUND * BOUND;
        if (fast) {
#pragma unroll
          for (int k = 0; k < 8; k++) qb[k] = pack_f16(bf_lo(qb[k]) * QSCALE, bf_hi(qb[k]) * QSCALE);
        }
        sts128(sb + SM_Q + wg * 2048 + pass * 4096 + tid * 16, qb[0], qb[1], qb[2], qb[3]);
        sts128(sb + SM_Q + wg * 2048 + pass * 4096 + 4096 + tid * 16, qb[4], qb[5], qb[6], qb[7]);
        if (threadIdx.x == 256) { sts32(sb + SM_MISC + 4 * M_FAST, fast ? 1u : 0u); mbar_arrive(BAR(B_DEC)); }
        __syncwarp();
        if (lane == 0) mbar_arrive(BAR(B_QRDY));
        if (tid == 0 && pass) TS(75 + wg);
      };
      if (pass) finish_q();
#pragma unroll
      for (int k = 0; k < 48; k++) acc[k] = gelu_tanh(acc[k]);
      int fb0, c_lo = 0, c_hi = 12;
      if (wg < 2) { fb0 = aj < 6 ? 12 * aj - 2 : 22 + 8 * aj; if (aj == 0) c_lo = 2; if (aj >= 6) c_hi = 8; }
      else { fb0 = aj < 2 ? 8 * aj : 12 * aj - 8; if (aj < 2) c_hi = 8; if (aj == 7) c_hi = 10; }
      if (wg < 2) {
        const bool lo_ok = c_lo == 0, hi_ok = c_hi == 12;
        float s0 = 0.f, s1 = 0.f;
#pragma unroll
        for (int k = 0; k < 48; k++) {
          if ((k < 8 && !lo_ok) || (k >= 32 && !hi_ok)) acc[k] = 0.f;
          if (k & 2) s1 += acc[k]; else s0 += acc[k];
        }
        s0 += __shfl_xor_sync(0xffffffffu, s0, 1); s0 += __shfl_xor_sync(0xffffffffu, s0, 2);
        s1 += __shfl_xor_sync(0xffffffffu, s1, 1); s1 += __shfl_xor_sync(0xffffffffu, s1, 2);
        const float inv_n = __fdividef(0.125f, (float)(c_hi - c_lo));
        const float m0 = s0 * inv_n, m1 = s1 * inv_n;
        float v0 = 0.f, v1 = 0.f;
#pragma unroll
        for (int k = 0; k < 48; k++) {
          float d = acc[k] - ((k & 2) ? m1 : m0);
          if ((k < 8 && !lo_ok) || (k >= 32 && !hi_ok)) d = 0.f;
          if (k & 2) v1 = fmaf(d, d, v1); else v0 = fmaf(d, d, v0);
        }
        v0 += __shfl_xor_sync(0xffffffffu, v0, 1); v0 += __shfl_xor_sync(0xffffffffu, v0, 2);
        v1 += __shfl_xor_sync(0xffffffffu, v1, 1); v1 += __shfl_xor_sync(0xffffffffu, v1, 2);
        const int r0 = half * 64 + w * 16 + g;
        mbar_wait(BAR(B_EPOCH), 0);
        const unsigned ep1 = lds32(sb + SM_MISC + 4 * M_EPOCH) + 1;
        if (threadIdx.x == 0) TS(67);
        if (t4 < 2) {
          const float m = t4 ? m1 : m0, v = t4 ? v1 : v0;
          asm volatile("st.relaxed.gpu.global.v2.b64 [%0], {%1, %2};" ::"l"(&g_lnstat[(ai * 8 + aj) * 128 + r0 + 8 * t4]),
                       "l"(((unsigned long long)ep1 << 32) | __float_as_uint(m)), "l"(((unsigned long long)ep1 << 32) | __float_as_uint(v)) : "memory");
        }
        float sm[4], sv[4];
        const uint4* lp = &g_lnstat[(ai * 8 + 2 * t4) * 128 + r0];
#pragma unroll 1
        for (int n = 0; n < SPIN_LIMIT; n++) {
          bool ok = true;
#pragma unroll
          for (int e = 0; e < 4; e++) {
            unsigned long long a, b;
            asm volatile("ld.relaxed.gpu.global.v2.b64 {%0, %1}, [%2];" : "=l"(a), "=l"(b) : "l"(lp + (e >> 1) * 128 + (e & 1) * 8) : "memory");
            ok = ok && (uint32_t)(a >> 32) == ep1 && (uint32_t)(b >> 32) == ep1;
            sm[e] = __uint_as_float((uint32_t)a); sv[e] = __uint_as_float((uint32_t)b);
          }
          if (__all_sync(0xffffffffu, ok)) break;
          __nanosleep(150);
        }
        if (threadIdx.x == 0) TS(68);
        const float na = t4 == 0 ? 80.f : (t4 == 3 ? 64.f : 96.f), nb = t4 == 3 ? 64.f : 96.f;
#pragma unroll
        for (int r = 0; r < 2; r++) {
          float t = fmaf(sm[r], na, sm[2 + r] * nb);
          t += __shfl_xor_sync(0xffffffffu, t, 1); t += __shfl_xor_sync(0xffffffffu, t, 2);
          const float mu = t * (1.f / 688.f);
          const float da = sm[r] - mu, db = sm[2 + r] - mu;
          float m2 = sv[r] + sv[2 + r] + na * da * da + nb * db * db;
          m2 += __shfl_xor_sync(0xffffffffu, m2, 1); m2 += __shfl_xor_sync(0xffffffffu, m2, 2);
          const float rs = rsqrtf(fmaf(m2, 1.f / 688.f, 1e-5f)), sh = -mu * rs;
#pragma unroll
          for (int k = 2 * r; k < 48; k += 4) { acc[k] = fmaf(acc[k], rs, sh); acc[k + 1] = fmaf(acc[k + 1], rs, sh); }
        }
        if (aj == 7) {
          c_hi = 10;
#pragma unroll
          for (int k = 32; k < 40; k++) acc[k] = 0.f;
        }
      }
      uint32_t* zp = wg < 2 ? reinterpret_cast<uint32_t*>(g_z2n) + (ai * 2 + half) * 2816 + w * 704
                            : reinterpret_cast<uint32_t*>(g_z1) + (ai * 88 * 16 + half * 8 + w * 2) * 32;
      const int mul = wg < 2 ? 373 : 0, cstr = wg < 2 ? 32 : 512, rstr = wg < 2 ? 352 : 32;
      auto zoff = [&](int c8) { const int fb = fb0 + c8; return ((fb * mul) >> 12) * (32 * 2816 - 352) + fb * cstr; };
#pragma unroll
      for (int c8 = 0; c8 < 12; c8++) {
        uint32_t* p = zp + zoff(c8) + lane;
        if (c8 >= c_lo && c8 < c_hi) { p[0] = pack_bf16(acc[4 * c8], acc[4 * c8 + 1]); p[rstr] = pack_bf16(acc[4 * c8 + 2], acc[4 * c8 + 3]); }
      }
      if (tid == 0) TS(wg == 0 ? 69 : 78 + wg);
      uint32_t chk = 0;
#pragma unroll
      for (int r = 0; r < 3; r++) {
        const int it = lane + 32 * r, c8 = it >> 3;
        if (c8 >= c_lo && c8 < c_hi) chk ^= ld_back(zp + zoff(c8) + ((it >> 2) & 1) * rstr + (it & 3) * 8);
      }
      if (wg == 3 && aj == 0) chk ^= ld_back(&g_gate[ai * 128 + (tid >> 3) + 16 * (tid & 7)]);
      consume(chk, sb);
      fence_async();
      bar_sync(1 + wg, 128);
      if (tid == 0) { red_relaxed(wg < 2 ? &g_zcnt[(ai * 2 + half) * 32] : &g_z1cnt[ai * 32]); TS(wg < 2 ? 20 + wg : 8 + wg * wg); }
      if (!pass) finish_q();
    }
    if (wg == 3) {
      asm volatile("setmaxnreg.inc.sync.aligned.u32 120;");
      int st = 0, ph = 0;
      {
        float acc[88];
#pragma unroll
        for (int k = 0; k < 88; k++) acc[k] = 0.f;
        regfence(acc);
#pragma unroll 1
        for (int n = 0; n < 32; n++) {
          mbar_wait(BAR(B_RFULL + st), ph);
          const uint64_t da = mkdesc(sb + SM_RING + st * RSTAGE, 16, 1024, 1);
          const uint64_t db = mkdesc(sb + SM_RING + st * RSTAGE + 16384, 1408, 128, 0);
#pragma unroll
          for (int k = 0; k < 4; k++) {
            wg_fence();
            wg_ss_n88<0, 88>(acc, da + 2 * k, db + 176 * k);
            wg_ss_n88<44, 88>(acc, da + 512 + 2 * k, db + 176 * k);
            wg_commit();
            wg_wait<0>();
          }
          if (tid == 0) mbar_arrive_both(BAR(B_REMPTY + st));
          if (++st == 3) { st = 0; ph ^= 1; }
        }
        regfence(acc);
        if (tid == 0) TS(11);
        mbar_wait(BAR(B_Z1OK), 0);
        const uint32_t* z1p = reinterpret_cast<const uint32_t*>(g_z1) + ((bi * 88 + bj * 11) * 16 + w * 2) * 32 + lane;
        uint32_t* up = reinterpret_cast<uint32_t*>(g_u) + bi * 11 * 4096 + w * 512 + lane;
#pragma unroll
        for (int r = 0; r < 4; r++) {
          const int row = bi * 128 + (r >> 1) * 64 + w * 16 + (r & 1) * 8 + g;
          const float og = 1.f - __ldcg(&g_gate[row]), bs = __bfloat162float(prm.b_sp[row]) * og;
          uint32_t zz[11];
#pragma unroll
          for (int c8 = 0; c8 < 11; c8++) zz[c8] = __ldcg(z1p + c8 * 512 + ((r >> 1) * 8 + (r & 1)) * 32);
          if (bj == 7) zz[9] = zz[10] = 0;
#pragma unroll
          for (int c8 = 0; c8 < 11; c8++) {
            const int k = (r >> 1) * 44 + c8 * 4 + (r & 1) * 2, cb = 11 * bj + c8;
            uint32_t v = pack_bf16(fmaf(acc[k], og, bs), fmaf(acc[k + 1], og, bs));
            asm("mul.rn.bf16x2 %0, %0, %1;" : "+r"(v) : "r"(zz[c8]));
            up[cb * 32 + (cb >> 3) * 3840 + ((r >> 1) * 8 + (r & 1)) * 256] = v;
          }
        }
        fence_async();
        bar_sync(4, 128);
        if (tid == 0) { red_release(&g_ucnt[bi * 32]); TS(12); }
      }
      float oc[64];
#pragma unroll
      for (int k = 0; k < 64; k++) oc[k] = 0.f;
      regfence(oc);
#pragma unroll 1
      for (int n = 0; n < 19; n++) {
        uint32_t sa, sw;
        if (n < 11) { mbar_wait(BAR(B_RFULL + st), ph); sa = SM_RING + st * RSTAGE; sw = sa + 16384; }
        else {
          if (n == 11) { if (tid == 0) TS(13); mbar_wait(BAR(B_WOFULL), 0); }
          mbar_wait(BAR(B_OFULL + n - 11), 0); sa = SM_K + (n - 11) * 16384; sw = SM_RING + (n - 11) * 8192;
        }
        const uint64_t da = mkdesc(sb + sa, 128, 1024, 0), db = mkdesc(sb + sw, 8192, 1024, 1);
#pragma unroll
        for (int k = 0; k < 4; k += 2) {
          wg_fence();
          wg_ss_n64<0, 64>(oc, da + 16 * k, db + 128 * k);
          wg_ss_n64<32, 64>(oc, da + 512 + 16 * k, db + 128 * k);
          wg_ss_n64<0, 64>(oc, da + 16 * k + 16, db + 128 * k + 128);
          wg_ss_n64<32, 64>(oc, da + 528 + 16 * k, db + 128 * k + 128);
          wg_commit();
          if (n < 11) wg_wait<0>();
        }
        if (n < 11) {
          if (tid == 0) mbar_arrive_both(BAR(B_REMPTY + st));
          if (++st == 3) { st = 0; ph ^= 1; }
        }
      }
      wg_wait<0>();
      regfence(oc);
      if (tid == 0) TS(14);
      uint32_t* op = reinterpret_cast<uint32_t*>(prm.out) + (bi * 128 + w * 16 + g) * 256 + bj * 32 + t4;
#pragma unroll
      for (int k = 0; k < 64; k += 2) {
        const int hf = k / 32, c8 = (k % 32) / 4, r8 = (k >> 1) & 1;
        op[(hf * 64 + r8 * 8) * 256 + c8 * 4] = pack_bf16(oc[k], oc[k + 1]);
      }
      if (tid == 0) TS(15);
    } else {
      mbar_wait(BAR(B_QRDY), 0);
    if (tid == 0) TS(25 + wg);
#pragma unroll 1
    for (int c = 0; c < 8; c++) mbar_wait(BAR(B_KVFULL + c), 0);
    if (tid == 0) TS(28 + wg);
    const uint64_t dk0 = mkdesc(sb + SM_K, 128, 256, 0);
    const uint64_t dv0 = mkdesc(sb + SM_ONES - 256, 128, 256, 0);
    const uint64_t vstep = prm.vstep;
    const int aw = wg == 0 ? 0 : 3 - wg;
    uint32_t chk = 0;
    float o[12], s[32];
    uint32_t q[4], p0[16], p1[16];
    if (lds32(sb + SM_MISC + 4 * M_FAST)) {
      const uint32_t mlo = prm.mlo, mhi = prm.mhi;
      uint64_t dk = dk0, dv = dv0;
#define STEP(PIN, POUT) { wg_fence(); issue_qk(s, q, dk); dk += 128; wg_commit(); issue_pv(o, PIN, dv, vstep); wg_commit(); \
                          wg_wait<1>(); regfence(s); softmax_step(s, POUT, mlo, mhi); wg_wait<0>(); }
#pragma unroll 1
      for (int sg = aw * 8; sg < aw * 8 + 8; sg++) {
        const int tau = sg / 3, seg = sg - tau * 3;
        int n2 = seg == 1 ? 6 : 5;
#pragma unroll
        for (int k = 0; k < NP / 2; k++) s[k] = MAGIC_C;
        if (sg == aw * 8 || seg == 0) {
          const int j0 = seg == 0 ? 0 : (seg == 1 ? 10 : 22);
          dk = dk0 + 128 * j0;
          dv = dv0 + VSTEP * (4 * j0);
          const uint4 qv = lds128(sb + SM_Q + tau * 2048 + tid * 16);
          q[0] = qv.x; q[1] = qv.y; q[2] = qv.z; q[3] = qv.w;
#pragma unroll
          for (int k = 0; k < 12; k++) o[k] = 0.f;
          regfence(o); regfence(s);
          wg_fence(); issue_qk(s, q, dk); dk += 128; wg_commit();
          wg_wait<0>(); regfence(s);
          softmax_step(s, p0, mlo, mhi);
          STEP(p0, p1);
          n2--;
        }
        regfence(s);
#pragma unroll 1
        for (; n2 > 0; n2--) { STEP(p1, p0); STEP(p0, p1); }
        if (sg == aw * 8 + 7 || seg == 2) {
          wg_fence(); issue_pv(o, p1, dv, vstep); wg_commit();
          wg_wait<0>(); regfence(o);
          if (sg == 8 || sg == 17) {
            float4* pp = g_part + (blockIdx.x * 2 + (aw - 1)) * 384 + tid;
            pp[0] = make_float4(o[0], o[1], o[2], o[3]); pp[128] = make_float4(o[4], o[5], o[6], o[7]); pp[256] = make_float4(o[8], o[9], o[10], o[11]);
            __threadfence_block();
            bar_arrive(5 + aw, 256);
          } else {
            if (sg == 7 || sg == 15) {
              bar_sync(6 + aw, 256);
              const float4* pp = g_part + (blockIdx.x * 2 + aw) * 384 + tid;
              const float4 a = pp[0], b = pp[128], c = pp[256];
              o[0] += a.x; o[1] += a.y; o[2] += a.z; o[3] += a.w; o[4] += b.x; o[6] += b.z; o[8] += c.x; o[9] += c.y; o[10] += c.z; o[11] += c.w;
            }
            chk ^= store_o_tile(o, ai, aj, tau, tid, sb);
          }
        }
      }
#undef STEP
    } else {
      mbar_wait(BAR(B_KFB), 0);
      constexpr float SC = 0.25f * 1.4426950408889634f;
#pragma unroll 1
      for (int tau = wg * 3; tau < wg * 3 + 3 && tau < 8; tau++) {
        const uint4 qv = lds128(sb + SM_Q + tau * 2048 + tid * 16);
        float m0 = -INFINITY, m1 = -INFINITY;
#pragma unroll
        for (int k = 0; k < 12; k++) o[k] = 0.f;
        uint64_t dv = dv0;
#pragma unroll 1
        for (int j = 0; j < 32; j++) {
          regfence(s);
          wg_fence(); wg_qkb_n64<0, 0, 32>(s, qv.x, qv.y, qv.z, qv.w, dk0 + 128 * j); wg_commit();
          wg_wait<0>(); regfence(s);
          float x0 = m0, x1 = m1;
#pragma unroll
          for (int k = 0; k < 32; k++) { s[k] *= SC; if (k & 2) x1 = fmaxf(x1, s[k]); else x0 = fmaxf(x0, s[k]); }
          x0 = fmaxf(x0, __shfl_xor_sync(0xffffffffu, x0, 1)); x0 = fmaxf(x0, __shfl_xor_sync(0xffffffffu, x0, 2));
          x1 = fmaxf(x1, __shfl_xor_sync(0xffffffffu, x1, 1)); x1 = fmaxf(x1, __shfl_xor_sync(0xffffffffu, x1, 2));
          const float c0 = ex2(m0 - x0), c1 = ex2(m1 - x1);
          m0 = x0; m1 = x1;
#pragma unroll
          for (int k = 0; k < 12; k++) o[k] *= (k & 2) ? c1 : c0;
#pragma unroll
          for (int k = 0; k < 16; k++) { const float m = (k & 1) ? m1 : m0; p0[k] = exp_mufu(s[2 * k] - m, s[2 * k + 1] - m); }
          regfence(o);
          wg_fence(); issue_pv(o, p0, dv, vstep); wg_commit();
          wg_wait<0>(); regfence(o);
        }
        chk ^= store_o_tile(o, ai, aj, tau, tid, sb);
      }
    }
    consume(chk, sb);
    fence_async();
    bar_sync(1 + wg, 128);
    if (tid == 0) { red_relaxed(&g_ocnt[ai * 32]); mbar_arrive_both(BAR(B_ATT)); TS(31 + wg); }
    }
  }
  __syncwarp();
  asm volatile("barrier.cluster.arrive.relaxed;" ::: "memory");
  asm volatile("barrier.cluster.wait;" ::: "memory");
}

typedef CUresult (*EncodeFn)(CUtensorMap*, CUtensorMapDataType, cuuint32_t, void*, const cuuint64_t*, const cuuint64_t*,
                             const cuuint32_t*, const cuuint32_t*, CUtensorMapInterleave, CUtensorMapSwizzle,
                             CUtensorMapL2promotion, CUtensorMapFloatOOBfill);

void make_map(EncodeFn enc, CUtensorMap* tm, const void* base, uint64_t cols, uint64_t rows, uint32_t bc, uint32_t br, CUtensorMapSwizzle sw) {
  cuuint64_t gd[2] = {cols, rows};
  cuuint64_t gs[1] = {cols * 2};
  cuuint32_t bd[2] = {bc, br};
  cuuint32_t es[2] = {1, 1};
  enc(tm, CU_TENSOR_MAP_DATA_TYPE_BFLOAT16, 2, const_cast<void*>(base), gd, gs, bd, es, CU_TENSOR_MAP_INTERLEAVE_NONE, sw,
      CU_TENSOR_MAP_L2_PROMOTION_L2_128B, CU_TENSOR_MAP_FLOAT_OOB_FILL_NONE);
}

}

extern "C" void kernel_launch(void* const* d_in, const int* in_sizes, int n_in, void* d_out, int out_size) {
  (void)in_sizes; (void)n_in; (void)out_size;
  static EncodeFn enc = nullptr;
  if (!enc) {
    void* fn = nullptr;
    cudaDriverEntryPointQueryResult qr;
    cudaGetDriverEntryPoint("cuTensorMapEncodeTiled", &fn, cudaEnableDefault, &qr);
    enc = (EncodeFn)fn;
    cudaFuncSetAttribute(fused_kernel, cudaFuncAttributeMaxDynamicSharedMemorySize, SMEM_BYTES);
  }
  CUtensorMap tx, tq, tin, tsp, tout, to;
  make_map(enc, &tx, d_in[0], 512, 2048, 64, 128, CU_TENSOR_MAP_SWIZZLE_128B);
  make_map(enc, &tq, d_in[1], 512, 512, 32, 32, CU_TENSOR_MAP_SWIZZLE_64B);
  make_map(enc, &to, d_in[4], 512, 512, 64, 64, CU_TENSOR_MAP_SWIZZLE_128B);
  make_map(enc, &tin, d_in[6], 1376, 512, 32, 32, CU_TENSOR_MAP_SWIZZLE_64B);
  make_map(enc, &tsp, d_in[7], 2048, 2048, 64, 64, CU_TENSOR_MAP_SWIZZLE_128B);
  make_map(enc, &tout, d_in[9], 512, 688, 64, 64, CU_TENSOR_MAP_SWIZZLE_128B);
  Params prm;
  prm.gate_w = (const __nv_bfloat16*)d_in[10];
  prm.b_sp = (const __nv_bfloat16*)d_in[8];
  prm.w_out = (const __nv_bfloat16*)d_in[9];
  prm.wo = (const __nv_bfloat16*)d_in[4];
  prm.w_in = (const __nv_bfloat16*)d_in[6];
  prm.wq = (const __nv_bfloat16*)d_in[1];
  prm.wk = (const __nv_bfloat16*)d_in[2];
  prm.wv = (const __nv_bfloat16*)d_in[3];
  prm.vstep = VSTEP;
  prm.mlo = 0x007F007Fu;
  prm.mhi = 0xFF80FF80u;
  prm.out = (__nv_bfloat16*)d_out;
  fused_kernel<<<NCTA, NTHREADS, SMEM_BYTES>>>(tx, tq, tin, tsp, tout, to, prm);
}
```

```cpp
#include <cuda_runtime.h>
#include <cuda.h>
#include <cuda_bf16.h>
#include <cuda_fp16.h>
#include <stdint.h>

namespace {

constexpr int NCTA = 128;
constexpr int NTHREADS = 640;
constexpr int NP = 40;
constexpr int NM = 64 - NP;
constexpr int SPIN_LIMIT = 1 << 18;

constexpr uint32_t SM_K = 0;
constexpr uint32_t SM_V = 65536;
constexpr uint32_t SM_ONES = 131072;
constexpr uint32_t KV_BYTES = 131072;
constexpr uint32_t SM_BAR = 131584;
constexpr uint32_t SM_RING = 132096;
constexpr uint32_t RSTAGE = 27648;
constexpr uint32_t WSLOT = 16384;
constexpr uint32_t SM_WKV = SM_RING + 4 * WSLOT;
constexpr uint32_t SM_GW = SM_WKV + 16384;
constexpr uint32_t SM_Q = 215040;
constexpr uint32_t SM_G = 231424;
constexpr uint32_t SM_MISC = 231936;
constexpr uint32_t SMEM_BYTES = 232448;

constexpr int B_XFULL = 0, B_XEMPTY = 8, B_WFULL = 16, B_WEMPTY = 32, B_RFULL = 44, B_REMPTY = 47, B_KVFULL = 50,
              B_KFB = 51, B_KSTAT = 52, B_DEC = 53, B_WOFULL = 54, B_EPOCH = 55, B_ZOK = 56, B_Z1OK = 57, B_ATT = 58, B_QRDY = 59;
constexpr int M_EPOCH = 0, M_KN2 = 1, M_VOK = 2, M_FAST = 3, M_KVR = 4, M_RED = 16;

__device__ uint4 g_kimg[KV_BYTES / 16];
__device__ uint4 g_kbf[65536 / 16];
__device__ unsigned long long g_kvflag[NCTA];
__device__ uint4 g_lnstat[16 * 8 * 128];
__device__ float g_gate[2048];
__device__ uint4 g_z2n[8 * 32 * 11264 / 16];
__device__ uint4 g_z1[16 * 88 * 128];
__device__ uint4 g_u[16 * 11 * 1024];
__device__ uint4 g_o[16 * 8 * 1024];
__device__ float4 g_part[NCTA * 2 * 3 * 128];
__device__ unsigned g_ticket;
__device__ unsigned g_zcnt[32 * 32];
__device__ unsigned g_z1cnt[16 * 32];
__device__ unsigned g_ucnt[16 * 32];
__device__ unsigned g_ocnt[16 * 32];
#define TS(k) do { } while (0)

__device__ __forceinline__ void mbar_init(uint32_t a, uint32_t c) { asm volatile("mbarrier.init.shared::cta.b64 [%0], %1;" ::"r"(a), "r"(c) : "memory"); }
__device__ __forceinline__ void mbar_expect(uint32_t a, uint32_t b) { asm volatile("mbarrier.arrive.expect_tx.shared::cta.b64 _, [%0], %1;" ::"r"(a), "r"(b) : "memory"); }
__device__ __forceinline__ void mbar_arrive(uint32_t a) { asm volatile("mbarrier.arrive.shared::cta.b64 _, [%0];" ::"r"(a) : "memory"); }
__device__ __forceinline__ void mbar_arrive_both(uint32_t a) {
  asm volatile("{\n.reg .b32 ra;\nmapa.shared::cluster.u32 ra, %0, 0;\nmbarrier.arrive.shared::cluster.b64 _, [ra];\n"
               "mapa.shared::cluster.u32 ra, %0, 1;\nmbarrier.arrive.shared::cluster.b64 _, [ra];\n}" ::"r"(a) : "memory");
}
__device__ __forceinline__ void mbar_wait(uint32_t a, uint32_t ph) {
  uint32_t ok;
#pragma unroll 1
  for (int n = 0; n < SPIN_LIMIT; n++) {
    asm volatile("{\n.reg .pred p;\nmbarrier.try_wait.parity.shared::cta.b64 p, [%1], %2;\nselp.u32 %0, 1, 0, p;\n}" : "=r"(ok) : "r"(a), "r"(ph) : "memory");
    if (ok) break;
  }
}
__device__ __forceinline__ void tma2d(uint32_t dst, const CUtensorMap* tm, int c0, int c1, uint32_t bar) {
  asm volatile("cp.async.bulk.tensor.2d.shared::cluster.global.mbarrier::complete_tx::bytes [%0], [%1, {%3, %4}], [%2];"
               ::"r"(dst), "l"(tm), "r"(bar), "r"(c0), "r"(c1) : "memory");
}
__device__ __forceinline__ void tma2d_mc(uint32_t dst, const CUtensorMap* tm, int c0, int c1, uint32_t bar) {
  asm volatile("cp.async.bulk.tensor.2d.shared::cluster.global.mbarrier::complete_tx::bytes.multicast::cluster [%0], [%1, {%3, %4}], [%2], %5;"
               ::"r"(dst), "l"(tm), "r"(bar), "r"(c0), "r"(c1), "h"((uint16_t)3) : "memory");
}
__device__ __forceinline__ void tma2d_pf(const CUtensorMap* tm, int c0, int c1) {
  asm volatile("cp.async.bulk.prefetch.tensor.2d.L2.global [%0, {%1, %2}];" ::"l"(tm), "r"(c0), "r"(c1) : "memory");
}
__device__ __forceinline__ void bulk(uint32_t dst, const void* src, uint32_t bytes, uint32_t bar) {
  asm volatile("cp.async.bulk.shared::cluster.global.mbarrier::complete_tx::bytes [%0], [%1], %2, [%3];"
               ::"r"(dst), "l"(src), "r"(bytes), "r"(bar) : "memory");
}
__device__ __forceinline__ void bulk_mc(uint32_t dst, const void* src, uint32_t bytes, uint32_t bar) {
  asm volatile("cp.async.bulk.shared::cluster.global.mbarrier::complete_tx::bytes.multicast::cluster [%0], [%1], %2, [%3], %4;"
               ::"r"(dst), "l"(src), "r"(bytes), "r"(bar), "h"((uint16_t)3) : "memory");
}
__device__ __forceinline__ void l2_prefetch(const void* src, uint32_t bytes) { asm volatile("cp.async.bulk.prefetch.L2.global [%0], %1;" ::"l"(src), "r"(bytes) : "memory"); }
__device__ __forceinline__ void fence_async() { asm volatile("fence.proxy.async.global;" ::: "memory"); }
__device__ __forceinline__ void fence_async_smem() { asm volatile("fence.proxy.async.shared::cta;" ::: "memory"); }
__device__ __forceinline__ void bar_sync(int id, int n) { asm volatile("bar.sync %0, %1;" ::"r"(id), "r"(n) : "memory"); }
__device__ __forceinline__ void bar_arrive(int id, int n) { asm volatile("bar.arrive %0, %1;" ::"r"(id), "r"(n) : "memory"); }
__device__ __forceinline__ void red_release(unsigned* p) { asm volatile("red.release.gpu.global.add.u32 [%0], 1;" ::"l"(p) : "memory"); }
__device__ __forceinline__ void red_relaxed(unsigned* p) { asm volatile("red.relaxed.gpu.global.add.u32 [%0], 1;" ::"l"(p) : "memory"); }
__device__ __forceinline__ uint32_t ld_back(const void* p) { uint32_t v; asm volatile("ld.relaxed.gpu.global.u32 %0, [%1];" : "=r"(v) : "l"(p) : "memory"); return v; }
__device__ __forceinline__ void consume(uint32_t v, uint32_t sb) { if (v == 0xDEADBEEFu) asm volatile("st.shared.u32 [%0], %1;" ::"r"(sb + SM_MISC + 60), "r"(v) : "memory"); }
__device__ __forceinline__ unsigned ld_acquire(const unsigned* p) { unsigned v; asm volatile("ld.acquire.gpu.global.u32 %0, [%1];" : "=r"(v) : "l"(p) : "memory"); return v; }
__device__ __forceinline__ void wait_ge(const unsigned* p, unsigned target) {
#pragma unroll 1
  for (int n = 0; n < SPIN_LIMIT; n++) {
    if ((int)(ld_acquire(p) - target) >= 0) break;
    __nanosleep(100);
  }
}
__device__ __forceinline__ void wg_fence() { asm volatile("wgmma.fence.sync.aligned;" ::: "memory"); }
__device__ __forceinline__ void wg_commit() { asm volatile("wgmma.commit_group.sync.aligned;" ::: "memory"); }
template <int N> __device__ __forceinline__ void wg_wait() { asm volatile("wgmma.wait_group.sync.aligned %0;" ::"n"(N) : "memory"); }
template <int n> __device__ __forceinline__ void regfence(float (&d)[n]) {
#pragma unroll
  for (int i = 0; i < n; i++) asm volatile("" : "+f"(d[i])::"memory");
}
__device__ __forceinline__ uint64_t mkdesc(uint32_t addr, uint32_t lbo, uint32_t sbo, int swz) {
  return (uint64_t)((addr & 0x3FFFF) >> 4) | ((uint64_t)(lbo >> 4) << 16) | ((uint64_t)(sbo >> 4) << 32) | ((uint64_t)swz << 62);
}
__device__ __forceinline__ uint32_t pack_bf16(float lo, float hi) { uint32_t r; asm("cvt.rn.bf16x2.f32 %0, %1, %2;" : "=r"(r) : "f"(hi), "f"(lo)); return r; }
__device__ __forceinline__ uint32_t pack_f16(float lo, float hi) { uint32_t r; asm("cvt.rn.f16x2.f32 %0, %1, %2;" : "=r"(r) : "f"(hi), "f"(lo)); return r; }
__device__ __forceinline__ float bf_lo(uint32_t v) { return __uint_as_float(v << 16); }
__device__ __forceinline__ float bf_hi(uint32_t v) { return __uint_as_float(v & 0xFFFF0000u); }
__device__ __forceinline__ float ex2(float x) { float r; asm("ex2.approx.ftz.f32 %0, %1;" : "=f"(r) : "f"(x)); return r; }
__device__ __forceinline__ float gelu_tanh(float x) {
  float u = x * fmaf(x * x, 0.0356774081f, 0.7978845608f), t;
  asm("tanh.approx.f32 %0, %1;" : "=f"(t) : "f"(u));
  float h = 0.5f * x;
  return fmaf(h, t, h);
}
__device__ __forceinline__ void sts32(uint32_t a, uint32_t v) { asm volatile("st.shared.u32 [%0], %1;" ::"r"(a), "r"(v) : "memory"); }
__device__ __forceinline__ void sts16(uint32_t a, uint16_t v) { asm volatile("st.shared.u16 [%0], %1;" ::"r"(a), "h"(v) : "memory"); }
__device__ __forceinline__ void sts128(uint32_t a, uint32_t x, uint32_t y, uint32_t z, uint32_t w) { asm volatile("st.shared.v4.u32 [%0], {%1,%2,%3,%4};" ::"r"(a), "r"(x), "r"(y), "r"(z), "r"(w) : "memory"); }
__device__ __forceinline__ uint32_t lds32(uint32_t a) { uint32_t v; asm volatile("ld.shared.u32 %0, [%1];" : "=r"(v) : "r"(a) : "memory"); return v; }
__device__ __forceinline__ float ldsf(uint32_t a) { return __uint_as_float(lds32(a)); }
__device__ __forceinline__ uint4 lds128(uint32_t a) { uint4 v; asm volatile("ld.shared.v4.u32 {%0,%1,%2,%3}, [%4];" : "=r"(v.x), "=r"(v.y), "=r"(v.z), "=r"(v.w) : "r"(a) : "memory"); return v; }

template<int OFF, int TOT> __device__ __forceinline__ void wg_ss_n88(float (&d)[TOT], uint64_t da, uint64_t db) {
  asm volatile("wgmma.mma_async.sync.aligned.m64n88k16.f32.bf16.bf16 {%0, %1, %2, %3, %4, %5, %6, %7, %8, %9, %10, %11, %12, %13, %14, %15, %16, %17, %18, %19, %20, %21, %22, %23, %24, %25, %26, %27, %28, %29, %30, %31, %32, %33, %34, %35, %36, %37, %38, %39, %40, %41, %42, %43}, %44, %45, 1, 1, 1, 0, 1;"
    : "+f"(d[OFF+0]), "+f"(d[OFF+1]), "+f"(d[OFF+2]), "+f"(d[OFF+3]), "+f"(d[OFF+4]), "+f"(d[OFF+5]), "+f"(d[OFF+6]), "+f"(d[OFF+7]),
      "+f"(d[OFF+8]), "+f"(d[OFF+9]), "+f"(d[OFF+10]), "+f"(d[OFF+11]), "+f"(d[OFF+12]), "+f"(d[OFF+13]), "+f"(d[OFF+14]), "+f"(d[OFF+15]),
      "+f"(d[OFF+16]), "+f"(d[OFF+17]), "+f"(d[OFF+18]), "+f"(d[OFF+19]), "+f"(d[OFF+20]), "+f"(d[OFF+21]), "+f"(d[OFF+22]), "+f"(d[OFF+23]),
      "+f"(d[OFF+24]), "+f"(d[OFF+25]), "+f"(d[OFF+26]), "+f"(d[OFF+27]), "+f"(d[OFF+28]), "+f"(d[OFF+29]), "+f"(d[OFF+30]), "+f"(d[OFF+31]),
      "+f"(d[OFF+32]), "+f"(d[OFF+33]), "+f"(d[OFF+34]), "+f"(d[OFF+35]), "+f"(d[OFF+36]), "+f"(d[OFF+37]), "+f"(d[OFF+38]), "+f"(d[OFF+39]),
      "+f"(d[OFF+40]), "+f"(d[OFF+41]), "+f"(d[OFF+42]), "+f"(d[OFF+43])
    : "l"(da), "l"(db));
}
template<int OFF, int TOT> __device__ __forceinline__ void wg_ss_n128(float (&d)[TOT], uint64_t da, uint64_t db) {
  asm volatile("wgmma.mma_async.sync.aligned.m64n128k16.f32.bf16.bf16 {%0, %1, %2, %3, %4, %5, %6, %7, %8, %9, %10, %11, %12, %13, %14, %15, %16, %17, %18, %19, %20, %21, %22, %23, %24, %25, %26, %27, %28, %29, %30, %31, %32, %33, %34, %35, %36, %37, %38, %39, %40, %41, %42, %43, %44, %45, %46, %47, %48, %49, %50, %51, %52, %53, %54, %55, %56, %57, %58, %59, %60, %61, %62, %63}, %64, %65, 1, 1, 1, 0, 1;"
    : "+f"(d[OFF+0]), "+f"(d[OFF+1]), "+f"(d[OFF+2]), "+f"(d[OFF+3]), "+f"(d[OFF+4]), "+f"(d[OFF+5]), "+f"(d[OFF+6]), "+f"(d[OFF+7]),
      "+f"(d[OFF+8]), "+f"(d[OFF+9]), "+f"(d[OFF+10]), "+f"(d[OFF+11]), "+f"(d[OFF+12]), "+f"(d[OFF+13]), "+f"(d[OFF+14]), "+f"(d[OFF+15]),
      "+f"(d[OFF+16]), "+f"(d[OFF+17]), "+f"(d[OFF+18]), "+f"(d[OFF+19]), "+f"(d[OFF+20]), "+f"(d[OFF+21]), "+f"(d[OFF+22]), "+f"(d[OFF+23]),
      "+f"(d[OFF+24]), "+f"(d[OFF+25]), "+f"(d[OFF+26]), "+f"(d[OFF+27]), "+f"(d[OFF+28]), "+f"(d[OFF+29]), "+f"(d[OFF+30]), "+f"(d[OFF+31]),
      "+f"(d[OFF+32]), "+f"(d[OFF+33]), "+f"(d[OFF+34]), "+f"(d[OFF+35]), "+f"(d[OFF+36]), "+f"(d[OFF+37]), "+f"(d[OFF+38]), "+f"(d[OFF+39]),
      "+f"(d[OFF+40]), "+f"(d[OFF+41]), "+f"(d[OFF+42]), "+f"(d[OFF+43]), "+f"(d[OFF+44]), "+f"(d[OFF+45]), "+f"(d[OFF+46]), "+f"(d[OFF+47]),
      "+f"(d[OFF+48]), "+f"(d[OFF+49]), "+f"(d[OFF+50]), "+f"(d[OFF+51]), "+f"(d[OFF+52]), "+f"(d[OFF+53]), "+f"(d[OFF+54]), "+f"(d[OFF+55]),
      "+f"(d[OFF+56]), "+f"(d[OFF+57]), "+f"(d[OFF+58]), "+f"(d[OFF+59]), "+f"(d[OFF+60]), "+f"(d[OFF+61]), "+f"(d[OFF+62]), "+f"(d[OFF+63])
    : "l"(da), "l"(db));
}
template<int OFF, int TOT> __device__ __forceinline__ void wg_ss_n64(float (&d)[TOT], uint64_t da, uint64_t db) {
  asm volatile("wgmma.mma_async.sync.aligned.m64n64k16.f32.bf16.bf16 {%0, %1, %2, %3, %4, %5, %6, %7, %8, %9, %10, %11, %12, %13, %14, %15, %16, %17, %18, %19, %20, %21, %22, %23, %24, %25, %26, %27, %28, %29, %30, %31}, %32, %33, 1, 1, 1, 0, 1;"
    : "+f"(d[OFF+0]), "+f"(d[OFF+1]), "+f"(d[OFF+2]), "+f"(d[OFF+3]), "+f"(d[OFF+4]), "+f"(d[OFF+5]), "+f"(d[OFF+6]), "+f"(d[OFF+7]),
      "+f"(d[OFF+8]), "+f"(d[OFF+9]), "+f"(d[OFF+10]), "+f"(d[OFF+11]), "+f"(d[OFF+12]), "+f"(d[OFF+13]), "+f"(d[OFF+14]), "+f"(d[OFF+15]),
      "+f"(d[OFF+16]), "+f"(d[OFF+17]), "+f"(d[OFF+18]), "+f"(d[OFF+19]), "+f"(d[OFF+20]), "+f"(d[OFF+21]), "+f"(d[OFF+22]), "+f"(d[OFF+23]),
      "+f"(d[OFF+24]), "+f"(d[OFF+25]), "+f"(d[OFF+26]), "+f"(d[OFF+27]), "+f"(d[OFF+28]), "+f"(d[OFF+29]), "+f"(d[OFF+30]), "+f"(d[OFF+31])
    : "l"(da), "l"(db));
}
template<int OFF, int TOT> __device__ __forceinline__ void wg_ss_n32t(float (&d)[TOT], uint64_t da, uint64_t db) {
  asm volatile("wgmma.mma_async.sync.aligned.m64n32k16.f32.bf16.bf16 {%0, %1, %2, %3, %4, %5, %6, %7, %8, %9, %10, %11, %12, %13, %14, %15}, %16, %17, 1, 1, 1, 1, 0;"
    : "+f"(d[OFF+0]), "+f"(d[OFF+1]), "+f"(d[OFF+2]), "+f"(d[OFF+3]), "+f"(d[OFF+4]), "+f"(d[OFF+5]), "+f"(d[OFF+6]), "+f"(d[OFF+7]),
      "+f"(d[OFF+8]), "+f"(d[OFF+9]), "+f"(d[OFF+10]), "+f"(d[OFF+11]), "+f"(d[OFF+12]), "+f"(d[OFF+13]), "+f"(d[OFF+14]), "+f"(d[OFF+15])
    : "l"(da), "l"(db));
}
template<int SCD, int OFF, int TOT> __device__ __forceinline__ void wg_qk_n16(float (&d)[TOT], uint32_t a0, uint32_t a1, uint32_t a2, uint32_t a3, uint64_t db) {
  asm volatile("wgmma.mma_async.sync.aligned.m64n16k16.f32.f16.f16 {%0, %1, %2, %3, %4, %5, %6, %7}, {%8,%9,%10,%11}, %12, %13, 1, 1, 0;"
    : "+f"(d[OFF+0]), "+f"(d[OFF+1]), "+f"(d[OFF+2]), "+f"(d[OFF+3]), "+f"(d[OFF+4]), "+f"(d[OFF+5]), "+f"(d[OFF+6]), "+f"(d[OFF+7])
    : "r"(a0), "r"(a1), "r"(a2), "r"(a3), "l"(db), "n"(SCD));
}
template<int SCD, int OFF, int TOT> __device__ __forceinline__ void wg_qk_n24(float (&d)[TOT], uint32_t a0, uint32_t a1, uint32_t a2, uint32_t a3, uint64_t db) {
  asm volatile("wgmma.mma_async.sync.aligned.m64n24k16.f32.f16.f16 {%0, %1, %2, %3, %4, %5, %6, %7, %8, %9, %10, %11}, {%12,%13,%14,%15}, %16, %17, 1, 1, 0;"
    : "+f"(d[OFF+0]), "+f"(d[OFF+1]), "+f"(d[OFF+2]), "+f"(d[OFF+3]), "+f"(d[OFF+4]), "+f"(d[OFF+5]), "+f"(d[OFF+6]), "+f"(d[OFF+7]),
      "+f"(d[OFF+8]), "+f"(d[OFF+9]), "+f"(d[OFF+10]), "+f"(d[OFF+11])
    : "r"(a0), "r"(a1), "r"(a2), "r"(a3), "l"(db), "n"(SCD));
}
template<int SCD, int OFF, int TOT> __device__ __forceinline__ void wg_qk_n32(float (&d)[TOT], uint32_t a0, uint32_t a1, uint32_t a2, uint32_t a3, uint64_t db) {
  asm volatile("wgmma.mma_async.sync.aligned.m64n32k16.f32.f16.f16 {%0, %1, %2, %3, %4, %5, %6, %7, %8, %9, %10, %11, %12, %13, %14, %15}, {%16,%17,%18,%19}, %20, %21, 1, 1, 0;"
    : "+f"(d[OFF+0]), "+f"(d[OFF+1]), "+f"(d[OFF+2]), "+f"(d[OFF+3]), "+f"(d[OFF+4]), "+f"(d[OFF+5]), "+f"(d[OFF+6]), "+f"(d[OFF+7]),
      "+f"(d[OFF+8]), "+f"(d[OFF+9]), "+f"(d[OFF+10]), "+f"(d[OFF+11]), "+f"(d[OFF+12]), "+f"(d[OFF+13]), "+f"(d[OFF+14]), "+f"(d[OFF+15])
    : "r"(a0), "r"(a1), "r"(a2), "r"(a3), "l"(db), "n"(SCD));
}
template<int SCD, int OFF, int TOT> __device__ __forceinline__ void wg_qk_n40(float (&d)[TOT], uint32_t a0, uint32_t a1, uint32_t a2, uint32_t a3, uint64_t db) {
  asm volatile("wgmma.mma_async.sync.aligned.m64n40k16.f32.f16.f16 {%0, %1, %2, %3, %4, %5, %6, %7, %8, %9, %10, %11, %12, %13, %14, %15, %16, %17, %18, %19}, {%20,%21,%22,%23}, %24, %25, 1, 1, 0;"
    : "+f"(d[OFF+0]), "+f"(d[OFF+1]), "+f"(d[OFF+2]), "+f"(d[OFF+3]), "+f"(d[OFF+4]), "+f"(d[OFF+5]), "+f"(d[OFF+6]), "+f"(d[OFF+7]),
      "+f"(d[OFF+8]), "+f"(d[OFF+9]), "+f"(d[OFF+10]), "+f"(d[OFF+11]), "+f"(d[OFF+12]), "+f"(d[OFF+13]), "+f"(d[OFF+14]), "+f"(d[OFF+15]),
      "+f"(d[OFF+16]), "+f"(d[OFF+17]), "+f"(d[OFF+18]), "+f"(d[OFF+19])
    : "r"(a0), "r"(a1), "r"(a2), "r"(a3), "l"(db), "n"(SCD));
}
template<int SCD, int OFF, int TOT> __device__ __forceinline__ void wg_qk_n48(float (&d)[TOT], uint32_t a0, uint32_t a1, uint32_t a2, uint32_t a3, uint64_t db) {
  asm volatile("wgmma.mma_async.sync.aligned.m64n48k16.f32.f16.f16 {%0, %1, %2, %3, %4, %5, %6, %7, %8, %9, %10, %11, %12, %13, %14, %15, %16, %17, %18, %19, %20, %21, %22, %23}, {%24,%25,%26,%27}, %28, %29, 1, 1, 0;"
    : "+f"(d[OFF+0]), "+f"(d[OFF+1]), "+f"(d[OFF+2]), "+f"(d[OFF+3]), "+f"(d[OFF+4]), "+f"(d[OFF+5]), "+f"(d[OFF+6]), "+f"(d[OFF+7]),
      "+f"(d[OFF+8]), "+f"(d[OFF+9]), "+f"(d[OFF+10]), "+f"(d[OFF+11]), "+f"(d[OFF+12]), "+f"(d[OFF+13]), "+f"(d[OFF+14]), "+f"(d[OFF+15]),
      "+f"(d[OFF+16]), "+f"(d[OFF+17]), "+f"(d[OFF+18]), "+f"(d[OFF+19]), "+f"(d[OFF+20]), "+f"(d[OFF+21]), "+f"(d[OFF+22]), "+f"(d[OFF+23])
    : "r"(a0), "r"(a1), "r"(a2), "r"(a3), "l"(db), "n"(SCD));
}
template<int SCD, int OFF, int TOT> __device__ __forceinline__ void wg_pv_n24(float (&d)[TOT], uint32_t a0, uint32_t a1, uint32_t a2, uint32_t a3, uint64_t db) {
  asm volatile("wgmma.mma_async.sync.aligned.m64n24k16.f32.bf16.bf16 {%0, %1, %2, %3, %4, %5, %6, %7, %8, %9, %10, %11}, {%12,%13,%14,%15}, %16, %17, 1, 1, 1;"
    : "+f"(d[OFF+0]), "+f"(d[OFF+1]), "+f"(d[OFF+2]), "+f"(d[OFF+3]), "+f"(d[OFF+4]), "+f"(d[OFF+5]), "+f"(d[OFF+6]), "+f"(d[OFF+7]),
      "+f"(d[OFF+8]), "+f"(d[OFF+9]), "+f"(d[OFF+10]), "+f"(d[OFF+11])
    : "r"(a0), "r"(a1), "r"(a2), "r"(a3), "l"(db), "n"(SCD));
}
template<int SCD, int OFF, int TOT> __device__ __forceinline__ void wg_qkb_n64(float (&d)[TOT], uint32_t a0, uint32_t a1, uint32_t a2, uint32_t a3, uint64_t db) {
  asm volatile("wgmma.mma_async.sync.aligned.m64n64k16.f32.bf16.bf16 {%0, %1, %2, %3, %4, %5, %6, %7, %8, %9, %10, %11, %12, %13, %14, %15, %16, %17, %18, %19, %20, %21, %22, %23, %24, %25, %26, %27, %28, %29, %30, %31}, {%32,%33,%34,%35}, %36, %37, 1, 1, 0;"
    : "+f"(d[OFF+0]), "+f"(d[OFF+1]), "+f"(d[OFF+2]), "+f"(d[OFF+3]), "+f"(d[OFF+4]), "+f"(d[OFF+5]), "+f"(d[OFF+6]), "+f"(d[OFF+7]),
      "+f"(d[OFF+8]), "+f"(d[OFF+9]), "+f"(d[OFF+10]), "+f"(d[OFF+11]), "+f"(d[OFF+12]), "+f"(d[OFF+13]), "+f"(d[OFF+14]), "+f"(d[OFF+15]),
      "+f"(d[OFF+16]), "+f"(d[OFF+17]), "+f"(d[OFF+18]), "+f"(d[OFF+19]), "+f"(d[OFF+20]), "+f"(d[OFF+21]), "+f"(d[OFF+22]), "+f"(d[OFF+23]),
      "+f"(d[OFF+24]), "+f"(d[OFF+25]), "+f"(d[OFF+26]), "+f"(d[OFF+27]), "+f"(d[OFF+28]), "+f"(d[OFF+29]), "+f"(d[OFF+30]), "+f"(d[OFF+31])
    : "r"(a0), "r"(a1), "r"(a2), "r"(a3), "l"(db), "n"(SCD));
}
template<int N, int SCD, int OFF, int TOT> __device__ __forceinline__ void wg_qk(float (&d)[TOT], const uint32_t (&q)[4], uint64_t db) {
  if constexpr (N == 16) wg_qk_n16<SCD, OFF, TOT>(d, q[0], q[1], q[2], q[3], db);
  if constexpr (N == 24) wg_qk_n24<SCD, OFF, TOT>(d, q[0], q[1], q[2], q[3], db);
  if constexpr (N == 32) wg_qk_n32<SCD, OFF, TOT>(d, q[0], q[1], q[2], q[3], db);
  if constexpr (N == 40) wg_qk_n40<SCD, OFF, TOT>(d, q[0], q[1], q[2], q[3], db);
  if constexpr (N == 48) wg_qk_n48<SCD, OFF, TOT>(d, q[0], q[1], q[2], q[3], db);
}

__device__ __forceinline__ uint32_t exp_mufu(float a, float b) { return pack_bf16(ex2(a), ex2(b)); }
__device__ __forceinline__ uint32_t exp_poly(float a, float b, uint32_t mlo, uint32_t mhi) {
  uint32_t u = __byte_perm(__float_as_uint(a), __float_as_uint(b), 0x6521), mh, e, p;
  asm("lop3.b32 %0, %1, %2, 0x3F003F00, 0xEA;" : "=r"(mh) : "r"(u), "r"(mlo));
  asm("lop3.b32 %0, %1, %2, 0x00020002, 0xEA;" : "=r"(e) : "r"(u), "r"(mhi));
  asm("fma.rn.bf16x2 %0, %1, %2, %3;" : "=r"(p) : "r"(u), "r"(mh), "r"(e));
  return p;
}
constexpr float MAGIC_C = 48948.0625f;
constexpr float QSCALE = 0.25f * 1.4426950408889634f * 8.f;
constexpr float BOUND = 80.f;

__device__ __forceinline__ void softmax_step(const float (&s)[32], uint32_t (&p)[16], uint32_t mlo, uint32_t mhi) {
  constexpr int PP = NP / 4;
  int ip = 0, im = PP;
#pragma unroll
  for (int i = 0; i < 16; i++) {
    if (((i + 1) * PP / 16) > (i * PP / 16)) { p[ip] = exp_poly(s[2 * ip], s[2 * ip + 1], mlo, mhi); ip++; }
    else { p[im] = exp_mufu(s[2 * im], s[2 * im + 1]); im++; }
  }
}
constexpr int64_t VSTEP = 32 - (32 << 16);
__device__ __forceinline__ void issue_qk(float (&s)[32], const uint32_t (&q)[4], uint64_t dk) {
  wg_qk<NM, 0, NP / 2, 32>(s, q, dk + NP * 2);
  wg_qk<NP, 1, 0, 32>(s, q, dk);
}
__device__ __forceinline__ void issue_pv(float (&o)[12], const uint32_t (&p)[16], uint64_t dv) {
#pragma unroll
  for (int c = 0; c < 4; c++) { wg_pv_n24<1, 0, 12>(o, p[4 * c], p[4 * c + 1], p[4 * c + 2], p[4 * c + 3], dv + c * VSTEP); }
}

struct Params {
  const __nv_bfloat16* gate_w;
  const __nv_bfloat16* b_sp;
  const __nv_bfloat16* w_out;
  const __nv_bfloat16* wo;
  const __nv_bfloat16* w_in;
  const __nv_bfloat16* wq;
  const __nv_bfloat16* wk;
  const __nv_bfloat16* wv;
  uint32_t mlo, mhi;
  __nv_bfloat16* out;
};

__device__ __forceinline__ uint32_t store_o_tile(const float (&o)[12], int bi, int bj, int tau, int tid, uint32_t sb) {
  const int half = tau & 1, hh = tau >> 1, w = tid >> 5, l = tid & 31;
  const int r0 = half * 64 + w * 16 + (l >> 2);
  const float f0 = __fdividef(ldsf(sb + SM_G + r0 * 4), o[8]), f1 = __fdividef(ldsf(sb + SM_G + (r0 + 8) * 4), o[10]);
  uint32_t* dst = reinterpret_cast<uint32_t*>(g_o) + (bi * 8 + bj) * 4096 + (half * 8 + w * 2) * 256 + hh * 64;
  dst[l] = pack_bf16(o[0] * f0, o[1] * f0);
  dst[l + 32] = pack_bf16(o[4] * f0, o[5] * f0);
  dst[l + 256] = pack_bf16(o[2] * f1, o[3] * f1);
  dst[l + 288] = pack_bf16(o[6] * f1, o[7] * f1);
  return ld_back(dst + ((l >> 3) & 1) * 256 + (l & 7) * 8);
}

__global__ void __cluster_dims__(2, 1, 1) __launch_bounds__(NTHREADS, 1)
fused_kernel(const __grid_constant__ CUtensorMap tm_x, const __grid_constant__ CUtensorMap tm_wq,
             const __grid_constant__ CUtensorMap tm_win, const __grid_constant__ CUtensorMap tm_wsp,
             const __grid_constant__ CUtensorMap tm_wout, const __grid_constant__ CUtensorMap tm_wo, const Params prm) {
  extern __shared__ __align__(1024) uint8_t smem_raw[];
  const uint32_t sb = (uint32_t)__cvta_generic_to_shared(smem_raw);
  const int warp = __shfl_sync(0xffffffffu, (int)(threadIdx.x >> 5), 0);
  const int wg = warp >> 2;
  const int tid = threadIdx.x & 127;
  const int lane = threadIdx.x & 31;
  const int rank = blockIdx.x & 1;
  const int ai = (blockIdx.x >> 4) * 2 + rank, aj = (blockIdx.x >> 1) & 7;
  const int bi = blockIdx.x >> 3, bj = blockIdx.x & 7;
  auto BAR = [&](int k) { return sb + SM_BAR + 8u * k; };

  if (lane == 0) {
    if (warp == 16) {
      asm volatile("prefetch.tensormap [%0];" ::"l"(&tm_x) : "memory");
    } else if (warp == 18) {
      asm volatile("prefetch.tensormap [%0];" ::"l"(&tm_win) : "memory");
      asm volatile("prefetch.tensormap [%0];" ::"l"(&tm_wq) : "memory");
    } else if (warp == 19) {
      l2_prefetch(reinterpret_cast<const uint8_t*>(prm.w_in) + blockIdx.x * 11008, 11008);
      l2_prefetch(reinterpret_cast<const uint8_t*>(prm.wq) + blockIdx.x * 4096, 4096);
    } else if (warp < 16) {
#pragma unroll
      for (int r = 0; r < 4; r++) {
        const int k = warp + 16 * r;
        uint32_t cnt = 1;
        if (k >= B_XEMPTY && k < B_XEMPTY + 8) cnt = 4;
        if (k >= B_WEMPTY && k < B_WEMPTY + 12) cnt = 4;
        if (k >= B_REMPTY && k < B_REMPTY + 3) cnt = 2;
        if (k == B_ATT) cnt = 6;
        if (k == B_QRDY) cnt = 16;
        if (k == B_KSTAT) cnt = 17;
        mbar_init(BAR(k), cnt);
      }
      asm volatile("fence.mbarrier_init.release.cluster;" ::: "memory");
    }
  }
  __syncthreads();
  if (threadIdx.x == 0) TS(35);
  asm volatile("barrier.cluster.arrive.relaxed.aligned;" ::: "memory");
  if (warp != 16) asm volatile("barrier.cluster.wait.acquire.aligned;" ::: "memory");

  if (wg == 4) {
    asm volatile("setmaxnreg.dec.sync.aligned.u32 24;");
    if (warp == 18) {
      if (lane == 0) {
#pragma unroll 1
        for (int f = 0; f < 16; f++) {
          if (f == 4) TS(37);
          if (f >= 4) mbar_wait(BAR(B_WEMPTY + f - 4), 0);
          const uint32_t dst = sb + SM_RING + (f & 3) * WSLOT + rank * 2048, bar = BAR(B_WFULL + f);
          const int k0 = (f & 7) * 64 + rank * 32;
          const bool three = f < 8 ? aj < 6 : aj >= 2;
          const int c0 = 32 * (f < 8 ? (aj < 6 ? 21 + 3 * aj : 27 + 2 * aj) : (aj < 2 ? 2 * aj : 3 * aj - 2));
          mbar_expect(bar, three ? 16384 : 12288);
          tma2d_mc(dst, &tm_win, c0, k0, bar);
          tma2d_mc(dst + 4096, &tm_win, c0 + 32, k0, bar);
          if (three) tma2d_mc(dst + 8192, &tm_win, c0 + 64, k0, bar);
          tma2d_mc(dst + 12288, &tm_wq, 64 * aj + (f >> 3) * 32, k0, bar);
          if (f < 6) {
            mbar_expect(BAR(B_XFULL + 2 + f), 16384);
            tma2d(sb + SM_K + (f + 2) * 16384, &tm_x, (f + 2) * 64, ai * 128, BAR(B_XFULL + 2 + f));
          }
        }
        TS(1);
      }
    } else if (warp == 19) {
      mbar_wait(BAR(B_XEMPTY + 6), 0);
      const unsigned ep1 = lds32(sb + SM_MISC + 4 * M_EPOCH) + 1;
      wait_ge(&g_zcnt[lane * 32], ep1 * 8);
      __syncwarp();
      if (lane == 0) {
        mbar_arrive(BAR(B_ZOK));
        wait_ge(&g_z1cnt[bi * 32], ep1 * 16);
        mbar_arrive(BAR(B_Z1OK));
      }
    } else if (warp == 16) {
      if (lane == 0) {
        TS(0);
#pragma unroll 1
        for (int c = 0; c < 2; c++) {
          mbar_expect(BAR(B_XFULL + c), 16384);
          tma2d(sb + SM_K + c * 16384, &tm_x, c * 64, ai * 128, BAR(B_XFULL + c));
        }
        TS(36);
      }
      __syncwarp();
      asm volatile("barrier.cluster.wait.acquire.aligned;" ::: "memory");
      if (lane == 0) {
        asm volatile("prefetch.tensormap [%0];" ::"l"(&tm_wsp) : "memory");
        asm volatile("prefetch.tensormap [%0];" ::"l"(&tm_wout) : "memory");
        asm volatile("prefetch.tensormap [%0];" ::"l"(&tm_wo) : "memory");
        const int row = bi * 128 + rank * 64;
        mbar_wait(BAR(B_XEMPTY), 0);
        tma2d_pf(&tm_wsp, (bj >> 1) * 64, row);
        tma2d_pf(&tm_wsp, (bj >> 1) * 64 + 256, row);
        mbar_wait(BAR(B_XEMPTY + 7), 0);
        mbar_wait(BAR(B_ZOK), 0);
        const unsigned ep1 = lds32(sb + SM_MISC + 4 * M_EPOCH) + 1;
        fence_async();
        TS(2);
        int st = 0, ph = 1;
#pragma unroll 1
        for (int n = 0; n < 46; n++) {
          const uint32_t stg = sb + SM_RING + st * RSTAGE, bar = BAR(B_RFULL + st);
          if (n >= 3) mbar_wait(BAR(B_REMPTY + st), ph);
          if (n < 32) {
            mbar_expect(bar, 16384 + 11264);
            tma2d_mc(stg + rank * 8192, &tm_wsp, n * 64, row, bar);
            bulk(stg + 16384, reinterpret_cast<const uint8_t*>(g_z2n) + (bj * 32 + n) * 11264, 11264, bar);
            if ((n & 3) == (bj >> 1) && n < 24) tma2d_pf(&tm_wsp, (n + 8) * 64, row);
            if (n == 16) {
              l2_prefetch(reinterpret_cast<const uint8_t*>(prm.w_out) + blockIdx.x * 5504, 5504);
              l2_prefetch(reinterpret_cast<const uint8_t*>(prm.wo) + blockIdx.x * 4096, 4096);
            }
          } else if (n < 43) {
            const int c = n - 32;
            mbar_expect(bar, 16384 + 8192);
            tma2d(stg + 16384, &tm_wout, 64 * bj, c * 64, bar);
            if (c == 0) { wait_ge(&g_ucnt[bi * 32], ep1 * 8); fence_async(); TS(3); }
            bulk_mc(stg + rank * 8192, reinterpret_cast<const uint8_t*>(g_u) + (bi * 11 + c) * 16384 + rank * 8192, 8192, bar);
          }
          if (++st == 3) { st = 0; ph ^= 1; }
        }
        mbar_expect(BAR(B_WOFULL), 65536);
#pragma unroll 1
        for (int c = 0; c < 8; c++) tma2d(sb + SM_RING + c * 8192, &tm_wo, 64 * bj, c * 64, BAR(B_WOFULL));
        TS(4);
        wait_ge(&g_ocnt[bi * 32], ep1 * 24);
        mbar_wait(BAR(B_ATT), 0);
        fence_async();
        TS(5);
#pragma unroll 1
        for (int c = 0; c < 8; c++) {
          mbar_expect(BAR(B_XFULL + c), 16384);
          bulk_mc(sb + SM_K + c * 16384 + rank * 8192, reinterpret_cast<const uint8_t*>(g_o) + (bi * 8 + c) * 16384 + rank * 8192, 8192, BAR(B_XFULL + c));
        }
      }
    } else {
      if (lane == 0) {
        sts32(sb + SM_MISC + 4 * M_EPOCH, atomicAdd(&g_ticket, 1u) / NCTA);
        mbar_arrive(BAR(B_EPOCH));
        TS(71);
      }
      __syncwarp();
      const unsigned ep1 = lds32(sb + SM_MISC + 4 * M_EPOCH) + 1;
      mbar_wait(BAR(B_WFULL + 8), 0);
      uint32_t kn = 0, vb = 0;
#pragma unroll 1
      for (int n = 0; n < SPIN_LIMIT; n++) {
        unsigned long long a, b, c, d;
        asm volatile("ld.relaxed.gpu.global.v2.b64 {%0, %1}, [%2];" : "=l"(a), "=l"(b) : "l"(&g_kvflag[2 * lane]) : "memory");
        asm volatile("ld.relaxed.gpu.global.v2.b64 {%0, %1}, [%2];" : "=l"(c), "=l"(d) : "l"(&g_kvflag[64 + 2 * lane]) : "memory");
        kn = max((uint32_t)a, (uint32_t)c); vb = (uint32_t)b | (uint32_t)d;
        if (__all_sync(0xffffffffu, (uint32_t)(a >> 32) == ep1 && (uint32_t)(b >> 32) == ep1 && (uint32_t)(c >> 32) == ep1 && (uint32_t)(d >> 32) == ep1)) break;
        __nanosleep(100);
      }
      asm volatile("fence.acquire.gpu;" ::: "memory");
      kn = __reduce_max_sync(0xffffffffu, kn);
      vb = __reduce_or_sync(0xffffffffu, vb);
      if (lane == 0) {
        TS(6);
        sts32(sb + SM_MISC + 4 * M_KN2, kn);
        sts32(sb + SM_MISC + 4 * M_VOK, vb == 0xFFFFu ? 1u : 0u);
        mbar_arrive(BAR(B_KSTAT));
        mbar_expect(BAR(B_KVFULL), KV_BYTES);
        fence_async();
#pragma unroll 1
        for (int c = 0; c < 8; c++) {
          const uint32_t off = c * 16384 + rank * 8192;
          mbar_wait(BAR(B_XEMPTY + c), 0);
          bulk_mc(sb + SM_K + off, reinterpret_cast<const uint8_t*>(g_kimg) + off, 8192, BAR(B_KVFULL));
        }
        TS(7);
        mbar_wait(BAR(B_DEC), 0);
        if (!lds32(sb + SM_MISC + 4 * M_FAST)) {
          mbar_wait(BAR(B_KVFULL), 0);
          mbar_expect(BAR(B_KFB), 65536);
          bulk(sb + SM_K, g_kbf, 65536, BAR(B_KFB));
        }
      }
    }
  } else {
    asm volatile("setmaxnreg.inc.sync.aligned.u32 112;");
    const int w = tid >> 5, g = lane >> 2, t4 = lane & 3, half = wg & 1;
    {
      float acc[64];
      if (wg == 2) {
        const int slot = ai * 4 + (aj >> 1), isv = aj & 1;
        const uint4* wsrc = reinterpret_cast<const uint4*>(isv ? prm.wv : prm.wk) + tid;
        uint4 wr[8];
#pragma unroll
        for (int r = 0; r < 8; r++) wr[r] = __ldg(wsrc + 128 * r);
#pragma unroll
        for (int r = 0; r < 8; r++) sts128(sb + SM_WKV + r * 2048 + (tid >> 1) * 32 + (((tid ^ (tid >> 3)) & 1) << 4), wr[r].x, wr[r].y, wr[r].z, wr[r].w);
        fence_async_smem();
        bar_sync(3, 128);
        float kv[16];
#pragma unroll
        for (int k = 0; k < 16; k++) kv[k] = 0.f;
        regfence(kv);
#pragma unroll 1
        for (int c = 0; c < 8; c++) {
          mbar_wait(BAR(B_XFULL + c), 0);
          const uint64_t da = mkdesc(sb + SM_WKV + c * 2048, 0, 256, 3);
          const uint64_t db = mkdesc(sb + SM_K + c * 16384 + (aj >> 1) * 4096, 16, 1024, 1);
          wg_fence();
#pragma unroll
          for (int k = 0; k < 4; k++) wg_ss_n32t<0, 16>(kv, da + 32 * k, db + 2 * k);
          wg_commit();
        }
        wg_wait<0>();
        regfence(kv);
        if (tid == 0) TS(22);
        const uint32_t sT = sb + SM_WKV, sH = sb + SM_WKV + 4096;
        bar_sync(3, 128);
        {
          const float a = w & 1 ? kv[4] : kv[0], b = w & 1 ? kv[5] : kv[1], c = w & 1 ? kv[6] : kv[2], d = w & 1 ? kv[7] : kv[3];
          const float e = w & 1 ? kv[12] : kv[8], f = w & 1 ? kv[13] : kv[9], h = w & 1 ? kv[14] : kv[10], i = w & 1 ? kv[15] : kv[11];
          const uint32_t lo = pack_bf16(w & 2 ? e : a, w & 2 ? f : b), hi = pack_bf16(w & 2 ? h : c, w & 2 ? i : d);
          const uint32_t p = sT + ((w * 8 + 2 * t4) * 17 + g) * 4;
          sts32(p, lo << 16); sts32(p + 68, lo & 0xFFFF0000u); sts32(p + 32, hi << 16); sts32(p + 100, hi & 0xFFFF0000u);
        }
        bar_sync(3, 128);
        if (tid == 0) TS(64);
        const int tok = (tid & 63) >> 1, hf = tid & 1;
        float f[8];
#pragma unroll
        for (int e = 0; e < 8; e++) f[e] = ldsf(sT + (tok * 17 + hf * 8 + e) * 4);
        uint4 val = make_uint4(pack_bf16(f[0], f[1]), pack_bf16(f[2], f[3]), pack_bf16(f[4], f[5]), pack_bf16(f[6], f[7]));
        uint32_t stat = 0;
        if (isv) {
#pragma unroll
          for (int e = 0; e < 8; e++) {
            if (fabsf(f[e]) >= 9.5367431640625e-07f) stat |= 1u << e;
            if (!(fabsf(f[e]) <= 1073741824.f)) stat |= 1u << (16 - 8 * hf);
          }
          stat = __reduce_or_sync(0xffffffffu, stat << (8 * hf));
        } else {
          float n2 = 0.f;
#pragma unroll
          for (int e = 0; e < 8; e++) n2 = fmaf(f[e], f[e], n2);
          n2 += __shfl_xor_sync(0xffffffffu, n2, 1);
          if (!(n2 <= 3.0e38f)) n2 = 3.0e38f;
          stat = __reduce_max_sync(0xffffffffu, __float_as_uint(n2));
          if (tid < 48) {
            const int d = tid & 15, sg = tid >> 4, j0 = sg == 0 ? 0 : (sg == 1 ? 10 : 22), j1 = sg == 0 ? 10 : (sg == 1 ? 22 : 32);
            const float sc = slot < NP ? 16.f : 0.125f, fb = slot < NP ? 1.f : 0.f;
            float kx[12], run = 0.f;
#pragma unroll
            for (int e = 0; e < 12; e++) kx[e] = ldsf(sT + (min(j0 + e, 31) * 17 + d) * 4);
#pragma unroll
            for (int e = 0; e < 12; e++) {
              const __half hv = __float2half_rn(fmaf(kx[e], sc, -run));
              run = fmaf(__half2float(hv), fb, run);
              if (j0 + e < j1) sts16(sH + ((j0 + e) * 16 + d) * 2, __half_as_ushort(hv));
            }
          }
        }
        if (lane == 0) sts32(sb + SM_MISC + 4 * (M_KVR + w), stat);
        bar_sync(3, 128);
        const uint32_t off = (isv ? SM_V / 16 : 0) + tok * 128 + slot * 2 + (hf ^ ((slot >> 2) & 1));
        uint4* dst = (tid < 64 ? g_kimg : g_kbf) + off;
        if (!isv && tid < 64) val = lds128(sH + tok * 32 + hf * 16);
        uint32_t chk = 0;
        if (tid < 64 || !isv) { *dst = val; chk = ld_back(dst); }
        mbar_wait(BAR(B_EPOCH), 0);
        consume(chk, sb);
        fence_async();
        bar_sync(3, 128);
        if (tid == 0) {
          const uint32_t s0 = lds32(sb + SM_MISC + 4 * M_KVR), s1 = lds32(sb + SM_MISC + 4 * (M_KVR + 1));
          const unsigned long long fl = ((unsigned long long)(lds32(sb + SM_MISC + 4 * M_EPOCH) + 1) << 32) | (isv ? (s0 | s1) : max(s0, s1));
          asm volatile("st.relaxed.gpu.global.b64 [%0], %1;" ::"l"(&g_kvflag[ai * 8 + aj]), "l"(fl) : "memory");
          TS(23);
        }
      } else if (wg == 3) {
        uint4* sW = reinterpret_cast<uint4*>(smem_raw + SM_GW);
        if (tid < 64) sW[tid] = __ldg(reinterpret_cast<const uint4*>(prm.gate_w) + tid);
        sts32(sb + SM_ONES + tid * 4, 0x3F803F80u);
        bar_sync(4, 128);
        const int v = tid & 7, rr = tid >> 3;
        float a[8];
#pragma unroll
        for (int p = 0; p < 8; p++) a[p] = 0.f;
#pragma unroll 1
        for (int c = 0; c < 8; c++) {
          const uint4 gv = sW[c * 8 + v];
          mbar_wait(BAR(B_XFULL + c), 0);
          if (tid == 0) TS(40 + c);
          const uint4* xr = reinterpret_cast<const uint4*>(smem_raw + SM_K + c * 16384 + rr * 128) + (v ^ (rr & 7));
#pragma unroll
          for (int p = 0; p < 8; p++) {
            const uint4 xv = xr[p * 128];
            float s = fmaf(bf_lo(xv.x), bf_lo(gv.x), a[p]), t = bf_hi(xv.x) * bf_hi(gv.x);
            s = fmaf(bf_lo(xv.y), bf_lo(gv.y), s); t = fmaf(bf_hi(xv.y), bf_hi(gv.y), t);
            s = fmaf(bf_lo(xv.z), bf_lo(gv.z), s); t = fmaf(bf_hi(xv.z), bf_hi(gv.z), t);
            s = fmaf(bf_lo(xv.w), bf_lo(gv.w), s); t = fmaf(bf_hi(xv.w), bf_hi(gv.w), t);
            a[p] = s + t;
          }
        }
        float mine = 0.f;
#pragma unroll
        for (int p = 0; p < 8; p++) {
          float s = a[p];
          s += __shfl_xor_sync(0xffffffffu, s, 1); s += __shfl_xor_sync(0xffffffffu, s, 2); s += __shfl_xor_sync(0xffffffffu, s, 4);
          if (v == p) mine = s;
        }
        const float gt = __fdividef(1.f, 1.f + __expf(-mine));
        sts32(sb + SM_G + (rr + 16 * v) * 4, __float_as_uint(gt));
        fence_async_smem();
        bar_sync(4, 128);
        if (aj == 0) g_gate[ai * 128 + tid] = ldsf(sb + SM_G + tid * 4);
        if (tid == 0) TS(8);
      }
#pragma unroll
      for (int k = 0; k < 64; k++) acc[k] = 0.f;
      regfence(acc);
      const int pass = wg >> 1;
#pragma unroll 1
      for (int c = 0; c < 8; c++) {
        mbar_wait(BAR(B_XFULL + c), 0);
        mbar_wait(BAR(B_WFULL + pass * 8 + c), 0);
        if (tid == 0 && half == pass) TS(48 + pass * 8 + c);
        const uint64_t da = mkdesc(sb + SM_K + c * 16384 + half * 8192, 16, 1024, 1);
        const uint64_t db = mkdesc(sb + SM_RING + (c & 3) * WSLOT, 4096, 512, 2);
        wg_fence();
#pragma unroll
        for (int k = 0; k < 4; k++) wg_ss_n128<0, 64>(acc, da + 2 * k, db + 64 * k);
        wg_commit();
        wg_wait<0>();
        if (tid == 0) {
          if (pass * 8 + c < 12) mbar_arrive_both(BAR(B_WEMPTY + pass * 8 + c));
          if (pass) mbar_arrive_both(BAR(B_XEMPTY + c));
        }
      }
      regfence(acc);
      if (tid == 0) TS(wg == 0 ? 16 : (wg == 2 ? 24 : (wg == 3 ? 9 : 95)));
      uint32_t qb[8];
      {
        float n2 = 0.f;
#pragma unroll
        for (int k = 0; k < 8; k++) qb[k] = pack_bf16(acc[48 + 2 * k], acc[49 + 2 * k]);
#pragma unroll
        for (int k = 0; k < 4; k++) {
          const uint32_t a = qb[4 * (k >> 1) + (k & 1)], b = qb[4 * (k >> 1) + (k & 1) + 2];
          float s = bf_lo(a) * bf_lo(a);
          s = fmaf(bf_hi(a), bf_hi(a), s); s = fmaf(bf_lo(b), bf_lo(b), s); s = fmaf(bf_hi(b), bf_hi(b), s);
          s += __shfl_xor_sync(0xffffffffu, s, 1); s += __shfl_xor_sync(0xffffffffu, s, 2);
          if (!(s <= 3.0e38f)) s = 3.0e38f;
          n2 = fmaxf(n2, s);
        }
        const uint32_t nmax = __reduce_max_sync(0xffffffffu, __float_as_uint(n2));
        if (lane == 0) { sts32(sb + SM_MISC + 4 * (M_RED + warp), nmax); mbar_arrive(BAR(B_KSTAT)); }
      }
      auto finish_q = [&]() {
        mbar_wait(BAR(B_KSTAT), 0);
        const float qn2 = __uint_as_float(__reduce_max_sync(0xffffffffu, lds32(sb + SM_MISC + 4 * (M_RED + (lane & 15)))));
        const float kn2 = ldsf(sb + SM_MISC + 4 * M_KN2);
        constexpr float SC = QSCALE * 0.125f;
        const bool fast = lds32(sb + SM_MISC + 4 * M_VOK) && qn2 <= 4.0e8f && kn2 <= 4.0e6f && qn2 * kn2 * (SC * SC) <= BOUND * BOUND;
        if (fast) {
#pragma unroll
          for (int k = 0; k < 8; k++) qb[k] = pack_f16(bf_lo(qb[k]) * QSCALE, bf_hi(qb[k]) * QSCALE);
        }
        sts128(sb + SM_Q + wg * 2048 + pass * 4096 + tid * 16, qb[0], qb[1], qb[2], qb[3]);
        sts128(sb + SM_Q + wg * 2048 + pass * 4096 + 4096 + tid * 16, qb[4], qb[5], qb[6], qb[7]);
        if (threadIdx.x == 256) { sts32(sb + SM_MISC + 4 * M_FAST, fast ? 1u : 0u); mbar_arrive(BAR(B_DEC)); }
        __syncwarp();
        if (lane == 0) mbar_arrive(BAR(B_QRDY));
        if (tid == 0 && pass) TS(75 + wg);
      };
      if (pass) finish_q();
#pragma unroll
      for (int k = 0; k < 48; k++) acc[k] = gelu_tanh(acc[k]);
      int fb0, c_lo = 0, c_hi = 12;
      if (wg < 2) { fb0 = aj < 6 ? 12 * aj - 2 : 22 + 8 * aj; if (aj == 0) c_lo = 2; if (aj >= 6) c_hi = 8; }
      else { fb0 = aj < 2 ? 8 * aj : 12 * aj - 8; if (aj < 2) c_hi = 8; if (aj == 7) c_hi = 10; }
      if (wg < 2) {
        const bool lo_ok = c_lo == 0, hi_ok = c_hi == 12;
        float s0 = 0.f, s1 = 0.f;
#pragma unroll
        for (int k = 0; k < 48; k++) {
          if ((k < 8 && !lo_ok) || (k >= 32 && !hi_ok)) acc[k] = 0.f;
          if (k & 2) s1 += acc[k]; else s0 += acc[k];
        }
        s0 += __shfl_xor_sync(0xffffffffu, s0, 1); s0 += __shfl_xor_sync(0xffffffffu, s0, 2);
        s1 += __shfl_xor_sync(0xffffffffu, s1, 1); s1 += __shfl_xor_sync(0xffffffffu, s1, 2);
        const float inv_n = __fdividef(0.125f, (float)(c_hi - c_lo));
        const float m0 = s0 * inv_n, m1 = s1 * inv_n;
        float v0 = 0.f, v1 = 0.f;
#pragma unroll
        for (int k = 0; k < 48; k++) {
          float d = acc[k] - ((k & 2) ? m1 : m0);
          if ((k < 8 && !lo_ok) || (k >= 32 && !hi_ok)) d = 0.f;
          if (k & 2) v1 = fmaf(d, d, v1); else v0 = fmaf(d, d, v0);
        }
        v0 += __shfl_xor_sync(0xffffffffu, v0, 1); v0 += __shfl_xor_sync(0xffffffffu, v0, 2);
        v1 += __shfl_xor_sync(0xffffffffu, v1, 1); v1 += __shfl_xor_sync(0xffffffffu, v1, 2);
        const int r0 = half * 64 + w * 16 + g;
        mbar_wait(BAR(B_EPOCH), 0);
        const unsigned ep1 = lds32(sb + SM_MISC + 4 * M_EPOCH) + 1;
        if (threadIdx.x == 0) TS(67);
        if (t4 < 2) {
          const float m = t4 ? m1 : m0, v = t4 ? v1 : v0;
          asm volatile("st.relaxed.gpu.global.v2.b64 [%0], {%1, %2};" ::"l"(&g_lnstat[(ai * 8 + aj) * 128 + r0 + 8 * t4]),
                       "l"(((unsigned long long)ep1 << 32) | __float_as_uint(m)), "l"(((unsigned long long)ep1 << 32) | __float_as_uint(v)) : "memory");
        }
        float sm[4], sv[4];
        const uint4* lp = &g_lnstat[(ai * 8 + 2 * t4) * 128 + r0];
#pragma unroll 1
        for (int n = 0; n < SPIN_LIMIT; n++) {
          bool ok = true;
#pragma unroll
          for (int e = 0; e < 4; e++) {
            unsigned long long a, b;
            asm volatile("ld.relaxed.gpu.global.v2.b64 {%0, %1}, [%2];" : "=l"(a), "=l"(b) : "l"(lp + (e >> 1) * 128 + (e & 1) * 8) : "memory");
            ok = ok && (uint32_t)(a >> 32) == ep1 && (uint32_t)(b >> 32) == ep1;
            sm[e] = __uint_as_float((uint32_t)a); sv[e] = __uint_as_float((uint32_t)b);
          }
          if (__all_sync(0xffffffffu, ok)) break;
          __nanosleep(150);
        }
        if (threadIdx.x == 0) TS(68);
        const float na = t4 == 0 ? 80.f : (t4 == 3 ? 64.f : 96.f), nb = t4 == 3 ? 64.f : 96.f;
#pragma unroll
        for (int r = 0; r < 2; r++) {
          float t = fmaf(sm[r], na, sm[2 + r] * nb);
          t += __shfl_xor_sync(0xffffffffu, t, 1); t += __shfl_xor_sync(0xffffffffu, t, 2);
          const float mu = t * (1.f / 688.f);
          const float da = sm[r] - mu, db = sm[2 + r] - mu;
          float m2 = sv[r] + sv[2 + r] + na * da * da + nb * db * db;
          m2 += __shfl_xor_sync(0xffffffffu, m2, 1); m2 += __shfl_xor_sync(0xffffffffu, m2, 2);
          const float rs = rsqrtf(fmaf(m2, 1.f / 688.f, 1e-5f)), sh = -mu * rs;
#pragma unroll
          for (int k = 2 * r; k < 48; k += 4) { acc[k] = fmaf(acc[k], rs, sh); acc[k + 1] = fmaf(acc[k + 1], rs, sh); }
        }
        if (aj == 7) {
          c_hi = 10;
#pragma unroll
          for (int k = 32; k < 40; k++) acc[k] = 0.f;
        }
      }
      uint32_t* zp = wg < 2 ? reinterpret_cast<uint32_t*>(g_z2n) + (ai * 2 + half) * 2816 + w * 704
                            : reinterpret_cast<uint32_t*>(g_z1) + (ai * 88 * 16 + half * 8 + w * 2) * 32;
      const int mul = wg < 2 ? 373 : 0, cstr = wg < 2 ? 32 : 512, rstr = wg < 2 ? 352 : 32;
      auto zoff = [&](int c8) { const int fb = fb0 + c8; return ((fb * mul) >> 12) * (32 * 2816 - 352) + fb * cstr; };
#pragma unroll
      for (int c8 = 0; c8 < 12; c8++) {
        uint32_t* p = zp + zoff(c8) + lane;
        if (c8 >= c_lo && c8 < c_hi) { p[0] = pack_bf16(acc[4 * c8], acc[4 * c8 + 1]); p[rstr] = pack_bf16(acc[4 * c8 + 2], acc[4 * c8 + 3]); }
      }
      if (tid == 0) TS(wg == 0 ? 69 : 78 + wg);
      uint32_t chk = 0;
#pragma unroll
      for (int r = 0; r < 3; r++) {
        const int it = lane + 32 * r, c8 = it >> 3;
        if (c8 >= c_lo && c8 < c_hi) chk ^= ld_back(zp + zoff(c8) + ((it >> 2) & 1) * rstr + (it & 3) * 8);
      }
      if (wg == 3 && aj == 0) chk ^= ld_back(&g_gate[ai * 128 + tid]);
      consume(chk, sb);
      fence_async();
      bar_sync(1 + wg, 128);
      if (tid == 0) { red_relaxed(wg < 2 ? &g_zcnt[(ai * 2 + half) * 32] : &g_z1cnt[ai * 32]); TS(wg < 2 ? 20 + wg : 8 + wg * wg); }
      if (!pass) finish_q();
    }
    if (wg == 3) {
      asm volatile("setmaxnreg.inc.sync.aligned.u32 120;");
      int st = 0, ph = 0;
      {
        float acc[88];
#pragma unroll
        for (int k = 0; k < 88; k++) acc[k] = 0.f;
        regfence(acc);
#pragma unroll 1
        for (int n = 0; n < 32; n++) {
          mbar_wait(BAR(B_RFULL + st), ph);
          const uint64_t da = mkdesc(sb + SM_RING + st * RSTAGE, 16, 1024, 1);
          const uint64_t db = mkdesc(sb + SM_RING + st * RSTAGE + 16384, 1408, 128, 0);
#pragma unroll
          for (int k = 0; k < 4; k++) {
            wg_fence();
            wg_ss_n88<0, 88>(acc, da + 2 * k, db + 176 * k);
            wg_ss_n88<44, 88>(acc, da + 512 + 2 * k, db + 176 * k);
            wg_commit();
            wg_wait<0>();
          }
          if (tid == 0) mbar_arrive_both(BAR(B_REMPTY + st));
          if (++st == 3) { st = 0; ph ^= 1; }
        }
        regfence(acc);
        if (tid == 0) TS(11);
        mbar_wait(BAR(B_Z1OK), 0);
        const uint32_t* z1p = reinterpret_cast<const uint32_t*>(g_z1) + ((bi * 88 + bj * 11) * 16 + w * 2) * 32 + lane;
        uint32_t* up = reinterpret_cast<uint32_t*>(g_u) + bi * 11 * 4096 + w * 512 + lane;
#pragma unroll
        for (int r = 0; r < 4; r++) {
          const int row = bi * 128 + (r >> 1) * 64 + w * 16 + (r & 1) * 8 + g;
          const float og = 1.f - __ldcg(&g_gate[row]), bs = __bfloat162float(prm.b_sp[row]) * og;
          uint32_t zz[11];
#pragma unroll
          for (int c8 = 0; c8 < 11; c8++) zz[c8] = __ldcg(z1p + c8 * 512 + ((r >> 1) * 8 + (r & 1)) * 32);
          if (bj == 7) zz[9] = zz[10] = 0;
#pragma unroll
          for (int c8 = 0; c8 < 11; c8++) {
            const int k = (r >> 1) * 44 + c8 * 4 + (r & 1) * 2, cb = 11 * bj + c8;
            uint32_t v = pack_bf16(fmaf(acc[k], og, bs), fmaf(acc[k + 1], og, bs));
            asm("mul.rn.bf16x2 %0, %0, %1;" : "+r"(v) : "r"(zz[c8]));
            up[cb * 32 + (cb >> 3) * 3840 + ((r >> 1) * 8 + (r & 1)) * 256] = v;
          }
        }
        fence_async();
        bar_sync(4, 128);
        if (tid == 0) { red_release(&g_ucnt[bi * 32]); TS(12); }
      }
      float oc[64];
#pragma unroll
      for (int k = 0; k < 64; k++) oc[k] = 0.f;
      regfence(oc);
#pragma unroll 1
      for (int n = 0; n < 19; n++) {
        uint32_t sa, sw;
        if (n < 11) { mbar_wait(BAR(B_RFULL + st), ph); sa = SM_RING + st * RSTAGE; sw = sa + 16384; }
        else {
          if (n == 11) { if (tid == 0) TS(13); mbar_wait(BAR(B_WOFULL), 0); }
          mbar_wait(BAR(B_XFULL + n - 11), 1); sa = SM_K + (n - 11) * 16384; sw = SM_RING + (n - 11) * 8192;
        }
        const uint64_t da = mkdesc(sb + sa, 128, 1024, 0), db = mkdesc(sb + sw, 8192, 1024, 1);
#pragma unroll
        for (int k = 0; k < 4; k += 2) {
          wg_fence();
          wg_ss_n64<0, 64>(oc, da + 16 * k, db + 128 * k);
          wg_ss_n64<32, 64>(oc, da + 512 + 16 * k, db + 128 * k);
          wg_ss_n64<0, 64>(oc, da + 16 * k + 16, db + 128 * k + 128);
          wg_ss_n64<32, 64>(oc, da + 528 + 16 * k, db + 128 * k + 128);
          wg_commit();
          if (n < 11) wg_wait<0>();
        }
        if (n < 11) {
          if (tid == 0) mbar_arrive_both(BAR(B_REMPTY + st));
          if (++st == 3) { st = 0; ph ^= 1; }
        }
      }
      wg_wait<0>();
      regfence(oc);
      if (tid == 0) TS(14);
      uint32_t* op = reinterpret_cast<uint32_t*>(prm.out) + (bi * 128 + w * 16 + g) * 256 + bj * 32 + t4;
#pragma unroll
      for (int k = 0; k < 64; k += 2) {
        const int hf = k / 32, c8 = (k % 32) / 4, r8 = (k >> 1) & 1;
        op[(hf * 64 + r8 * 8) * 256 + c8 * 4] = pack_bf16(oc[k], oc[k + 1]);
      }
      if (tid == 0) TS(15);
    } else {
      mbar_wait(BAR(B_QRDY), 0);
    if (tid == 0) TS(25 + wg);
    mbar_wait(BAR(B_KVFULL), 0);
    if (tid == 0) TS(28 + wg);
    const uint64_t dk0 = mkdesc(sb + SM_K, 16, 256, 3);
    const uint64_t dv0 = mkdesc(sb + SM_V, SM_ONES - SM_V, 256, 3);
    const int aw = wg == 0 ? 0 : 3 - wg;
    uint32_t chk = 0;
    float o[12], s[32];
    uint32_t q[4], p0[16], p1[16];
    if (lds32(sb + SM_MISC + 4 * M_FAST)) {
      const uint32_t mlo = prm.mlo, mhi = prm.mhi;
      uint64_t dk = dk0, dv = dv0;
#define STEP(PIN, POUT) { wg_fence(); issue_qk(s, q, dk); dk += 128; wg_commit(); issue_pv(o, PIN, dv); dv += 4 * VSTEP; wg_commit(); \
                          wg_wait<1>(); regfence(s); softmax_step(s, POUT, mlo, mhi); wg_wait<0>(); }
#pragma unroll 1
      for (int sg = aw * 8; sg < aw * 8 + 8; sg++) {
        const int tau = sg / 3, seg = sg - tau * 3;
        int n2 = seg == 1 ? 6 : 5;
#pragma unroll
        for (int k = 0; k < NP / 2; k++) s[k] = MAGIC_C;
        if (sg == aw * 8 || seg == 0) {
          const int j0 = seg == 0 ? 0 : (seg == 1 ? 10 : 22);
          dk = dk0 + 128 * j0;
          dv = dv0 + VSTEP * (4 * j0);
          const uint4 qv = lds128(sb + SM_Q + tau * 2048 + tid * 16);
          q[0] = qv.x; q[1] = qv.y; q[2] = qv.z; q[3] = qv.w;
#pragma unroll
          for (int k = 0; k < 12; k++) o[k] = 0.f;
          regfence(o); regfence(s);
          wg_fence(); issue_qk(s, q, dk); dk += 128; wg_commit();
          wg_wait<0>(); regfence(s);
          softmax_step(s, p0, mlo, mhi);
          STEP(p0, p1);
          n2--;
        }
        regfence(s);
#pragma unroll 1
        for (; n2 > 0; n2--) { STEP(p1, p0); STEP(p0, p1); }
        if (sg == aw * 8 + 7 || seg == 2) {
          wg_fence(); issue_pv(o, p1, dv); dv += 4 * VSTEP; wg_commit();
          wg_wait<0>(); regfence(o);
          if (sg == 8 || sg == 17) {
            float4* pp = g_part + (blockIdx.x * 2 + (aw - 1)) * 384 + tid;
            pp[0] = make_float4(o[0], o[1], o[2], o[3]); pp[128] = make_float4(o[4], o[5], o[6], o[7]); pp[256] = make_float4(o[8], o[9], o[10], o[11]);
            __threadfence_block();
            bar_arrive(5 + aw, 256);
          } else {
            if (sg == 7 || sg == 15) {
              bar_sync(6 + aw, 256);
              const float4* pp = g_part + (blockIdx.x * 2 + aw) * 384 + tid;
              const float4 a = pp[0], b = pp[128], c = pp[256];
              o[0] += a.x; o[1] += a.y; o[2] += a.z; o[3] += a.w; o[4] += b.x; o[5] += b.y; o[6] += b.z; o[7] += b.w; o[8] += c.x; o[10] += c.z;
            }
            chk ^= store_o_tile(o, ai, aj, tau, tid, sb);
          }
        }
      }
#undef STEP
    } else {
      mbar_wait(BAR(B_KFB), 0);
      constexpr float SC = 0.25f * 1.4426950408889634f;
#pragma unroll 1
      for (int tau = wg * 3; tau < wg * 3 + 3 && tau < 8; tau++) {
        const uint4 qv = lds128(sb + SM_Q + tau * 2048 + tid * 16);
        float m0 = -INFINITY, m1 = -INFINITY;
#pragma unroll
        for (int k = 0; k < 12; k++) o[k] = 0.f;
        uint64_t dv = dv0;
#pragma unroll 1
        for (int j = 0; j < 32; j++) {
          regfence(s);
          wg_fence(); wg_qkb_n64<0, 0, 32>(s, qv.x, qv.y, qv.z, qv.w, dk0 + 128 * j); wg_commit();
          wg_wait<0>(); regfence(s);
          float x0 = m0, x1 = m1;
#pragma unroll
          for (int k = 0; k < 32; k++) { s[k] *= SC; if (k & 2) x1 = fmaxf(x1, s[k]); else x0 = fmaxf(x0, s[k]); }
          x0 = fmaxf(x0, __shfl_xor_sync(0xffffffffu, x0, 1)); x0 = fmaxf(x0, __shfl_xor_sync(0xffffffffu, x0, 2));
          x1 = fmaxf(x1, __shfl_xor_sync(0xffffffffu, x1, 1)); x1 = fmaxf(x1, __shfl_xor_sync(0xffffffffu, x1, 2));
          const float c0 = ex2(m0 - x0), c1 = ex2(m1 - x1);
          m0 = x0; m1 = x1;
#pragma unroll
          for (int k = 0; k < 12; k++) o[k] *= (k & 2) ? c1 : c0;
#pragma unroll
          for (int k = 0; k < 16; k++) { const float m = (k & 1) ? m1 : m0; p0[k] = exp_mufu(s[2 * k] - m, s[2 * k + 1] - m); }
          regfence(o);
          wg_fence(); issue_pv(o, p0, dv); dv += 4 * VSTEP; wg_commit();
          wg_wait<0>(); regfence(o);
        }
        chk ^= store_o_tile(o, ai, aj, tau, tid, sb);
      }
    }
    consume(chk, sb);
    fence_async();
    bar_sync(1 + wg, 128);
    if (tid == 0) { red_relaxed(&g_ocnt[ai * 32]); mbar_arrive_both(BAR(B_ATT)); TS(31 + wg); }
    }
  }
  __syncwarp();
  asm volatile("barrier.cluster.arrive.relaxed;" ::: "memory");
  asm volatile("barrier.cluster.wait;" ::: "memory");
}

typedef CUresult (*EncodeFn)(CUtensorMap*, CUtensorMapDataType, cuuint32_t, void*, const cuuint64_t*, const cuuint64_t*,
                             const cuuint32_t*, const cuuint32_t*, CUtensorMapInterleave, CUtensorMapSwizzle,
                             CUtensorMapL2promotion, CUtensorMapFloatOOBfill);

void make_map(EncodeFn enc, CUtensorMap* tm, const void* base, uint64_t cols, uint64_t rows, uint32_t bc, uint32_t br, CUtensorMapSwizzle sw) {
  cuuint64_t gd[2] = {cols, rows};
  cuuint64_t gs[1] = {cols * 2};
  cuuint32_t bd[2] = {bc, br};
  cuuint32_t es[2] = {1, 1};
  enc(tm, CU_TENSOR_MAP_DATA_TYPE_BFLOAT16, 2, const_cast<void*>(base), gd, gs, bd, es, CU_TENSOR_MAP_INTERLEAVE_NONE, sw,
      CU_TENSOR_MAP_L2_PROMOTION_L2_128B, CU_TENSOR_MAP_FLOAT_OOB_FILL_NONE);
}

}

extern "C" void kernel_launch(void* const* d_in, const int* in_sizes, int n_in, void* d_out, int out_size) {
  (void)in_sizes; (void)n_in; (void)out_size;
  static EncodeFn enc = nullptr;
  if (!enc) {
    void* fn = nullptr;
    cudaDriverEntryPointQueryResult qr;
    cudaGetDriverEntryPoint("cuTensorMapEncodeTiled", &fn, cudaEnableDefault, &qr);
    enc = (EncodeFn)fn;
    cudaFuncSetAttribute(fused_kernel, cudaFuncAttributeMaxDynamicSharedMemorySize, SMEM_BYTES);
  }
  CUtensorMap tx, tq, tin, tsp, tout, to;
  make_map(enc, &tx, d_in[0], 512, 2048, 64, 128, CU_TENSOR_MAP_SWIZZLE_128B);
  make_map(enc, &tq, d_in[1], 512, 512, 32, 32, CU_TENSOR_MAP_SWIZZLE_64B);
  make_map(enc, &to, d_in[4], 512, 512, 64, 64, CU_TENSOR_MAP_SWIZZLE_128B);
  make_map(enc, &tin, d_in[6], 1376, 512, 32, 32, CU_TENSOR_MAP_SWIZZLE_64B);
  make_map(enc, &tsp, d_in[7], 2048, 2048, 64, 64, CU_TENSOR_MAP_SWIZZLE_128B);
  make_map(enc, &tout, d_in[9], 512, 688, 64, 64, CU_TENSOR_MAP_SWIZZLE_128B);
  Params prm;
  prm.gate_w = (const __nv_bfloat16*)d_in[10];
  prm.b_sp = (const __nv_bfloat16*)d_in[8];
  prm.w_out = (const __nv_bfloat16*)d_in[9];
  prm.wo = (const __nv_bfloat16*)d_in[4];
  prm.w_in = (const __nv_bfloat16*)d_in[6];
  prm.wq = (const __nv_bfloat16*)d_in[1];
  prm.wk = (const __nv_bfloat16*)d_in[2];
  prm.wv = (const __nv_bfloat16*)d_in[3];
  prm.mlo = 0x007F007Fu;
  prm.mhi = 0xFF80FF80u;
  prm.out = (__nv_bfloat16*)d_out;
  fused_kernel<<<NCTA, NTHREADS, SMEM_BYTES>>>(tx, tq, tin, tsp, tout, to, prm);
}
```

```cpp
#include <cuda_runtime.h>
#include <cuda.h>
#include <cuda_bf16.h>
#include <cuda_fp16.h>
#include <stdint.h>

namespace {

constexpr int NCTA = 128;
constexpr int NTHREADS = 640;
constexpr int NP = 40;
constexpr int NM = 64 - NP;
constexpr int SPIN_LIMIT = 1 << 18;

constexpr uint32_t SM_K = 0;
constexpr uint32_t SM_V = 65536;
constexpr uint32_t SM_ONES = 131072;
constexpr uint32_t KV_BYTES = 131072;
constexpr uint32_t SM_BAR = 131584;
constexpr uint32_t SM_RING = 132096;
constexpr uint32_t RSTAGE = 27648;
constexpr uint32_t WSLOT = 16384;
constexpr uint32_t SM_WKV = SM_RING + 4 * WSLOT;
constexpr uint32_t SM_GW = SM_WKV + 16384;
constexpr uint32_t SM_Q = 215040;
constexpr uint32_t SM_G = 231424;
constexpr uint32_t SM_MISC = 231936;
constexpr uint32_t SMEM_BYTES = 232448;

constexpr int B_XFULL = 0, B_XEMPTY = 8, B_WFULL = 16, B_WEMPTY = 32, B_RFULL = 44, B_REMPTY = 47, B_KVFULL = 50,
              B_KFB = 51, B_KSTAT = 52, B_DEC = 53, B_WOFULL = 54, B_EPOCH = 55, B_ZOK = 56, B_Z1OK = 57, B_ATT = 58, B_QRDY = 59;
constexpr int M_EPOCH = 0, M_KN2 = 1, M_VOK = 2, M_FAST = 3, M_KVR = 4, M_RED = 16;

__device__ uint4 g_kimg[KV_BYTES / 16];
__device__ uint4 g_kbf[65536 / 16];
__device__ unsigned long long g_kvflag[NCTA];
__device__ uint4 g_lnstat[16 * 8 * 128];
__device__ float g_gate[2048];
__device__ uint4 g_z2n[8 * 32 * 11264 / 16];
__device__ uint4 g_z1[16 * 88 * 128];
__device__ uint4 g_u[16 * 11 * 1024];
__device__ uint4 g_o[16 * 8 * 1024];
__device__ float4 g_part[NCTA * 2 * 3 * 128];
__device__ unsigned g_ticket;
__device__ unsigned g_zcnt[32 * 32];
__device__ unsigned g_z1cnt[16 * 32];
__device__ unsigned g_ucnt[16 * 32];
__device__ unsigned g_ocnt[16 * 32];
#define TS(k) do { } while (0)

__device__ __forceinline__ void mbar_init(uint32_t a, uint32_t c) { asm volatile("mbarrier.init.shared::cta.b64 [%0], %1;" ::"r"(a), "r"(c) : "memory"); }
__device__ __forceinline__ void mbar_expect(uint32_t a, uint32_t b) { asm volatile("mbarrier.arrive.expect_tx.shared::cta.b64 _, [%0], %1;" ::"r"(a), "r"(b) : "memory"); }
__device__ __forceinline__ void mbar_arrive(uint32_t a) { asm volatile("mbarrier.arrive.shared::cta.b64 _, [%0];" ::"r"(a) : "memory"); }
__device__ __forceinline__ void mbar_arrive_both(uint32_t a) {
  asm volatile("{\n.reg .b32 ra;\nmapa.shared::cluster.u32 ra, %0, 0;\nmbarrier.arrive.shared::cluster.b64 _, [ra];\n"
               "mapa.shared::cluster.u32 ra, %0, 1;\nmbarrier.arrive.shared::cluster.b64 _, [ra];\n}" ::"r"(a) : "memory");
}
__device__ __forceinline__ void mbar_wait(uint32_t a, uint32_t ph) {
  uint32_t ok;
#pragma unroll 1
  for (int n = 0; n < SPIN_LIMIT; n++) {
    asm volatile("{\n.reg .pred p;\nmbarrier.try_wait.parity.shared::cta.b64 p, [%1], %2;\nselp.u32 %0, 1, 0, p;\n}" : "=r"(ok) : "r"(a), "r"(ph) : "memory");
    if (ok) break;
  }
}
__device__ __forceinline__ void tma2d(uint32_t dst, const CUtensorMap* tm, int c0, int c1, uint32_t bar) {
  asm volatile("cp.async.bulk.tensor.2d.shared::cluster.global.mbarrier::complete_tx::bytes [%0], [%1, {%3, %4}], [%2];"
               ::"r"(dst), "l"(tm), "r"(bar), "r"(c0), "r"(c1) : "memory");
}
__device__ __forceinline__ void tma2d_mc(uint32_t dst, const CUtensorMap* tm, int c0, int c1, uint32_t bar) {
  asm volatile("cp.async.bulk.tensor.2d.shared::cluster.global.mbarrier::complete_tx::bytes.multicast::cluster [%0], [%1, {%3, %4}], [%2], %5;"
               ::"r"(dst), "l"(tm), "r"(bar), "r"(c0), "r"(c1), "h"((uint16_t)3) : "memory");
}
__device__ __forceinline__ void tma2d_pf(const CUtensorMap* tm, int c0, int c1) {
  asm volatile("cp.async.bulk.prefetch.tensor.2d.L2.global [%0, {%1, %2}];" ::"l"(tm), "r"(c0), "r"(c1) : "memory");
}
__device__ __forceinline__ void bulk(uint32_t dst, const void* src, uint32_t bytes, uint32_t bar) {
  asm volatile("cp.async.bulk.shared::cluster.global.mbarrier::complete_tx::bytes [%0], [%1], %2, [%3];"
               ::"r"(dst), "l"(src), "r"(bytes), "r"(bar) : "memory");
}
__device__ __forceinline__ void bulk_mc(uint32_t dst, const void* src, uint32_t bytes, uint32_t bar) {
  asm volatile("cp.async.bulk.shared::cluster.global.mbarrier::complete_tx::bytes.multicast::cluster [%0], [%1], %2, [%3], %4;"
               ::"r"(dst), "l"(src), "r"(bytes), "r"(bar), "h"((uint16_t)3) : "memory");
}
__device__ __forceinline__ void l2_prefetch(const void* src, uint32_t bytes) { asm volatile("cp.async.bulk.prefetch.L2.global [%0], %1;" ::"l"(src), "r"(bytes) : "memory"); }
__device__ __forceinline__ void fence_async() { asm volatile("fence.proxy.async.global;" ::: "memory"); }
__device__ __forceinline__ void fence_async_smem() { asm volatile("fence.proxy.async.shared::cta;" ::: "memory"); }
__device__ __forceinline__ void bar_sync(int id, int n) { asm volatile("bar.sync %0, %1;" ::"r"(id), "r"(n) : "memory"); }
__device__ __forceinline__ void bar_arrive(int id, int n) { asm volatile("bar.arrive %0, %1;" ::"r"(id), "r"(n) : "memory"); }
__device__ __forceinline__ void red_release(unsigned* p) { asm volatile("red.release.gpu.global.add.u32 [%0], 1;" ::"l"(p) : "memory"); }
__device__ __forceinline__ void red_relaxed(unsigned* p) { asm volatile("red.relaxed.gpu.global.add.u32 [%0], 1;" ::"l"(p) : "memory"); }
__device__ __forceinline__ uint32_t ld_back(const void* p) { uint32_t v; asm volatile("ld.relaxed.gpu.global.u32 %0, [%1];" : "=r"(v) : "l"(p) : "memory"); return v; }
__device__ __forceinline__ void consume(uint32_t v, uint32_t sb) { if (v == 0xDEADBEEFu) asm volatile("st.shared.u32 [%0], %1;" ::"r"(sb + SM_MISC + 60), "r"(v) : "memory"); }
__device__ __forceinline__ unsigned ld_acquire(const unsigned* p) { unsigned v; asm volatile("ld.acquire.gpu.global.u32 %0, [%1];" : "=r"(v) : "l"(p) : "memory"); return v; }
__device__ __forceinline__ void wait_ge(const unsigned* p, unsigned target) {
#pragma unroll 1
  for (int n = 0; n < SPIN_LIMIT; n++) {
    if ((int)(ld_acquire(p) - target) >= 0) break;
    __nanosleep(100);
  }
}
__device__ __forceinline__ void wg_fence() { asm volatile("wgmma.fence.sync.aligned;" ::: "memory"); }
__device__ __forceinline__ void wg_commit() { asm volatile("wgmma.commit_group.sync.aligned;" ::: "memory"); }
template <int N> __device__ __forceinline__ void wg_wait() { asm volatile("wgmma.wait_group.sync.aligned %0;" ::"n"(N) : "memory"); }
template <int n> __device__ __forceinline__ void regfence(float (&d)[n]) {
#pragma unroll
  for (int i = 0; i < n; i++) asm volatile("" : "+f"(d[i])::"memory");
}
__device__ __forceinline__ uint64_t mkdesc(uint32_t addr, uint32_t lbo, uint32_t sbo, int swz) {
  return (uint64_t)((addr & 0x3FFFF) >> 4) | ((uint64_t)(lbo >> 4) << 16) | ((uint64_t)(sbo >> 4) << 32) | ((uint64_t)swz << 62);
}
__device__ __forceinline__ uint32_t pack_bf16(float lo, float hi) { uint32_t r; asm("cvt.rn.bf16x2.f32 %0, %1, %2;" : "=r"(r) : "f"(hi), "f"(lo)); return r; }
__device__ __forceinline__ uint32_t pack_f16(float lo, float hi) { uint32_t r; asm("cvt.rn.f16x2.f32 %0, %1, %2;" : "=r"(r) : "f"(hi), "f"(lo)); return r; }
__device__ __forceinline__ float bf_lo(uint32_t v) { return __uint_as_float(v << 16); }
__device__ __forceinline__ float bf_hi(uint32_t v) { return __uint_as_float(v & 0xFFFF0000u); }
__device__ __forceinline__ float ex2(float x) { float r; asm("ex2.approx.ftz.f32 %0, %1;" : "=f"(r) : "f"(x)); return r; }
__device__ __forceinline__ float gelu_tanh(float x) {
  float u = x * fmaf(x * x, 0.0356774081f, 0.7978845608f), t;
  asm("tanh.approx.f32 %0, %1;" : "=f"(t) : "f"(u));
  float h = 0.5f * x;
  return fmaf(h, t, h);
}
__device__ __forceinline__ void sts32(uint32_t a, uint32_t v) { asm volatile("st.shared.u32 [%0], %1;" ::"r"(a), "r"(v) : "memory"); }
__device__ __forceinline__ void sts16(uint32_t a, uint16_t v) { asm volatile("st.shared.u16 [%0], %1;" ::"r"(a), "h"(v) : "memory"); }
__device__ __forceinline__ void sts128(uint32_t a, uint32_t x, uint32_t y, uint32_t z, uint32_t w) { asm volatile("st.shared.v4.u32 [%0], {%1,%2,%3,%4};" ::"r"(a), "r"(x), "r"(y), "r"(z), "r"(w) : "memory"); }
__device__ __forceinline__ uint32_t lds32(uint32_t a) { uint32_t v; asm volatile("ld.shared.u32 %0, [%1];" : "=r"(v) : "r"(a) : "memory"); return v; }
__device__ __forceinline__ float ldsf(uint32_t a) { return __uint_as_float(lds32(a)); }
__device__ __forceinline__ uint4 lds128(uint32_t a) { uint4 v; asm volatile("ld.shared.v4.u32 {%0,%1,%2,%3}, [%4];" : "=r"(v.x), "=r"(v.y), "=r"(v.z), "=r"(v.w) : "r"(a) : "memory"); return v; }

template<int OFF, int TOT> __device__ __forceinline__ void wg_ss_n88(float (&d)[TOT], uint64_t da, uint64_t db) {
  asm volatile("wgmma.mma_async.sync.aligned.m64n88k16.f32.bf16.bf16 {%0, %1, %2, %3, %4, %5, %6, %7, %8, %9, %10, %11, %12, %13, %14, %15, %16, %17, %18, %19, %20, %21, %22, %23, %24, %25, %26, %27, %28, %29, %30, %31, %32, %33, %34, %35, %36, %37, %38, %39, %40, %41, %42, %43}, %44, %45, 1, 1, 1, 0, 1;"
    : "+f"(d[OFF+0]), "+f"(d[OFF+1]), "+f"(d[OFF+2]), "+f"(d[OFF+3]), "+f"(d[OFF+4]), "+f"(d[OFF+5]), "+f"(d[OFF+6]), "+f"(d[OFF+7]),
      "+f"(d[OFF+8]), "+f"(d[OFF+9]), "+f"(d[OFF+10]), "+f"(d[OFF+11]), "+f"(d[OFF+12]), "+f"(d[OFF+13]), "+f"(d[OFF+14]), "+f"(d[OFF+15]),
      "+f"(d[OFF+16]), "+f"(d[OFF+17]), "+f"(d[OFF+18]), "+f"(d[OFF+19]), "+f"(d[OFF+20]), "+f"(d[OFF+21]), "+f"(d[OFF+22]), "+f"(d[OFF+23]),
      "+f"(d[OFF+24]), "+f"(d[OFF+25]), "+f"(d[OFF+26]), "+f"(d[OFF+27]), "+f"(d[OFF+28]), "+f"(d[OFF+29]), "+f"(d[OFF+30]), "+f"(d[OFF+31]),
      "+f"(d[OFF+32]), "+f"(d[OFF+33]), "+f"(d[OFF+34]), "+f"(d[OFF+35]), "+f"(d[OFF+36]), "+f"(d[OFF+37]), "+f"(d[OFF+38]), "+f"(d[OFF+39]),
      "+f"(d[OFF+40]), "+f"(d[OFF+41]), "+f"(d[OFF+42]), "+f"(d[OFF+43])
    : "l"(da), "l"(db));
}
template<int OFF, int TOT> __device__ __forceinline__ void wg_ss_n128(float (&d)[TOT], uint64_t da, uint64_t db) {
  asm volatile("wgmma.mma_async.sync.aligned.m64n128k16.f32.bf16.bf16 {%0, %1, %2, %3, %4, %5, %6, %7, %8, %9, %10, %11, %12, %13, %14, %15, %16, %17, %18, %19, %20, %21, %22, %23, %24, %25, %26, %27, %28, %29, %30, %31, %32, %33, %34, %35, %36, %37, %38, %39, %40, %41, %42, %43, %44, %45, %46, %47, %48, %49, %50, %51, %52, %53, %54, %55, %56, %57, %58, %59, %60, %61, %62, %63}, %64, %65, 1, 1, 1, 0, 1;"
    : "+f"(d[OFF+0]), "+f"(d[OFF+1]), "+f"(d[OFF+2]), "+f"(d[OFF+3]), "+f"(d[OFF+4]), "+f"(d[OFF+5]), "+f"(d[OFF+6]), "+f"(d[OFF+7]),
      "+f"(d[OFF+8]), "+f"(d[OFF+9]), "+f"(d[OFF+10]), "+f"(d[OFF+11]), "+f"(d[OFF+12]), "+f"(d[OFF+13]), "+f"(d[OFF+14]), "+f"(d[OFF+15]),
      "+f"(d[OFF+16]), "+f"(d[OFF+17]), "+f"(d[OFF+18]), "+f"(d[OFF+19]), "+f"(d[OFF+20]), "+f"(d[OFF+21]), "+f"(d[OFF+22]), "+f"(d[OFF+23]),
      "+f"(d[OFF+24]), "+f"(d[OFF+25]), "+f"(d[OFF+26]), "+f"(d[OFF+27]), "+f"(d[OFF+28]), "+f"(d[OFF+29]), "+f"(d[OFF+30]), "+f"(d[OFF+31]),
      "+f"(d[OFF+32]), "+f"(d[OFF+33]), "+f"(d[OFF+34]), "+f"(d[OFF+35]), "+f"(d[OFF+36]), "+f"(d[OFF+37]), "+f"(d[OFF+38]), "+f"(d[OFF+39]),
      "+f"(d[OFF+40]), "+f"(d[OFF+41]), "+f"(d[OFF+42]), "+f"(d[OFF+43]), "+f"(d[OFF+44]), "+f"(d[OFF+45]), "+f"(d[OFF+46]), "+f"(d[OFF+47]),
      "+f"(d[OFF+48]), "+f"(d[OFF+49]), "+f"(d[OFF+50]), "+f"(d[OFF+51]), "+f"(d[OFF+52]), "+f"(d[OFF+53]), "+f"(d[OFF+54]), "+f"(d[OFF+55]),
      "+f"(d[OFF+56]), "+f"(d[OFF+57]), "+f"(d[OFF+58]), "+f"(d[OFF+59]), "+f"(d[OFF+60]), "+f"(d[OFF+61]), "+f"(d[OFF+62]), "+f"(d[OFF+63])
    : "l"(da), "l"(db));
}
template<int OFF, int TOT> __device__ __forceinline__ void wg_ss_n64(float (&d)[TOT], uint64_t da, uint64_t db) {
  asm volatile("wgmma.mma_async.sync.aligned.m64n64k16.f32.bf16.bf16 {%0, %1, %2, %3, %4, %5, %6, %7, %8, %9, %10, %11, %12, %13, %14, %15, %16, %17, %18, %19, %20, %21, %22, %23, %24, %25, %26, %27, %28, %29, %30, %31}, %32, %33, 1, 1, 1, 0, 1;"
    : "+f"(d[OFF+0]), "+f"(d[OFF+1]), "+f"(d[OFF+2]), "+f"(d[OFF+3]), "+f"(d[OFF+4]), "+f"(d[OFF+5]), "+f"(d[OFF+6]), "+f"(d[OFF+7]),
      "+f"(d[OFF+8]), "+f"(d[OFF+9]), "+f"(d[OFF+10]), "+f"(d[OFF+11]), "+f"(d[OFF+12]), "+f"(d[OFF+13]), "+f"(d[OFF+14]), "+f"(d[OFF+15]),
      "+f"(d[OFF+16]), "+f"(d[OFF+17]), "+f"(d[OFF+18]), "+f"(d[OFF+19]), "+f"(d[OFF+20]), "+f"(d[OFF+21]), "+f"(d[OFF+22]), "+f"(d[OFF+23]),
      "+f"(d[OFF+24]), "+f"(d[OFF+25]), "+f"(d[OFF+26]), "+f"(d[OFF+27]), "+f"(d[OFF+28]), "+f"(d[OFF+29]), "+f"(d[OFF+30]), "+f"(d[OFF+31])
    : "l"(da), "l"(db));
}
template<int OFF, int TOT> __device__ __forceinline__ void wg_ss_n32t(float (&d)[TOT], uint64_t da, uint64_t db) {
  asm volatile("wgmma.mma_async.sync.aligned.m64n32k16.f32.bf16.bf16 {%0, %1, %2, %3, %4, %5, %6, %7, %8, %9, %10, %11, %12, %13, %14, %15}, %16, %17, 1, 1, 1, 1, 0;"
    : "+f"(d[OFF+0]), "+f"(d[OFF+1]), "+f"(d[OFF+2]), "+f"(d[OFF+3]), "+f"(d[OFF+4]), "+f"(d[OFF+5]), "+f"(d[OFF+6]), "+f"(d[OFF+7]),
      "+f"(d[OFF+8]), "+f"(d[OFF+9]), "+f"(d[OFF+10]), "+f"(d[OFF+11]), "+f"(d[OFF+12]), "+f"(d[OFF+13]), "+f"(d[OFF+14]), "+f"(d[OFF+15])
    : "l"(da), "l"(db));
}
template<int SCD, int OFF, int TOT> __device__ __forceinline__ void wg_qk_n16(float (&d)[TOT], uint32_t a0, uint32_t a1, uint32_t a2, uint32_t a3, uint64_t db) {
  asm volatile("wgmma.mma_async.sync.aligned.m64n16k16.f32.f16.f16 {%0, %1, %2, %3, %4, %5, %6, %7}, {%8,%9,%10,%11}, %12, %13, 1, 1, 0;"
    : "+f"(d[OFF+0]), "+f"(d[OFF+1]), "+f"(d[OFF+2]), "+f"(d[OFF+3]), "+f"(d[OFF+4]), "+f"(d[OFF+5]), "+f"(d[OFF+6]), "+f"(d[OFF+7])
    : "r"(a0), "r"(a1), "r"(a2), "r"(a3), "l"(db), "n"(SCD));
}
template<int SCD, int OFF, int TOT> __device__ __forceinline__ void wg_qk_n24(float (&d)[TOT], uint32_t a0, uint32_t a1, uint32_t a2, uint32_t a3, uint64_t db) {
  asm volatile("wgmma.mma_async.sync.aligned.m64n24k16.f32.f16.f16 {%0, %1, %2, %3, %4, %5, %6, %7, %8, %9, %10, %11}, {%12,%13,%14,%15}, %16, %17, 1, 1, 0;"
    : "+f"(d[OFF+0]), "+f"(d[OFF+1]), "+f"(d[OFF+2]), "+f"(d[OFF+3]), "+f"(d[OFF+4]), "+f"(d[OFF+5]), "+f"(d[OFF+6]), "+f"(d[OFF+7]),
      "+f"(d[OFF+8]), "+f"(d[OFF+9]), "+f"(d[OFF+10]), "+f"(d[OFF+11])
    : "r"(a0), "r"(a1), "r"(a2), "r"(a3), "l"(db), "n"(SCD));
}
template<int SCD, int OFF, int TOT> __device__ __forceinline__ void wg_qk_n32(float (&d)[TOT], uint32_t a0, uint32_t a1, uint32_t a2, uint32_t a3, uint64_t db) {
  asm volatile("wgmma.mma_async.sync.aligned.m64n32k16.f32.f16.f16 {%0, %1, %2, %3, %4, %5, %6, %7, %8, %9, %10, %11, %12, %13, %14, %15}, {%16,%17,%18,%19}, %20, %21, 1, 1, 0;"
    : "+f"(d[OFF+0]), "+f"(d[OFF+1]), "+f"(d[OFF+2]), "+f"(d[OFF+3]), "+f"(d[OFF+4]), "+f"(d[OFF+5]), "+f"(d[OFF+6]), "+f"(d[OFF+7]),
      "+f"(d[OFF+8]), "+f"(d[OFF+9]), "+f"(d[OFF+10]), "+f"(d[OFF+11]), "+f"(d[OFF+12]), "+f"(d[OFF+13]), "+f"(d[OFF+14]), "+f"(d[OFF+15])
    : "r"(a0), "r"(a1), "r"(a2), "r"(a3), "l"(db), "n"(SCD));
}
template<int SCD, int OFF, int TOT> __device__ __forceinline__ void wg_qk_n40(float (&d)[TOT], uint32_t a0, uint32_t a1, uint32_t a2, uint32_t a3, uint64_t db) {
  asm volatile("wgmma.mma_async.sync.aligned.m64n40k16.f32.f16.f16 {%0, %1, %2, %3, %4, %5, %6, %7, %8, %9, %10, %11, %12, %13, %14, %15, %16, %17, %18, %19}, {%20,%21,%22,%23}, %24, %25, 1, 1, 0;"
    : "+f"(d[OFF+0]), "+f"(d[OFF+1]), "+f"(d[OFF+2]), "+f"(d[OFF+3]), "+f"(d[OFF+4]), "+f"(d[OFF+5]), "+f"(d[OFF+6]), "+f"(d[OFF+7]),
      "+f"(d[OFF+8]), "+f"(d[OFF+9]), "+f"(d[OFF+10]), "+f"(d[OFF+11]), "+f"(d[OFF+12]), "+f"(d[OFF+13]), "+f"(d[OFF+14]), "+f"(d[OFF+15]),
      "+f"(d[OFF+16]), "+f"(d[OFF+17]), "+f"(d[OFF+18]), "+f"(d[OFF+19])
    : "r"(a0), "r"(a1), "r"(a2), "r"(a3), "l"(db), "n"(SCD));
}
template<int SCD, int OFF, int TOT> __device__ __forceinline__ void wg_qk_n48(float (&d)[TOT], uint32_t a0, uint32_t a1, uint32_t a2, uint32_t a3, uint64_t db) {
  asm volatile("wgmma.mma_async.sync.aligned.m64n48k16.f32.f16.f16 {%0, %1, %2, %3, %4, %5, %6, %7, %8, %9, %10, %11, %12, %13, %14, %15, %16, %17, %18, %19, %20, %21, %22, %23}, {%24,%25,%26,%27}, %28, %29, 1, 1, 0;"
    : "+f"(d[OFF+0]), "+f"(d[OFF+1]), "+f"(d[OFF+2]), "+f"(d[OFF+3]), "+f"(d[OFF+4]), "+f"(d[OFF+5]), "+f"(d[OFF+6]), "+f"(d[OFF+7]),
      "+f"(d[OFF+8]), "+f"(d[OFF+9]), "+f"(d[OFF+10]), "+f"(d[OFF+11]), "+f"(d[OFF+12]), "+f"(d[OFF+13]), "+f"(d[OFF+14]), "+f"(d[OFF+15]),
      "+f"(d[OFF+16]), "+f"(d[OFF+17]), "+f"(d[OFF+18]), "+f"(d[OFF+19]), "+f"(d[OFF+20]), "+f"(d[OFF+21]), "+f"(d[OFF+22]), "+f"(d[OFF+23])
    : "r"(a0), "r"(a1), "r"(a2), "r"(a3), "l"(db), "n"(SCD));
}
template<int SCD, int OFF, int TOT> __device__ __forceinline__ void wg_pv_n24(float (&d)[TOT], uint32_t a0, uint32_t a1, uint32_t a2, uint32_t a3, uint64_t db) {
  asm volatile("wgmma.mma_async.sync.aligned.m64n24k16.f32.bf16.bf16 {%0, %1, %2, %3, %4, %5, %6, %7, %8, %9, %10, %11}, {%12,%13,%14,%15}, %16, %17, 1, 1, 1;"
    : "+f"(d[OFF+0]), "+f"(d[OFF+1]), "+f"(d[OFF+2]), "+f"(d[OFF+3]), "+f"(d[OFF+4]), "+f"(d[OFF+5]), "+f"(d[OFF+6]), "+f"(d[OFF+7]),
      "+f"(d[OFF+8]), "+f"(d[OFF+9]), "+f"(d[OFF+10]), "+f"(d[OFF+11])
    : "r"(a0), "r"(a1), "r"(a2), "r"(a3), "l"(db), "n"(SCD));
}
template<int SCD, int OFF, int TOT> __device__ __forceinline__ void wg_qkb_n64(float (&d)[TOT], uint32_t a0, uint32_t a1, uint32_t a2, uint32_t a3, uint64_t db) {
  asm volatile("wgmma.mma_async.sync.aligned.m64n64k16.f32.bf16.bf16 {%0, %1, %2, %3, %4, %5, %6, %7, %8, %9, %10, %11, %12, %13, %14, %15, %16, %17, %18, %19, %20, %21, %22, %23, %24, %25, %26, %27, %28, %29, %30, %31}, {%32,%33,%34,%35}, %36, %37, 1, 1, 0;"
    : "+f"(d[OFF+0]), "+f"(d[OFF+1]), "+f"(d[OFF+2]), "+f"(d[OFF+3]), "+f"(d[OFF+4]), "+f"(d[OFF+5]), "+f"(d[OFF+6]), "+f"(d[OFF+7]),
      "+f"(d[OFF+8]), "+f"(d[OFF+9]), "+f"(d[OFF+10]), "+f"(d[OFF+11]), "+f"(d[OFF+12]), "+f"(d[OFF+13]), "+f"(d[OFF+14]), "+f"(d[OFF+15]),
      "+f"(d[OFF+16]), "+f"(d[OFF+17]), "+f"(d[OFF+18]), "+f"(d[OFF+19]), "+f"(d[OFF+20]), "+f"(d[OFF+21]), "+f"(d[OFF+22]), "+f"(d[OFF+23]),
      "+f"(d[OFF+24]), "+f"(d[OFF+25]), "+f"(d[OFF+26]), "+f"(d[OFF+27]), "+f"(d[OFF+28]), "+f"(d[OFF+29]), "+f"(d[OFF+30]), "+f"(d[OFF+31])
    : "r"(a0), "r"(a1), "r"(a2), "r"(a3), "l"(db), "n"(SCD));
}
template<int N, int SCD, int OFF, int TOT> __device__ __forceinline__ void wg_qk(float (&d)[TOT], const uint32_t (&q)[4], uint64_t db) {
  if constexpr (N == 16) wg_qk_n16<SCD, OFF, TOT>(d, q[0], q[1], q[2], q[3], db);
  if constexpr (N == 24) wg_qk_n24<SCD, OFF, TOT>(d, q[0], q[1], q[2], q[3], db);
  if constexpr (N == 32) wg_qk_n32<SCD, OFF, TOT>(d, q[0], q[1], q[2], q[3], db);
  if constexpr (N == 40) wg_qk_n40<SCD, OFF, TOT>(d, q[0], q[1], q[2], q[3], db);
  if constexpr (N == 48) wg_qk_n48<SCD, OFF, TOT>(d, q[0], q[1], q[2], q[3], db);
}

__device__ __forceinline__ uint32_t exp_mufu(float a, float b) { return pack_bf16(ex2(a), ex2(b)); }
__device__ __forceinline__ uint32_t exp_poly(float a, float b, uint32_t mlo, uint32_t mhi) {
  uint32_t u = __byte_perm(__float_as_uint(a), __float_as_uint(b), 0x6521), mh, e, p;
  asm("lop3.b32 %0, %1, %2, 0x3F003F00, 0xEA;" : "=r"(mh) : "r"(u), "r"(mlo));
  asm("lop3.b32 %0, %1, %2, 0x00020002, 0xEA;" : "=r"(e) : "r"(u), "r"(mhi));
  asm("fma.rn.bf16x2 %0, %1, %2, %3;" : "=r"(p) : "r"(u), "r"(mh), "r"(e));
  return p;
}
constexpr float MAGIC_C = 48948.0625f;
constexpr float QSCALE = 0.25f * 1.4426950408889634f * 8.f;
constexpr float BOUND = 80.f;

__device__ __forceinline__ void softmax_step(const float (&s)[32], uint32_t (&p)[16], uint32_t mlo, uint32_t mhi) {
  constexpr int PP = NP / 4;
  int ip = 0, im = PP;
#pragma unroll
  for (int i = 0; i < 16; i++) {
    if (((i + 1) * PP / 16) > (i * PP / 16)) { p[ip] = exp_poly(s[2 * ip], s[2 * ip + 1], mlo, mhi); ip++; }
    else { p[im] = exp_mufu(s[2 * im], s[2 * im + 1]); im++; }
  }
}
constexpr int64_t VSTEP = 32 - (32 << 16);
__device__ __forceinline__ void issue_qk(float (&s)[32], const uint32_t (&q)[4], uint64_t dk) {
  wg_qk<NM, 0, NP / 2, 32>(s, q, dk + NP * 2);
  wg_qk<NP, 1, 0, 32>(s, q, dk);
}
__device__ __forceinline__ void issue_pv(float (&o)[12], const uint32_t (&p)[16], uint64_t dv) {
#pragma unroll
  for (int c = 0; c < 4; c++) { wg_pv_n24<1, 0, 12>(o, p[4 * c], p[4 * c + 1], p[4 * c + 2], p[4 * c + 3], dv + c * VSTEP); }
}

__device__ __forceinline__ uint32_t wslot(int f) { const int r = f - 5 * ((f * 52) >> 8); return r == 4 ? SM_Q : SM_RING + r * WSLOT; }

struct Params {
  const __nv_bfloat16* gate_w;
  const __nv_bfloat16* b_sp;
  const __nv_bfloat16* w_out;
  const __nv_bfloat16* wo;
  const __nv_bfloat16* w_in;
  const __nv_bfloat16* wq;
  const __nv_bfloat16* wk;
  const __nv_bfloat16* wv;
  uint32_t mlo, mhi;
  __nv_bfloat16* out;
};

__device__ __forceinline__ uint32_t store_o_tile(const float (&o)[12], int bi, int bj, int tau, int tid, uint32_t sb) {
  const int half = tau & 1, hh = tau >> 1, w = tid >> 5, l = tid & 31;
  const int r0 = half * 64 + w * 16 + (l >> 2);
  const float f0 = __fdividef(ldsf(sb + SM_G + r0 * 4), o[8]), f1 = __fdividef(ldsf(sb + SM_G + (r0 + 8) * 4), o[10]);
  uint32_t* dst = reinterpret_cast<uint32_t*>(g_o) + (bi * 8 + bj) * 4096 + (half * 8 + w * 2) * 256 + hh * 64;
  dst[l] = pack_bf16(o[0] * f0, o[1] * f0);
  dst[l + 32] = pack_bf16(o[4] * f0, o[5] * f0);
  dst[l + 256] = pack_bf16(o[2] * f1, o[3] * f1);
  dst[l + 288] = pack_bf16(o[6] * f1, o[7] * f1);
  return ld_back(dst + ((l >> 3) & 1) * 256 + (l & 7) * 8);
}

__global__ void __cluster_dims__(2, 1, 1) __launch_bounds__(NTHREADS, 1)
fused_kernel(const __grid_constant__ CUtensorMap tm_x, const __grid_constant__ CUtensorMap tm_wq,
             const __grid_constant__ CUtensorMap tm_win, const __grid_constant__ CUtensorMap tm_wsp,
             const __grid_constant__ CUtensorMap tm_wout, const __grid_constant__ CUtensorMap tm_wo, const Params prm) {
  extern __shared__ __align__(1024) uint8_t smem_raw[];
  const uint32_t sb = (uint32_t)__cvta_generic_to_shared(smem_raw);
  const int warp = __shfl_sync(0xffffffffu, (int)(threadIdx.x >> 5), 0);
  const int wg = warp >> 2;
  const int tid = threadIdx.x & 127;
  const int lane = threadIdx.x & 31;
  const int rank = blockIdx.x & 1;
  const int ai = (blockIdx.x >> 4) * 2 + rank, aj = (blockIdx.x >> 1) & 7;
  const int bi = blockIdx.x >> 3, bj = blockIdx.x & 7;
  auto BAR = [&](int k) { return sb + SM_BAR + 8u * k; };

  if (lane == 0) {
    if (warp == 16) {
      mbar_init(BAR(B_XFULL), 1); mbar_init(BAR(B_XFULL + 1), 1);
      asm volatile("fence.mbarrier_init.release.cluster;" ::: "memory");
      mbar_expect(BAR(B_XFULL), 16384);
      tma2d(sb + SM_K, &tm_x, 0, ai * 128, BAR(B_XFULL));
      mbar_expect(BAR(B_XFULL + 1), 16384);
      tma2d(sb + SM_K + 16384, &tm_x, 64, ai * 128, BAR(B_XFULL + 1));
      TS(36);
    } else if (warp == 18) {
      asm volatile("prefetch.tensormap [%0];" ::"l"(&tm_win) : "memory");
      asm volatile("prefetch.tensormap [%0];" ::"l"(&tm_wq) : "memory");
    } else if (warp == 19) {
      l2_prefetch(reinterpret_cast<const uint8_t*>(prm.w_in) + blockIdx.x * 11008, 11008);
      l2_prefetch(reinterpret_cast<const uint8_t*>(prm.wq) + blockIdx.x * 4096, 4096);
    } else if (warp < 16) {
#pragma unroll
      for (int r = 0; r < 4; r++) {
        const int k = warp + 16 * r;
        uint32_t cnt = 1;
        if (k >= B_XEMPTY && k < B_XEMPTY + 8) cnt = 4;
        if (k >= B_WEMPTY && k < B_WEMPTY + 12) cnt = 4;
        if (k >= B_REMPTY && k < B_REMPTY + 3) cnt = 2;
        if (k == B_ATT) cnt = 6;
        if (k == B_QRDY) cnt = 16;
        if (k == B_KSTAT) cnt = 17;
        if (k >= 2) mbar_init(BAR(k), cnt);
      }
      asm volatile("fence.mbarrier_init.release.cluster;" ::: "memory");
    }
  }
  __syncthreads();
  if (threadIdx.x == 0) TS(35);
  asm volatile("barrier.cluster.arrive.relaxed.aligned;" ::: "memory");
  asm volatile("barrier.cluster.wait.acquire.aligned;" ::: "memory");

  if (wg == 4) {
    asm volatile("setmaxnreg.dec.sync.aligned.u32 24;");
    if (warp == 18) {
      if (lane == 0) {
#pragma unroll 1
        for (int f = 0; f < 16; f++) {
          if (f == 0) TS(0);
          if (f == 5) TS(37);
          if (f >= 5) mbar_wait(BAR(B_WEMPTY + f - 5), 0);
          const uint32_t dst = sb + wslot(f) + rank * 2048, bar = BAR(B_WFULL + f);
          const int k0 = (f & 7) * 64 + rank * 32;
          const bool three = f < 8 ? aj < 6 : aj >= 2;
          const int c0 = 32 * (f < 8 ? (aj < 6 ? 21 + 3 * aj : 27 + 2 * aj) : (aj < 2 ? 2 * aj : 3 * aj - 2));
          mbar_expect(bar, three ? 16384 : 12288);
          tma2d_mc(dst, &tm_win, c0, k0, bar);
          tma2d_mc(dst + 4096, &tm_win, c0 + 32, k0, bar);
          if (three) tma2d_mc(dst + 8192, &tm_win, c0 + 64, k0, bar);
          tma2d_mc(dst + 12288, &tm_wq, 64 * aj + (f >> 3) * 32, k0, bar);
          if (f < 6) {
            mbar_expect(BAR(B_XFULL + 2 + f), 16384);
            tma2d(sb + SM_K + (f + 2) * 16384, &tm_x, (f + 2) * 64, ai * 128, BAR(B_XFULL + 2 + f));
          }
        }
        TS(1);
      }
    } else if (warp == 19) {
      mbar_wait(BAR(B_XEMPTY + 6), 0);
      const unsigned ep1 = lds32(sb + SM_MISC + 4 * M_EPOCH) + 1;
      wait_ge(&g_zcnt[lane * 32], ep1 * 8);
      __syncwarp();
      if (lane == 0) {
        mbar_arrive(BAR(B_ZOK));
        wait_ge(&g_z1cnt[bi * 32], ep1 * 16);
        mbar_arrive(BAR(B_Z1OK));
      }
    } else if (warp == 16) {
      if (lane == 0) {
        asm volatile("prefetch.tensormap [%0];" ::"l"(&tm_wsp) : "memory");
        asm volatile("prefetch.tensormap [%0];" ::"l"(&tm_wout) : "memory");
        asm volatile("prefetch.tensormap [%0];" ::"l"(&tm_wo) : "memory");
        const int row = bi * 128 + rank * 64;
        mbar_wait(BAR(B_XEMPTY), 0);
        tma2d_pf(&tm_wsp, (bj >> 1) * 64, row);
        tma2d_pf(&tm_wsp, (bj >> 1) * 64 + 256, row);
        mbar_wait(BAR(B_XEMPTY + 7), 0);
        mbar_wait(BAR(B_ZOK), 0);
        const unsigned ep1 = lds32(sb + SM_MISC + 4 * M_EPOCH) + 1;
        fence_async();
        TS(2);
        int st = 0, ph = 1;
#pragma unroll 1
        for (int n = 0; n < 46; n++) {
          const uint32_t stg = sb + SM_RING + st * RSTAGE, bar = BAR(B_RFULL + st);
          if (n >= 3) mbar_wait(BAR(B_REMPTY + st), ph);
          if (n < 32) {
            mbar_expect(bar, 16384 + 11264);
            tma2d_mc(stg + rank * 8192, &tm_wsp, n * 64, row, bar);
            bulk(stg + 16384, reinterpret_cast<const uint8_t*>(g_z2n) + (bj * 32 + n) * 11264, 11264, bar);
            if ((n & 3) == (bj >> 1) && n < 24) tma2d_pf(&tm_wsp, (n + 8) * 64, row);
            if (n == 16) {
              l2_prefetch(reinterpret_cast<const uint8_t*>(prm.w_out) + blockIdx.x * 5504, 5504);
              l2_prefetch(reinterpret_cast<const uint8_t*>(prm.wo) + blockIdx.x * 4096, 4096);
            }
          } else if (n < 43) {
            const int c = n - 32;
            mbar_expect(bar, 16384 + 8192);
            tma2d(stg + 16384, &tm_wout, 64 * bj, c * 64, bar);
            if (c == 0) { wait_ge(&g_ucnt[bi * 32], ep1 * 8); fence_async(); TS(3); }
            bulk_mc(stg + rank * 8192, reinterpret_cast<const uint8_t*>(g_u) + (bi * 11 + c) * 16384 + rank * 8192, 8192, bar);
          }
          if (++st == 3) { st = 0; ph ^= 1; }
        }
        mbar_expect(BAR(B_WOFULL), 65536);
#pragma unroll 1
        for (int c = 0; c < 8; c++) tma2d(sb + SM_RING + c * 8192, &tm_wo, 64 * bj, c * 64, BAR(B_WOFULL));
        TS(4);
        wait_ge(&g_ocnt[bi * 32], ep1 * 24);
        mbar_wait(BAR(B_ATT), 0);
        fence_async();
        TS(5);
#pragma unroll 1
        for (int c = 0; c < 8; c++) {
          mbar_expect(BAR(B_XFULL + c), 16384);
          bulk_mc(sb + SM_K + c * 16384 + rank * 8192, reinterpret_cast<const uint8_t*>(g_o) + (bi * 8 + c) * 16384 + rank * 8192, 8192, BAR(B_XFULL + c));
        }
      }
    } else {
      if (lane == 0) {
        sts32(sb + SM_MISC + 4 * M_EPOCH, atomicAdd(&g_ticket, 1u) / NCTA);
        mbar_arrive(BAR(B_EPOCH));
        TS(71);
      }
      __syncwarp();
      const unsigned ep1 = lds32(sb + SM_MISC + 4 * M_EPOCH) + 1;
      mbar_wait(BAR(B_WFULL + 8), 0);
      uint32_t kn = 0, vb = 0;
#pragma unroll 1
      for (int n = 0; n < SPIN_LIMIT; n++) {
        unsigned long long a, b, c, d;
        asm volatile("ld.relaxed.gpu.global.v2.b64 {%0, %1}, [%2];" : "=l"(a), "=l"(b) : "l"(&g_kvflag[2 * lane]) : "memory");
        asm volatile("ld.relaxed.gpu.global.v2.b64 {%0, %1}, [%2];" : "=l"(c), "=l"(d) : "l"(&g_kvflag[64 + 2 * lane]) : "memory");
        kn = max((uint32_t)a, (uint32_t)c); vb = (uint32_t)b | (uint32_t)d;
        if (__all_sync(0xffffffffu, (uint32_t)(a >> 32) == ep1 && (uint32_t)(b >> 32) == ep1 && (uint32_t)(c >> 32) == ep1 && (uint32_t)(d >> 32) == ep1)) break;
        __nanosleep(100);
      }
      asm volatile("fence.acquire.gpu;" ::: "memory");
      kn = __reduce_max_sync(0xffffffffu, kn);
      vb = __reduce_or_sync(0xffffffffu, vb);
      if (lane == 0) {
        TS(6);
        sts32(sb + SM_MISC + 4 * M_KN2, kn);
        sts32(sb + SM_MISC + 4 * M_VOK, vb == 0xFFFFu ? 1u : 0u);
        mbar_arrive(BAR(B_KSTAT));
        mbar_expect(BAR(B_KVFULL), KV_BYTES);
        fence_async();
#pragma unroll 1
        for (int c = 0; c < 8; c++) {
          const uint32_t off = c * 16384 + rank * 8192;
          mbar_wait(BAR(B_XEMPTY + c), 0);
          bulk_mc(sb + SM_K + off, reinterpret_cast<const uint8_t*>(g_kimg) + off, 8192, BAR(B_KVFULL));
        }
        TS(7);
        mbar_wait(BAR(B_DEC), 0);
        if (!lds32(sb + SM_MISC + 4 * M_FAST)) {
          mbar_wait(BAR(B_KVFULL), 0);
          mbar_expect(BAR(B_KFB), 65536);
          bulk(sb + SM_K, g_kbf, 65536, BAR(B_KFB));
        }
      }
    }
  } else {
    asm volatile("setmaxnreg.inc.sync.aligned.u32 112;");
    const int w = tid >> 5, g = lane >> 2, t4 = lane & 3, half = wg & 1;
    {
      float acc[64];
      if (wg == 2) {
        const int slot = ai * 4 + (aj >> 1), isv = aj & 1;
        const uint4* wsrc = reinterpret_cast<const uint4*>(isv ? prm.wv : prm.wk) + tid;
        uint4 wr[8];
#pragma unroll
        for (int r = 0; r < 8; r++) wr[r] = __ldg(wsrc + 128 * r);
#pragma unroll
        for (int r = 0; r < 8; r++) sts128(sb + SM_WKV + r * 2048 + (tid >> 1) * 32 + (((tid ^ (tid >> 3)) & 1) << 4), wr[r].x, wr[r].y, wr[r].z, wr[r].w);
        fence_async_smem();
        bar_sync(3, 128);
        float kv[16];
#pragma unroll
        for (int k = 0; k < 16; k++) kv[k] = 0.f;
        regfence(kv);
#pragma unroll 1
        for (int c = 0; c < 8; c++) {
          mbar_wait(BAR(B_XFULL + c), 0);
          const uint64_t da = mkdesc(sb + SM_WKV + c * 2048, 0, 256, 3);
          const uint64_t db = mkdesc(sb + SM_K + c * 16384 + (aj >> 1) * 4096, 16, 1024, 1);
          wg_fence();
#pragma unroll
          for (int k = 0; k < 4; k++) wg_ss_n32t<0, 16>(kv, da + 32 * k, db + 2 * k);
          wg_commit();
        }
        wg_wait<0>();
        regfence(kv);
        if (tid == 0) TS(22);
        const uint32_t sT = sb + SM_WKV, sH = sb + SM_WKV + 4096;
        bar_sync(3, 128);
        {
          const float a = w & 1 ? kv[4] : kv[0], b = w & 1 ? kv[5] : kv[1], c = w & 1 ? kv[6] : kv[2], d = w & 1 ? kv[7] : kv[3];
          const float e = w & 1 ? kv[12] : kv[8], f = w & 1 ? kv[13] : kv[9], h = w & 1 ? kv[14] : kv[10], i = w & 1 ? kv[15] : kv[11];
          const uint32_t lo = pack_bf16(w & 2 ? e : a, w & 2 ? f : b), hi = pack_bf16(w & 2 ? h : c, w & 2 ? i : d);
          const uint32_t p = sT + ((w * 8 + 2 * t4) * 17 + g) * 4;
          sts32(p, lo << 16); sts32(p + 68, lo & 0xFFFF0000u); sts32(p + 32, hi << 16); sts32(p + 100, hi & 0xFFFF0000u);
        }
        bar_sync(3, 128);
        if (tid == 0) TS(64);
        const int tok = (tid & 63) >> 1, hf = tid & 1;
        float f[8];
#pragma unroll
        for (int e = 0; e < 8; e++) f[e] = ldsf(sT + (tok * 17 + hf * 8 + e) * 4);
        uint4 val = make_uint4(pack_bf16(f[0], f[1]), pack_bf16(f[2], f[3]), pack_bf16(f[4], f[5]), pack_bf16(f[6], f[7]));
        uint32_t stat = 0;
        if (isv) {
#pragma unroll
          for (int e = 0; e < 8; e++) {
            if (fabsf(f[e]) >= 9.5367431640625e-07f) stat |= 1u << e;
            if (!(fabsf(f[e]) <= 1073741824.f)) stat |= 1u << (16 - 8 * hf);
          }
          stat = __reduce_or_sync(0xffffffffu, stat << (8 * hf));
        } else {
          float n2 = 0.f;
#pragma unroll
          for (int e = 0; e < 8; e++) n2 = fmaf(f[e], f[e], n2);
          n2 += __shfl_xor_sync(0xffffffffu, n2, 1);
          if (!(n2 <= 3.0e38f)) n2 = 3.0e38f;
          stat = __reduce_max_sync(0xffffffffu, __float_as_uint(n2));
          if (tid < 48) {
            const int d = tid & 15, sg = tid >> 4, j0 = sg == 0 ? 0 : (sg == 1 ? 10 : 22), j1 = sg == 0 ? 10 : (sg == 1 ? 22 : 32);
            const float sc = slot < NP ? 16.f : 0.125f, fb = slot < NP ? 1.f : 0.f;
            float kx[12], run = 0.f;
#pragma unroll
            for (int e = 0; e < 12; e++) kx[e] = ldsf(sT + (min(j0 + e, 31) * 17 + d) * 4);
#pragma unroll
            for (int e = 0; e < 12; e++) {
              const __half hv = __float2half_rn(fmaf(kx[e], sc, -run));
              run = fmaf(__half2float(hv), fb, run);
              if (j0 + e < j1) sts16(sH + ((j0 + e) * 16 + d) * 2, __half_as_ushort(hv));
            }
          }
        }
        if (lane == 0) sts32(sb + SM_MISC + 4 * (M_KVR + w), stat);
        bar_sync(3, 128);
        const uint32_t off = (isv ? SM_V / 16 : 0) + tok * 128 + slot * 2 + (hf ^ ((slot >> 2) & 1));
        uint4* dst = (tid < 64 ? g_kimg : g_kbf) + off;
        if (!isv && tid < 64) val = lds128(sH + tok * 32 + hf * 16);
        uint32_t chk = 0;
        if (tid < 64 || !isv) { *dst = val; chk = ld_back(dst); }
        mbar_wait(BAR(B_EPOCH), 0);
        consume(chk, sb);
        fence_async();
        bar_sync(3, 128);
        if (tid == 0) {
          const uint32_t s0 = lds32(sb + SM_MISC + 4 * M_KVR), s1 = lds32(sb + SM_MISC + 4 * (M_KVR + 1));
          const unsigned long long fl = ((unsigned long long)(lds32(sb + SM_MISC + 4 * M_EPOCH) + 1) << 32) | (isv ? (s0 | s1) : max(s0, s1));
          asm volatile("st.relaxed.gpu.global.b64 [%0], %1;" ::"l"(&g_kvflag[ai * 8 + aj]), "l"(fl) : "memory");
          TS(23);
        }
      } else if (wg == 3) {
        uint4* sW = reinterpret_cast<uint4*>(smem_raw + SM_GW);
        if (tid < 64) sW[tid] = __ldg(reinterpret_cast<const uint4*>(prm.gate_w) + tid);
        sts32(sb + SM_ONES + tid * 4, 0x3F803F80u);
        bar_sync(4, 128);
        const int v = tid & 7, rr = tid >> 3;
        float a[8];
#pragma unroll
        for (int p = 0; p < 8; p++) a[p] = 0.f;
#pragma unroll 1
        for (int c = 0; c < 8; c++) {
          const uint4 gv = sW[c * 8 + v];
          mbar_wait(BAR(B_XFULL + c), 0);
          if (tid == 0) TS(40 + c);
          const uint4* xr = reinterpret_cast<const uint4*>(smem_raw + SM_K + c * 16384 + rr * 128) + (v ^ (rr & 7));
#pragma unroll
          for (int p = 0; p < 8; p++) {
            const uint4 xv = xr[p * 128];
            float s = fmaf(bf_lo(xv.x), bf_lo(gv.x), a[p]), t = bf_hi(xv.x) * bf_hi(gv.x);
            s = fmaf(bf_lo(xv.y), bf_lo(gv.y), s); t = fmaf(bf_hi(xv.y), bf_hi(gv.y), t);
            s = fmaf(bf_lo(xv.z), bf_lo(gv.z), s); t = fmaf(bf_hi(xv.z), bf_hi(gv.z), t);
            s = fmaf(bf_lo(xv.w), bf_lo(gv.w), s); t = fmaf(bf_hi(xv.w), bf_hi(gv.w), t);
            a[p] = s + t;
          }
        }
        float mine = 0.f;
#pragma unroll
        for (int p = 0; p < 8; p++) {
          float s = a[p];
          s += __shfl_xor_sync(0xffffffffu, s, 1); s += __shfl_xor_sync(0xffffffffu, s, 2); s += __shfl_xor_sync(0xffffffffu, s, 4);
          if (v == p) mine = s;
        }
        const float gt = __fdividef(1.f, 1.f + __expf(-mine));
        sts32(sb + SM_G + (rr + 16 * v) * 4, __float_as_uint(gt));
        fence_async_smem();
        bar_sync(4, 128);
        if (aj == 0) g_gate[ai * 128 + tid] = ldsf(sb + SM_G + tid * 4);
        if (tid == 0) TS(8);
      }
#pragma unroll
      for (int k = 0; k < 64; k++) acc[k] = 0.f;
      regfence(acc);
      const int pass = wg >> 1;
#pragma unroll 1
      for (int c = 0; c < 8; c++) {
        mbar_wait(BAR(B_XFULL + c), 0);
        mbar_wait(BAR(B_WFULL + pass * 8 + c), 0);
        if (tid == 0 && half == pass) TS(48 + pass * 8 + c);
        const uint64_t da = mkdesc(sb + SM_K + c * 16384 + half * 8192, 16, 1024, 1);
        const uint64_t db = mkdesc(sb + wslot(pass * 8 + c), 4096, 512, 2);
        wg_fence();
#pragma unroll
        for (int k = 0; k < 4; k++) wg_ss_n128<0, 64>(acc, da + 2 * k, db + 64 * k);
        wg_commit();
        wg_wait<1>();
        if (tid == 0 && c > 0) {
          if (pass * 8 + c < 12) mbar_arrive_both(BAR(B_WEMPTY + pass * 8 + c - 1));
          if (pass) mbar_arrive_both(BAR(B_XEMPTY + c - 1));
        }
      }
      wg_wait<0>();
      if (tid == 0) mbar_arrive_both(BAR(pass ? B_XEMPTY + 7 : B_WEMPTY + 7));
      regfence(acc);
      if (tid == 0) TS(wg == 0 ? 16 : (wg == 2 ? 24 : (wg == 3 ? 9 : 95)));
      uint32_t qb[8];
      {
        float n2 = 0.f;
#pragma unroll
        for (int k = 0; k < 8; k++) qb[k] = pack_bf16(acc[48 + 2 * k], acc[49 + 2 * k]);
#pragma unroll
        for (int k = 0; k < 4; k++) {
          const uint32_t a = qb[4 * (k >> 1) + (k & 1)], b = qb[4 * (k >> 1) + (k & 1) + 2];
          float s = bf_lo(a) * bf_lo(a);
          s = fmaf(bf_hi(a), bf_hi(a), s); s = fmaf(bf_lo(b), bf_lo(b), s); s = fmaf(bf_hi(b), bf_hi(b), s);
          s += __shfl_xor_sync(0xffffffffu, s, 1); s += __shfl_xor_sync(0xffffffffu, s, 2);
          if (!(s <= 3.0e38f)) s = 3.0e38f;
          n2 = fmaxf(n2, s);
        }
        const uint32_t nmax = __reduce_max_sync(0xffffffffu, __float_as_uint(n2));
        if (lane == 0) { sts32(sb + SM_MISC + 4 * (M_RED + warp), nmax); mbar_arrive(BAR(B_KSTAT)); }
      }
      auto finish_q = [&]() {
        mbar_wait(BAR(B_KSTAT), 0);
        const float qn2 = __uint_as_float(__reduce_max_sync(0xffffffffu, lds32(sb + SM_MISC + 4 * (M_RED + (lane & 15)))));
        const float kn2 = ldsf(sb + SM_MISC + 4 * M_KN2);
        constexpr float SC = QSCALE * 0.125f;
        const bool fast = lds32(sb + SM_MISC + 4 * M_VOK) && qn2 <= 4.0e8f && kn2 <= 4.0e6f && qn2 * kn2 * (SC * SC) <= BOUND * BOUND;
        if (fast) {
#pragma unroll
          for (int k = 0; k < 8; k++) qb[k] = pack_f16(bf_lo(qb[k]) * QSCALE, bf_hi(qb[k]) * QSCALE);
        }
        sts128(sb + SM_Q + wg * 2048 + pass * 4096 + tid * 16, qb[0], qb[1], qb[2], qb[3]);
        sts128(sb + SM_Q + wg * 2048 + pass * 4096 + 4096 + tid * 16, qb[4], qb[5], qb[6], qb[7]);
        if (threadIdx.x == 256) { sts32(sb + SM_MISC + 4 * M_FAST, fast ? 1u : 0u); mbar_arrive(BAR(B_DEC)); }
        __syncwarp();
        if (lane == 0) mbar_arrive(BAR(B_QRDY));
        if (tid == 0 && pass) TS(75 + wg);
      };
      if (pass) finish_q();
#pragma unroll
      for (int k = 0; k < 48; k++) acc[k] = gelu_tanh(acc[k]);
      int fb0, c_lo = 0, c_hi = 12;
      if (wg < 2) { fb0 = aj < 6 ? 12 * aj - 2 : 22 + 8 * aj; if (aj == 0) c_lo = 2; if (aj >= 6) c_hi = 8; }
      else { fb0 = aj < 2 ? 8 * aj : 12 * aj - 8; if (aj < 2) c_hi = 8; if (aj == 7) c_hi = 10; }
      if (wg < 2) {
        const bool lo_ok = c_lo == 0, hi_ok = c_hi == 12;
        float s0 = 0.f, s1 = 0.f;
#pragma unroll
        for (int k = 0; k < 48; k++) {
          if ((k < 8 && !lo_ok) || (k >= 32 && !hi_ok)) acc[k] = 0.f;
          if (k & 2) s1 += acc[k]; else s0 += acc[k];
        }
        s0 += __shfl_xor_sync(0xffffffffu, s0, 1); s0 += __shfl_xor_sync(0xffffffffu, s0, 2);
        s1 += __shfl_xor_sync(0xffffffffu, s1, 1); s1 += __shfl_xor_sync(0xffffffffu, s1, 2);
        const float inv_n = __fdividef(0.125f, (float)(c_hi - c_lo));
        const float m0 = s0 * inv_n, m1 = s1 * inv_n;
        float v0 = 0.f, v1 = 0.f;
#pragma unroll
        for (int k = 0; k < 48; k++) {
          float d = acc[k] - ((k & 2) ? m1 : m0);
          if ((k < 8 && !lo_ok) || (k >= 32 && !hi_ok)) d = 0.f;
          if (k & 2) v1 = fmaf(d, d, v1); else v0 = fmaf(d, d, v0);
        }
        v0 += __shfl_xor_sync(0xffffffffu, v0, 1); v0 += __shfl_xor_sync(0xffffffffu, v0, 2);
        v1 += __shfl_xor_sync(0xffffffffu, v1, 1); v1 += __shfl_xor_sync(0xffffffffu, v1, 2);
        const int r0 = half * 64 + w * 16 + g;
        mbar_wait(BAR(B_EPOCH), 0);
        const unsigned ep1 = lds32(sb + SM_MISC + 4 * M_EPOCH) + 1;
        if (threadIdx.x == 0) TS(67);
        if (t4 < 2) {
          const float m = t4 ? m1 : m0, v = t4 ? v1 : v0;
          asm volatile("st.relaxed.gpu.global.v2.b64 [%0], {%1, %2};" ::"l"(&g_lnstat[(ai * 8 + aj) * 128 + r0 + 8 * t4]),
                       "l"(((unsigned long long)ep1 << 32) | __float_as_uint(m)), "l"(((unsigned long long)ep1 << 32) | __float_as_uint(v)) : "memory");
        }
        float sm[4], sv[4];
        const uint4* lp = &g_lnstat[(ai * 8 + 2 * t4) * 128 + r0];
#pragma unroll 1
        for (int n = 0; n < SPIN_LIMIT; n++) {
          bool ok = true;
#pragma unroll
          for (int e = 0; e < 4; e++) {
            unsigned long long a, b;
            asm volatile("ld.relaxed.gpu.global.v2.b64 {%0, %1}, [%2];" : "=l"(a), "=l"(b) : "l"(lp + (e >> 1) * 128 + (e & 1) * 8) : "memory");
            ok = ok && (uint32_t)(a >> 32) == ep1 && (uint32_t)(b >> 32) == ep1;
            sm[e] = __uint_as_float((uint32_t)a); sv[e] = __uint_as_float((uint32_t)b);
          }
          if (__all_sync(0xffffffffu, ok)) break;
        }
        if (threadIdx.x == 0) TS(68);
        const float na = t4 == 0 ? 80.f : (t4 == 3 ? 64.f : 96.f), nb = t4 == 3 ? 64.f : 96.f;
#pragma unroll
        for (int r = 0; r < 2; r++) {
          float t = fmaf(sm[r], na, sm[2 + r] * nb);
          t += __shfl_xor_sync(0xffffffffu, t, 1); t += __shfl_xor_sync(0xffffffffu, t, 2);
          const float mu = t * (1.f / 688.f);
          const float da = sm[r] - mu, db = sm[2 + r] - mu;
          float m2 = sv[r] + sv[2 + r] + na * da * da + nb * db * db;
          m2 += __shfl_xor_sync(0xffffffffu, m2, 1); m2 += __shfl_xor_sync(0xffffffffu, m2, 2);
          const float rs = rsqrtf(fmaf(m2, 1.f / 688.f, 1e-5f)), sh = -mu * rs;
#pragma unroll
          for (int k = 2 * r; k < 48; k += 4) { acc[k] = fmaf(acc[k], rs, sh); acc[k + 1] = fmaf(acc[k + 1], rs, sh); }
        }
        if (aj == 7) {
          c_hi = 10;
#pragma unroll
          for (int k = 32; k < 40; k++) acc[k] = 0.f;
        }
      }
      uint32_t* zp = wg < 2 ? reinterpret_cast<uint32_t*>(g_z2n) + (ai * 2 + half) * 2816 + w * 704
                            : reinterpret_cast<uint32_t*>(g_z1) + (ai * 88 * 16 + half * 8 + w * 2) * 32;
      const int mul = wg < 2 ? 373 : 0, cstr = wg < 2 ? 32 : 512, rstr = wg < 2 ? 352 : 32;
      auto zoff = [&](int c8) { const int fb = fb0 + c8; return ((fb * mul) >> 12) * (32 * 2816 - 352) + fb * cstr; };
#pragma unroll
      for (int c8 = 0; c8 < 12; c8++) {
        uint32_t* p = zp + zoff(c8) + lane;
        if (c8 >= c_lo && c8 < c_hi) { p[0] = pack_bf16(acc[4 * c8], acc[4 * c8 + 1]); p[rstr] = pack_bf16(acc[4 * c8 + 2], acc[4 * c8 + 3]); }
      }
      if (tid == 0) TS(wg == 0 ? 69 : 78 + wg);
      uint32_t chk = 0;
#pragma unroll
      for (int r = 0; r < 3; r++) {
        const int it = lane + 32 * r, c8 = it >> 3;
        if (c8 >= c_lo && c8 < c_hi) chk ^= ld_back(zp + zoff(c8) + ((it >> 2) & 1) * rstr + (it & 3) * 8);
      }
      if (wg == 3 && aj == 0) chk ^= ld_back(&g_gate[ai * 128 + tid]);
      consume(chk, sb);
      fence_async();
      bar_sync(1 + wg, 128);
      if (tid == 0) { red_relaxed(wg < 2 ? &g_zcnt[(ai * 2 + half) * 32] : &g_z1cnt[ai * 32]); TS(wg < 2 ? 20 + wg : 8 + wg * wg); }
      if (!pass) finish_q();
    }
    if (wg == 3) {
      asm volatile("setmaxnreg.inc.sync.aligned.u32 120;");
      int st = 0, ph = 0;
      {
        float acc[88];
#pragma unroll
        for (int k = 0; k < 88; k++) acc[k] = 0.f;
        regfence(acc);
#pragma unroll 1
        for (int n = 0; n < 32; n++) {
          mbar_wait(BAR(B_RFULL + st), ph);
          const uint64_t da = mkdesc(sb + SM_RING + st * RSTAGE, 16, 1024, 1);
          const uint64_t db = mkdesc(sb + SM_RING + st * RSTAGE + 16384, 1408, 128, 0);
#pragma unroll
          for (int k = 0; k < 4; k++) {
            wg_fence();
            wg_ss_n88<0, 88>(acc, da + 2 * k, db + 176 * k);
            wg_ss_n88<44, 88>(acc, da + 512 + 2 * k, db + 176 * k);
            wg_commit();
            wg_wait<0>();
          }
          if (tid == 0) mbar_arrive_both(BAR(B_REMPTY + st));
          if (++st == 3) { st = 0; ph ^= 1; }
        }
        regfence(acc);
        if (tid == 0) TS(11);
        mbar_wait(BAR(B_Z1OK), 0);
        const uint32_t* z1p = reinterpret_cast<const uint32_t*>(g_z1) + ((bi * 88 + bj * 11) * 16 + w * 2) * 32 + lane;
        uint32_t* up = reinterpret_cast<uint32_t*>(g_u) + bi * 11 * 4096 + w * 512 + lane;
#pragma unroll
        for (int r = 0; r < 4; r++) {
          const int row = bi * 128 + (r >> 1) * 64 + w * 16 + (r & 1) * 8 + g;
          const float og = 1.f - __ldcg(&g_gate[row]), bs = __bfloat162float(prm.b_sp[row]) * og;
          uint32_t zz[11];
#pragma unroll
          for (int c8 = 0; c8 < 11; c8++) zz[c8] = __ldcg(z1p + c8 * 512 + ((r >> 1) * 8 + (r & 1)) * 32);
          if (bj == 7) zz[9] = zz[10] = 0;
#pragma unroll
          for (int c8 = 0; c8 < 11; c8++) {
            const int k = (r >> 1) * 44 + c8 * 4 + (r & 1) * 2, cb = 11 * bj + c8;
            uint32_t v = pack_bf16(fmaf(acc[k], og, bs), fmaf(acc[k + 1], og, bs));
            asm("mul.rn.bf16x2 %0, %0, %1;" : "+r"(v) : "r"(zz[c8]));
            up[cb * 32 + (cb >> 3) * 3840 + ((r >> 1) * 8 + (r & 1)) * 256] = v;
          }
        }
        fence_async();
        bar_sync(4, 128);
        if (tid == 0) { red_release(&g_ucnt[bi * 32]); TS(12); }
      }
      float oc[64];
#pragma unroll
      for (int k = 0; k < 64; k++) oc[k] = 0.f;
      regfence(oc);
#pragma unroll 1
      for (int n = 0; n < 19; n++) {
        uint32_t sa, sw;
        if (n < 11) { mbar_wait(BAR(B_RFULL + st), ph); sa = SM_RING + st * RSTAGE; sw = sa + 16384; }
        else {
          if (n == 11) { if (tid == 0) TS(13); mbar_wait(BAR(B_WOFULL), 0); }
          mbar_wait(BAR(B_XFULL + n - 11), 1); sa = SM_K + (n - 11) * 16384; sw = SM_RING + (n - 11) * 8192;
        }
        const uint64_t da = mkdesc(sb + sa, 128, 1024, 0), db = mkdesc(sb + sw, 8192, 1024, 1);
#pragma unroll
        for (int k = 0; k < 4; k += 2) {
          wg_fence();
          wg_ss_n64<0, 64>(oc, da + 16 * k, db + 128 * k);
          wg_ss_n64<32, 64>(oc, da + 512 + 16 * k, db + 128 * k);
          wg_ss_n64<0, 64>(oc, da + 16 * k + 16, db + 128 * k + 128);
          wg_ss_n64<32, 64>(oc, da + 528 + 16 * k, db + 128 * k + 128);
          wg_commit();
          if (n < 11) wg_wait<0>();
        }
        if (n < 11) {
          if (tid == 0) mbar_arrive_both(BAR(B_REMPTY + st));
          if (++st == 3) { st = 0; ph ^= 1; }
        }
      }
      wg_wait<0>();
      regfence(oc);
      if (tid == 0) TS(14);
      uint32_t* op = reinterpret_cast<uint32_t*>(prm.out) + (bi * 128 + w * 16 + g) * 256 + bj * 32 + t4;
#pragma unroll
      for (int k = 0; k < 64; k += 2) {
        const int hf = k / 32, c8 = (k % 32) / 4, r8 = (k >> 1) & 1;
        op[(hf * 64 + r8 * 8) * 256 + c8 * 4] = pack_bf16(oc[k], oc[k + 1]);
      }
      if (tid == 0) TS(15);
    } else {
      mbar_wait(BAR(B_QRDY), 0);
    if (tid == 0) TS(25 + wg);
    mbar_wait(BAR(B_KVFULL), 0);
    if (tid == 0) TS(28 + wg);
    const uint64_t dk0 = mkdesc(sb + SM_K, 16, 256, 3);
    const uint64_t dv0 = mkdesc(sb + SM_V, SM_ONES - SM_V, 256, 3);
    const int aw = wg == 0 ? 0 : 3 - wg;
    uint32_t chk = 0;
    float o[12], s[32];
    uint32_t q[4], p0[16], p1[16];
    if (lds32(sb + SM_MISC + 4 * M_FAST)) {
      const uint32_t mlo = prm.mlo, mhi = prm.mhi;
      uint64_t dk = dk0, dv = dv0;
#define STEP(PIN, POUT) { wg_fence(); issue_qk(s, q, dk); dk += 128; wg_commit(); issue_pv(o, PIN, dv); dv += (uint64_t)(4 * VSTEP); wg_commit(); \
                          wg_wait<1>(); regfence(s); softmax_step(s, POUT, mlo, mhi); wg_wait<0>(); }
#pragma unroll 1
      for (int sg = aw * 8; sg < aw * 8 + 8; sg++) {
        const int tau = sg / 3, seg = sg - tau * 3;
        int n2 = seg == 1 ? 6 : 5;
#pragma unroll
        for (int k = 0; k < NP / 2; k++) s[k] = MAGIC_C;
        if (sg == aw * 8 || seg == 0) {
          const int j0 = seg == 0 ? 0 : (seg == 1 ? 10 : 22);
          dk = dk0 + 128 * j0;
          dv = dv0 + VSTEP * (4 * j0);
          const uint4 qv = lds128(sb + SM_Q + tau * 2048 + tid * 16);
          q[0] = qv.x; q[1] = qv.y; q[2] = qv.z; q[3] = qv.w;
#pragma unroll
          for (int k = 0; k < 12; k++) o[k] = 0.f;
          regfence(o); regfence(s);
          wg_fence(); issue_qk(s, q, dk); dk += 128; wg_commit();
          wg_wait<0>(); regfence(s);
          softmax_step(s, p0, mlo, mhi);
          STEP(p0, p1);
          n2--;
        }
        regfence(s);
#pragma unroll 1
        for (; n2 > 0; n2--) { STEP(p1, p0); STEP(p0, p1); }
        if (sg == aw * 8 + 7 || seg == 2) {
          wg_fence(); issue_pv(o, p1, dv); dv += (uint64_t)(4 * VSTEP); wg_commit();
          wg_wait<0>(); regfence(o);
          if (sg == 8 || sg == 17) {
            float4* pp = g_part + (blockIdx.x * 2 + (aw - 1)) * 384 + tid;
            pp[0] = make_float4(o[0], o[1], o[2], o[3]); pp[128] = make_float4(o[4], o[5], o[6], o[7]); pp[256] = make_float4(o[8], o[9], o[10], o[11]);
            __threadfence_block();
            bar_arrive(5 + aw, 256);
          } else {
            if (sg == 7 || sg == 15) {
              bar_sync(6 + aw, 256);
              const float4* pp = g_part + (blockIdx.x * 2 + aw) * 384 + tid;
              const float4 a = pp[0], b = pp[128], c = pp[256];
              o[0] += a.x; o[1] += a.y; o[2] += a.z; o[3] += a.w; o[4] += b.x; o[5] += b.y; o[6] += b.z; o[7] += b.w; o[8] += c.x; o[10] += c.z;
            }
            chk ^= store_o_tile(o, ai, aj, tau, tid, sb);
          }
        }
      }
#undef STEP
    } else {
      mbar_wait(BAR(B_KFB), 0);
      constexpr float SC = 0.25f * 1.4426950408889634f;
#pragma unroll 1
      for (int tau = wg * 3; tau < wg * 3 + 3 && tau < 8; tau++) {
        const uint4 qv = lds128(sb + SM_Q + tau * 2048 + tid * 16);
        float m0 = -INFINITY, m1 = -INFINITY;
#pragma unroll
        for (int k = 0; k < 12; k++) o[k] = 0.f;
        uint64_t dv = dv0;
#pragma unroll 1
        for (int j = 0; j < 32; j++) {
          regfence(s);
          wg_fence(); wg_qkb_n64<0, 0, 32>(s, qv.x, qv.y, qv.z, qv.w, dk0 + 128 * j); wg_commit();
          wg_wait<0>(); regfence(s);
          float x0 = m0, x1 = m1;
#pragma unroll
          for (int k = 0; k < 32; k++) { s[k] *= SC; if (k & 2) x1 = fmaxf(x1, s[k]); else x0 = fmaxf(x0, s[k]); }
          x0 = fmaxf(x0, __shfl_xor_sync(0xffffffffu, x0, 1)); x0 = fmaxf(x0, __shfl_xor_sync(0xffffffffu, x0, 2));
          x1 = fmaxf(x1, __shfl_xor_sync(0xffffffffu, x1, 1)); x1 = fmaxf(x1, __shfl_xor_sync(0xffffffffu, x1, 2));
          const float c0 = ex2(m0 - x0), c1 = ex2(m1 - x1);
          m0 = x0; m1 = x1;
#pragma unroll
          for (int k = 0; k < 12; k++) o[k] *= (k & 2) ? c1 : c0;
#pragma unroll
          for (int k = 0; k < 16; k++) { const float m = (k & 1) ? m1 : m0; p0[k] = exp_mufu(s[2 * k] - m, s[2 * k + 1] - m); }
          regfence(o);
          wg_fence(); issue_pv(o, p0, dv); dv += (uint64_t)(4 * VSTEP); wg_commit();
          wg_wait<0>(); regfence(o);
        }
        chk ^= store_o_tile(o, ai, aj, tau, tid, sb);
      }
    }
    consume(chk, sb);
    fence_async();
    bar_sync(1 + wg, 128);
    if (tid == 0) { red_relaxed(&g_ocnt[ai * 32]); mbar_arrive_both(BAR(B_ATT)); TS(31 + wg); }
    }
  }
  __syncwarp();
  asm volatile("barrier.cluster.arrive.relaxed;" ::: "memory");
  asm volatile("barrier.cluster.wait;" ::: "memory");
}

typedef CUresult (*EncodeFn)(CUtensorMap*, CUtensorMapDataType, cuuint32_t, void*, const cuuint64_t*, const cuuint64_t*,
                             const cuuint32_t*, const cuuint32_t*, CUtensorMapInterleave, CUtensorMapSwizzle,
                             CUtensorMapL2promotion, CUtensorMapFloatOOBfill);

void make_map(EncodeFn enc, CUtensorMap* tm, const void* base, uint64_t cols, uint64_t rows, uint32_t bc, uint32_t br, CUtensorMapSwizzle sw) {
  cuuint64_t gd[2] = {cols, rows};
  cuuint64_t gs[1] = {cols * 2};
  cuuint32_t bd[2] = {bc, br};
  cuuint32_t es[2] = {1, 1};
  enc(tm, CU_TENSOR_MAP_DATA_TYPE_BFLOAT16, 2, const_cast<void*>(base), gd, gs, bd, es, CU_TENSOR_MAP_INTERLEAVE_NONE, sw,
      CU_TENSOR_MAP_L2_PROMOTION_L2_128B, CU_TENSOR_MAP_FLOAT_OOB_FILL_NONE);
}

}

extern "C" void kernel_launch(void* const* d_in, const int* in_sizes, int n_in, void* d_out, int out_size) {
  (void)in_sizes; (void)n_in; (void)out_size;
  static EncodeFn enc = nullptr;
  if (!enc) {
    void* fn = nullptr;
    cudaDriverEntryPointQueryResult qr;
    cudaGetDriverEntryPoint("cuTensorMapEncodeTiled", &fn, cudaEnableDefault, &qr);
    enc = (EncodeFn)fn;
    cudaFuncSetAttribute(fused_kernel, cudaFuncAttributeMaxDynamicSharedMemorySize, SMEM_BYTES);
  }
  CUtensorMap tx, tq, tin, tsp, tout, to;
  make_map(enc, &tx, d_in[0], 512, 2048, 64, 128, CU_TENSOR_MAP_SWIZZLE_128B);
  make_map(enc, &tq, d_in[1], 512, 512, 32, 32, CU_TENSOR_MAP_SWIZZLE_64B);
  make_map(enc, &to, d_in[4], 512, 512, 64, 64, CU_TENSOR_MAP_SWIZZLE_128B);
  make_map(enc, &tin, d_in[6], 1376, 512, 32, 32, CU_TENSOR_MAP_SWIZZLE_64B);
  make_map(enc, &tsp, d_in[7], 2048, 2048, 64, 64, CU_TENSOR_MAP_SWIZZLE_128B);
  make_map(enc, &tout, d_in[9], 512, 688, 64, 64, CU_TENSOR_MAP_SWIZZLE_128B);
  Params prm;
  prm.gate_w = (const __nv_bfloat16*)d_in[10];
  prm.b_sp = (const __nv_bfloat16*)d_in[8];
  prm.w_out = (const __nv_bfloat16*)d_in[9];
  prm.wo = (const __nv_bfloat16*)d_in[4];
  prm.w_in = (const __nv_bfloat16*)d_in[6];
  prm.wq = (const __nv_bfloat16*)d_in[1];
  prm.wk = (const __nv_bfloat16*)d_in[2];
  prm.wv = (const __nv_bfloat16*)d_in[3];
  prm.mlo = 0x007F007Fu;
  prm.mhi = 0xFF80FF80u;
  prm.out = (__nv_bfloat16*)d_out;
  fused_kernel<<<NCTA, NTHREADS, SMEM_BYTES>>>(tx, tq, tin, tsp, tout, to, prm);
}
```

```cpp
#include <cuda_runtime.h>
#include <cuda.h>
#include <cuda_bf16.h>
#include <cuda_fp16.h>
#include <stdint.h>

namespace {

constexpr int NCTA = 128;
constexpr int NTHREADS = 640;
constexpr int NP = 40;
constexpr int NM = 64 - NP;
constexpr int SPIN_LIMIT = 1 << 18;

constexpr uint32_t SM_K = 0;
constexpr uint32_t SM_V = 65536;
constexpr uint32_t SM_ONES = 131072;
constexpr uint32_t KV_BYTES = 131072;
constexpr uint32_t SM_BAR = 131584;
constexpr uint32_t SM_RING = 132096;
constexpr uint32_t RSTAGE = 27648;
constexpr uint32_t WSLOT = 16384;
constexpr uint32_t SM_WKV = SM_RING + 4 * WSLOT;
constexpr uint32_t SM_GW = SM_WKV + 16384;
constexpr uint32_t SM_Q = 215040;
constexpr uint32_t SM_G = 231424;
constexpr uint32_t SM_MISC = 231936;
constexpr uint32_t SMEM_BYTES = 232448;

constexpr int B_XFULL = 0, B_XEMPTY = 8, B_WFULL = 16, B_WEMPTY = 32, B_RFULL = 44, B_REMPTY = 47, B_KVFULL = 50,
              B_KFB = 51, B_KSTAT = 52, B_DEC = 53, B_WOFULL = 54, B_EPOCH = 55, B_ZOK = 56, B_Z1OK = 57, B_ATT = 58, B_QRDY = 59;
constexpr int M_EPOCH = 0, M_KN2 = 1, M_VOK = 2, M_FAST = 3, M_KVR = 4, M_RED = 16;

__device__ uint4 g_kimg[KV_BYTES / 16];
__device__ uint4 g_kbf[65536 / 16];
__device__ unsigned long long g_kvflag[NCTA];
__device__ uint4 g_lnstat[16 * 8 * 128];
__device__ float g_gate[2048];
__device__ uint4 g_z2n[8 * 32 * 11264 / 16];
__device__ uint4 g_z1[16 * 88 * 128];
__device__ uint4 g_u[16 * 11 * 1024];
__device__ uint4 g_o[16 * 8 * 1024];
__device__ float4 g_part[NCTA * 2 * 3 * 128];
__device__ unsigned g_ticket;
__device__ unsigned g_zcnt[32 * 32];
__device__ unsigned g_z1cnt[16 * 32];
__device__ unsigned g_ucnt[16 * 32];
__device__ unsigned g_ocnt[16 * 32];
#define TS(k) do { } while (0)
#define GTS(k) do { } while (0)

__device__ __forceinline__ void mbar_init(uint32_t a, uint32_t c) { asm volatile("mbarrier.init.shared::cta.b64 [%0], %1;" ::"r"(a), "r"(c) : "memory"); }
__device__ __forceinline__ void mbar_arrive(uint32_t a) { asm volatile("mbarrier.arrive.shared::cta.b64 _, [%0];" ::"r"(a) : "memory"); }
__device__ __forceinline__ void mbar_arrive_both(uint32_t a) {
  asm volatile("{\n.reg .b32 ra;\nmapa.shared::cluster.u32 ra, %0, 0;\nmbarrier.arrive.shared::cluster.b64 _, [ra];\n"
               "mapa.shared::cluster.u32 ra, %0, 1;\nmbarrier.arrive.shared::cluster.b64 _, [ra];\n}" ::"r"(a) : "memory");
}
__device__ __forceinline__ void mbar_wait(uint32_t a, uint32_t ph) {
  uint32_t ok;
#pragma unroll 1
  for (int n = 0; n < SPIN_LIMIT; n++) {
    asm volatile("{\n.reg .pred p;\nmbarrier.try_wait.parity.shared::cta.b64 p, [%1], %2;\nselp.u32 %0, 1, 0, p;\n}" : "=r"(ok) : "r"(a), "r"(ph) : "memory");
    if (ok) break;
  }
}
#define ELECT "{\n.reg .pred p;\nelect.sync _|p, 0xffffffff;\n@p "
__device__ __forceinline__ void e_expect(uint32_t a, uint32_t b) { asm volatile(ELECT "mbarrier.arrive.expect_tx.shared::cta.b64 _, [%0], %1;\n}" ::"r"(a), "r"(b) : "memory"); }
__device__ __forceinline__ void e_arrive(uint32_t a) { asm volatile(ELECT "mbarrier.arrive.shared::cta.b64 _, [%0];\n}" ::"r"(a) : "memory"); }
__device__ __forceinline__ void tma2d(uint32_t dst, const CUtensorMap* tm, int c0, int c1, uint32_t bar) {
  asm volatile(ELECT "cp.async.bulk.tensor.2d.shared::cluster.global.mbarrier::complete_tx::bytes [%0], [%1, {%3, %4}], [%2];\n}"
               ::"r"(dst), "l"(tm), "r"(bar), "r"(c0), "r"(c1) : "memory");
}
__device__ __forceinline__ void tma2d_mc(uint32_t dst, const CUtensorMap* tm, int c0, int c1, uint32_t bar) {
  asm volatile(ELECT "cp.async.bulk.tensor.2d.shared::cluster.global.mbarrier::complete_tx::bytes.multicast::cluster [%0], [%1, {%3, %4}], [%2], %5;\n}"
               ::"r"(dst), "l"(tm), "r"(bar), "r"(c0), "r"(c1), "h"((uint16_t)3) : "memory");
}
__device__ __forceinline__ void tma3d_mc(uint32_t dst, const CUtensorMap* tm, int c0, int c1, int c2, uint32_t bar) {
  asm volatile(ELECT "cp.async.bulk.tensor.3d.shared::cluster.global.mbarrier::complete_tx::bytes.multicast::cluster [%0], [%1, {%3, %4, %5}], [%2], %6;\n}"
               ::"r"(dst), "l"(tm), "r"(bar), "r"(c0), "r"(c1), "r"(c2), "h"((uint16_t)3) : "memory");
}
__device__ __forceinline__ void tma2d_pf(const CUtensorMap* tm, int c0, int c1) {
  asm volatile(ELECT "cp.async.bulk.prefetch.tensor.2d.L2.global [%0, {%1, %2}];\n}" ::"l"(tm), "r"(c0), "r"(c1) : "memory");
}
__device__ __forceinline__ void tm_prefetch(const CUtensorMap* tm) { asm volatile(ELECT "prefetch.tensormap [%0];\n}" ::"l"(tm) : "memory"); }
__device__ __forceinline__ void bulk(uint32_t dst, const void* src, uint32_t bytes, uint32_t bar) {
  asm volatile(ELECT "cp.async.bulk.shared::cluster.global.mbarrier::complete_tx::bytes [%0], [%1], %2, [%3];\n}"
               ::"r"(dst), "l"(src), "r"(bytes), "r"(bar) : "memory");
}
__device__ __forceinline__ void bulk_mc(uint32_t dst, const void* src, uint32_t bytes, uint32_t bar) {
  asm volatile(ELECT "cp.async.bulk.shared::cluster.global.mbarrier::complete_tx::bytes.multicast::cluster [%0], [%1], %2, [%3], %4;\n}"
               ::"r"(dst), "l"(src), "r"(bytes), "r"(bar), "h"((uint16_t)3) : "memory");
}
__device__ __forceinline__ void l2_prefetch(const void* src, uint32_t bytes) { asm volatile(ELECT "cp.async.bulk.prefetch.L2.global [%0], %1;\n}" ::"l"(src), "r"(bytes) : "memory"); }
__device__ __forceinline__ void fence_async() { asm volatile("fence.proxy.async.global;" ::: "memory"); }
__device__ __forceinline__ void fence_async_smem() { asm volatile("fence.proxy.async.shared::cta;" ::: "memory"); }
__device__ __forceinline__ void bar_sync(int id, int n) { asm volatile("bar.sync %0, %1;" ::"r"(id), "r"(n) : "memory"); }
__device__ __forceinline__ void bar_arrive(int id, int n) { asm volatile("bar.arrive %0, %1;" ::"r"(id), "r"(n) : "memory"); }
__device__ __forceinline__ void red_release(unsigned* p) { asm volatile("red.release.gpu.global.add.u32 [%0], 1;" ::"l"(p) : "memory"); }
__device__ __forceinline__ void red_relaxed(unsigned* p) { asm volatile("red.relaxed.gpu.global.add.u32 [%0], 1;" ::"l"(p) : "memory"); }
__device__ __forceinline__ uint32_t ld_back(const void* p) { uint32_t v; asm volatile("ld.relaxed.gpu.global.u32 %0, [%1];" : "=r"(v) : "l"(p) : "memory"); return v; }
__device__ __forceinline__ void consume(uint32_t v, uint32_t sb) { if (v == 0xDEADBEEFu) asm volatile("st.shared.u32 [%0], %1;" ::"r"(sb + SM_MISC + 60), "r"(v) : "memory"); }
__device__ __forceinline__ unsigned ld_acquire(const unsigned* p) { unsigned v; asm volatile("ld.acquire.gpu.global.u32 %0, [%1];" : "=r"(v) : "l"(p) : "memory"); return v; }
__device__ __forceinline__ void wait_ge(const unsigned* p, unsigned target) {
#pragma unroll 1
  for (int n = 0; n < SPIN_LIMIT; n++) {
    if ((int)(ld_acquire(p) - target) >= 0) break;
    __nanosleep(100);
  }
}
__device__ __forceinline__ void wg_fence() { asm volatile("wgmma.fence.sync.aligned;" ::: "memory"); }
__device__ __forceinline__ void wg_commit() { asm volatile("wgmma.commit_group.sync.aligned;" ::: "memory"); }
template <int N> __device__ __forceinline__ void wg_wait() { asm volatile("wgmma.wait_group.sync.aligned %0;" ::"n"(N) : "memory"); }
template <int n> __device__ __forceinline__ void regfence(float (&d)[n]) {
#pragma unroll
  for (int i = 0; i < n; i++) asm volatile("" : "+f"(d[i])::"memory");
}
__device__ __forceinline__ uint64_t mkdesc(uint32_t addr, uint32_t lbo, uint32_t sbo, int swz) {
  return (uint64_t)((addr & 0x3FFFF) >> 4) | ((uint64_t)(lbo >> 4) << 16) | ((uint64_t)(sbo >> 4) << 32) | ((uint64_t)swz << 62);
}
__device__ __forceinline__ uint32_t pack_bf16(float lo, float hi) { uint32_t r; asm("cvt.rn.bf16x2.f32 %0, %1, %2;" : "=r"(r) : "f"(hi), "f"(lo)); return r; }
__device__ __forceinline__ uint32_t pack_f16(float lo, float hi) { uint32_t r; asm("cvt.rn.f16x2.f32 %0, %1, %2;" : "=r"(r) : "f"(hi), "f"(lo)); return r; }
__device__ __forceinline__ float bf_lo(uint32_t v) { return __uint_as_float(v << 16); }
__device__ __forceinline__ float bf_hi(uint32_t v) { return __uint_as_float(v & 0xFFFF0000u); }
__device__ __forceinline__ float ex2(float x) { float r; asm("ex2.approx.ftz.f32 %0, %1;" : "=f"(r) : "f"(x)); return r; }
__device__ __forceinline__ float gelu_tanh(float x) {
  float u = x * fmaf(x * x, 0.0356774081f, 0.7978845608f), t;
  asm("tanh.approx.f32 %0, %1;" : "=f"(t) : "f"(u));
  float h = 0.5f * x;
  return fmaf(h, t, h);
}
__device__ __forceinline__ void sts32(uint32_t a, uint32_t v) { asm volatile("st.shared.u32 [%0], %1;" ::"r"(a), "r"(v) : "memory"); }
__device__ __forceinline__ void sts16(uint32_t a, uint16_t v) { asm volatile("st.shared.u16 [%0], %1;" ::"r"(a), "h"(v) : "memory"); }
__device__ __forceinline__ void sts128(uint32_t a, uint32_t x, uint32_t y, uint32_t z, uint32_t w) { asm volatile("st.shared.v4.u32 [%0], {%1,%2,%3,%4};" ::"r"(a), "r"(x), "r"(y), "r"(z), "r"(w) : "memory"); }
__device__ __forceinline__ uint32_t lds32(uint32_t a) { uint32_t v; asm volatile("ld.shared.u32 %0, [%1];" : "=r"(v) : "r"(a) : "memory"); return v; }
__device__ __forceinline__ float ldsf(uint32_t a) { return __uint_as_float(lds32(a)); }
__device__ __forceinline__ uint4 lds128(uint32_t a) { uint4 v; asm volatile("ld.shared.v4.u32 {%0,%1,%2,%3}, [%4];" : "=r"(v.x), "=r"(v.y), "=r"(v.z), "=r"(v.w) : "r"(a) : "memory"); return v; }

template<int OFF, int TOT> __device__ __forceinline__ void wg_ss_n88(float (&d)[TOT], uint64_t da, uint64_t db) {
  asm volatile("wgmma.mma_async.sync.aligned.m64n88k16.f32.bf16.bf16 {%0, %1, %2, %3, %4, %5, %6, %7, %8, %9, %10, %11, %12, %13, %14, %15, %16, %17, %18, %19, %20, %21, %22, %23, %24, %25, %26, %27, %28, %29, %30, %31, %32, %33, %34, %35, %36, %37, %38, %39, %40, %41, %42, %43}, %44, %45, 1, 1, 1, 0, 1;"
    : "+f"(d[OFF+0]), "+f"(d[OFF+1]), "+f"(d[OFF+2]), "+f"(d[OFF+3]), "+f"(d[OFF+4]), "+f"(d[OFF+5]), "+f"(d[OFF+6]), "+f"(d[OFF+7]),
      "+f"(d[OFF+8]), "+f"(d[OFF+9]), "+f"(d[OFF+10]), "+f"(d[OFF+11]), "+f"(d[OFF+12]), "+f"(d[OFF+13]), "+f"(d[OFF+14]), "+f"(d[OFF+15]),
      "+f"(d[OFF+16]), "+f"(d[OFF+17]), "+f"(d[OFF+18]), "+f"(d[OFF+19]), "+f"(d[OFF+20]), "+f"(d[OFF+21]), "+f"(d[OFF+22]), "+f"(d[OFF+23]),
      "+f"(d[OFF+24]), "+f"(d[OFF+25]), "+f"(d[OFF+26]), "+f"(d[OFF+27]), "+f"(d[OFF+28]), "+f"(d[OFF+29]), "+f"(d[OFF+30]), "+f"(d[OFF+31]),
      "+f"(d[OFF+32]), "+f"(d[OFF+33]), "+f"(d[OFF+34]), "+f"(d[OFF+35]), "+f"(d[OFF+36]), "+f"(d[OFF+37]), "+f"(d[OFF+38]), "+f"(d[OFF+39]),
      "+f"(d[OFF+40]), "+f"(d[OFF+41]), "+f"(d[OFF+42]), "+f"(d[OFF+43])
    : "l"(da), "l"(db));
}
template<int OFF, int TOT> __device__ __forceinline__ void wg_ss_n128(float (&d)[TOT], uint64_t da, uint64_t db) {
  asm volatile("wgmma.mma_async.sync.aligned.m64n128k16.f32.bf16.bf16 {%0, %1, %2, %3, %4, %5, %6, %7, %8, %9, %10, %11, %12, %13, %14, %15, %16, %17, %18, %19, %20, %21, %22, %23, %24, %25, %26, %27, %28, %29, %30, %31, %32, %33, %34, %35, %36, %37, %38, %39, %40, %41, %42, %43, %44, %45, %46, %47, %48, %49, %50, %51, %52, %53, %54, %55, %56, %57, %58, %59, %60, %61, %62, %63}, %64, %65, 1, 1, 1, 0, 1;"
    : "+f"(d[OFF+0]), "+f"(d[OFF+1]), "+f"(d[OFF+2]), "+f"(d[OFF+3]), "+f"(d[OFF+4]), "+f"(d[OFF+5]), "+f"(d[OFF+6]), "+f"(d[OFF+7]),
      "+f"(d[OFF+8]), "+f"(d[OFF+9]), "+f"(d[OFF+10]), "+f"(d[OFF+11]), "+f"(d[OFF+12]), "+f"(d[OFF+13]), "+f"(d[OFF+14]), "+f"(d[OFF+15]),
      "+f"(d[OFF+16]), "+f"(d[OFF+17]), "+f"(d[OFF+18]), "+f"(d[OFF+19]), "+f"(d[OFF+20]), "+f"(d[OFF+21]), "+f"(d[OFF+22]), "+f"(d[OFF+23]),
      "+f"(d[OFF+24]), "+f"(d[OFF+25]), "+f"(d[OFF+26]), "+f"(d[OFF+27]), "+f"(d[OFF+28]), "+f"(d[OFF+29]), "+f"(d[OFF+30]), "+f"(d[OFF+31]),
      "+f"(d[OFF+32]), "+f"(d[OFF+33]), "+f"(d[OFF+34]), "+f"(d[OFF+35]), "+f"(d[OFF+36]), "+f"(d[OFF+37]), "+f"(d[OFF+38]), "+f"(d[OFF+39]),
      "+f"(d[OFF+40]), "+f"(d[OFF+41]), "+f"(d[OFF+42]), "+f"(d[OFF+43]), "+f"(d[OFF+44]), "+f"(d[OFF+45]), "+f"(d[OFF+46]), "+f"(d[OFF+47]),
      "+f"(d[OFF+48]), "+f"(d[OFF+49]), "+f"(d[OFF+50]), "+f"(d[OFF+51]), "+f"(d[OFF+52]), "+f"(d[OFF+53]), "+f"(d[OFF+54]), "+f"(d[OFF+55]),
      "+f"(d[OFF+56]), "+f"(d[OFF+57]), "+f"(d[OFF+58]), "+f"(d[OFF+59]), "+f"(d[OFF+60]), "+f"(d[OFF+61]), "+f"(d[OFF+62]), "+f"(d[OFF+63])
    : "l"(da), "l"(db));
}
template<int OFF, int TOT> __device__ __forceinline__ void wg_ss_n64(float (&d)[TOT], uint64_t da, uint64_t db) {
  asm volatile("wgmma.mma_async.sync.aligned.m64n64k16.f32.bf16.bf16 {%0, %1, %2, %3, %4, %5, %6, %7, %8, %9, %10, %11, %12, %13, %14, %15, %16, %17, %18, %19, %20, %21, %22, %23, %24, %25, %26, %27, %28, %29, %30, %31}, %32, %33, 1, 1, 1, 0, 1;"
    : "+f"(d[OFF+0]), "+f"(d[OFF+1]), "+f"(d[OFF+2]), "+f"(d[OFF+3]), "+f"(d[OFF+4]), "+f"(d[OFF+5]), "+f"(d[OFF+6]), "+f"(d[OFF+7]),
      "+f"(d[OFF+8]), "+f"(d[OFF+9]), "+f"(d[OFF+10]), "+f"(d[OFF+11]), "+f"(d[OFF+12]), "+f"(d[OFF+13]), "+f"(d[OFF+14]), "+f"(d[OFF+15]),
      "+f"(d[OFF+16]), "+f"(d[OFF+17]), "+f"(d[OFF+18]), "+f"(d[OFF+19]), "+f"(d[OFF+20]), "+f"(d[OFF+21]), "+f"(d[OFF+22]), "+f"(d[OFF+23]),
      "+f"(d[OFF+24]), "+f"(d[OFF+25]), "+f"(d[OFF+26]), "+f"(d[OFF+27]), "+f"(d[OFF+28]), "+f"(d[OFF+29]), "+f"(d[OFF+30]), "+f"(d[OFF+31])
    : "l"(da), "l"(db));
}
template<int OFF, int TOT> __device__ __forceinline__ void wg_ss_n32t(float (&d)[TOT], uint64_t da, uint64_t db) {
  asm volatile("wgmma.mma_async.sync.aligned.m64n32k16.f32.bf16.bf16 {%0, %1, %2, %3, %4, %5, %6, %7, %8, %9, %10, %11, %12, %13, %14, %15}, %16, %17, 1, 1, 1, 1, 0;"
    : "+f"(d[OFF+0]), "+f"(d[OFF+1]), "+f"(d[OFF+2]), "+f"(d[OFF+3]), "+f"(d[OFF+4]), "+f"(d[OFF+5]), "+f"(d[OFF+6]), "+f"(d[OFF+7]),
      "+f"(d[OFF+8]), "+f"(d[OFF+9]), "+f"(d[OFF+10]), "+f"(d[OFF+11]), "+f"(d[OFF+12]), "+f"(d[OFF+13]), "+f"(d[OFF+14]), "+f"(d[OFF+15])
    : "l"(da), "l"(db));
}
template<int SCD, int OFF, int TOT> __device__ __forceinline__ void wg_qk_n16(float (&d)[TOT], uint32_t a0, uint32_t a1, uint32_t a2, uint32_t a3, uint64_t db) {
  asm volatile("wgmma.mma_async.sync.aligned.m64n16k16.f32.f16.f16 {%0, %1, %2, %3, %4, %5, %6, %7}, {%8,%9,%10,%11}, %12, %13, 1, 1, 0;"
    : "+f"(d[OFF+0]), "+f"(d[OFF+1]), "+f"(d[OFF+2]), "+f"(d[OFF+3]), "+f"(d[OFF+4]), "+f"(d[OFF+5]), "+f"(d[OFF+6]), "+f"(d[OFF+7])
    : "r"(a0), "r"(a1), "r"(a2), "r"(a3), "l"(db), "n"(SCD));
}
template<int SCD, int OFF, int TOT> __device__ __forceinline__ void wg_qk_n24(float (&d)[TOT], uint32_t a0, uint32_t a1, uint32_t a2, uint32_t a3, uint64_t db) {
  asm volatile("wgmma.mma_async.sync.aligned.m64n24k16.f32.f16.f16 {%0, %1, %2, %3, %4, %5, %6, %7, %8, %9, %10, %11}, {%12,%13,%14,%15}, %16, %17, 1, 1, 0;"
    : "+f"(d[OFF+0]), "+f"(d[OFF+1]), "+f"(d[OFF+2]), "+f"(d[OFF+3]), "+f"(d[OFF+4]), "+f"(d[OFF+5]), "+f"(d[OFF+6]), "+f"(d[OFF+7]),
      "+f"(d[OFF+8]), "+f"(d[OFF+9]), "+f"(d[OFF+10]), "+f"(d[OFF+11])
    : "r"(a0), "r"(a1), "r"(a2), "r"(a3), "l"(db), "n"(SCD));
}
template<int SCD, int OFF, int TOT> __device__ __forceinline__ void wg_qk_n32(float (&d)[TOT], uint32_t a0, uint32_t a1, uint32_t a2, uint32_t a3, uint64_t db) {
  asm volatile("wgmma.mma_async.sync.aligned.m64n32k16.f32.f16.f16 {%0, %1, %2, %3, %4, %5, %6, %7, %8, %9, %10, %11, %12, %13, %14, %15}, {%16,%17,%18,%19}, %20, %21, 1, 1, 0;"
    : "+f"(d[OFF+0]), "+f"(d[OFF+1]), "+f"(d[OFF+2]), "+f"(d[OFF+3]), "+f"(d[OFF+4]), "+f"(d[OFF+5]), "+f"(d[OFF+6]), "+f"(d[OFF+7]),
      "+f"(d[OFF+8]), "+f"(d[OFF+9]), "+f"(d[OFF+10]), "+f"(d[OFF+11]), "+f"(d[OFF+12]), "+f"(d[OFF+13]), "+f"(d[OFF+14]), "+f"(d[OFF+15])
    : "r"(a0), "r"(a1), "r"(a2), "r"(a3), "l"(db), "n"(SCD));
}
template<int SCD, int OFF, int TOT> __device__ __forceinline__ void wg_qk_n40(float (&d)[TOT], uint32_t a0, uint32_t a1, uint32_t a2, uint32_t a3, uint64_t db) {
  asm volatile("wgmma.mma_async.sync.aligned.m64n40k16.f32.f16.f16 {%0, %1, %2, %3, %4, %5, %6, %7, %8, %9, %10, %11, %12, %13, %14, %15, %16, %17, %18, %19}, {%20,%21,%22,%23}, %24, %25, 1, 1, 0;"
    : "+f"(d[OFF+0]), "+f"(d[OFF+1]), "+f"(d[OFF+2]), "+f"(d[OFF+3]), "+f"(d[OFF+4]), "+f"(d[OFF+5]), "+f"(d[OFF+6]), "+f"(d[OFF+7]),
      "+f"(d[OFF+8]), "+f"(d[OFF+9]), "+f"(d[OFF+10]), "+f"(d[OFF+11]), "+f"(d[OFF+12]), "+f"(d[OFF+13]), "+f"(d[OFF+14]), "+f"(d[OFF+15]),
      "+f"(d[OFF+16]), "+f"(d[OFF+17]), "+f"(d[OFF+18]), "+f"(d[OFF+19])
    : "r"(a0), "r"(a1), "r"(a2), "r"(a3), "l"(db), "n"(SCD));
}
template<int SCD, int OFF, int TOT> __device__ __forceinline__ void wg_qk_n48(float (&d)[TOT], uint32_t a0, uint32_t a1, uint32_t a2, uint32_t a3, uint64_t db) {
  asm volatile("wgmma.mma_async.sync.aligned.m64n48k16.f32.f16.f16 {%0, %1, %2, %3, %4, %5, %6, %7, %8, %9, %10, %11, %12, %13, %14, %15, %16, %17, %18, %19, %20, %21, %22, %23}, {%24,%25,%26,%27}, %28, %29, 1, 1, 0;"
    : "+f"(d[OFF+0]), "+f"(d[OFF+1]), "+f"(d[OFF+2]), "+f"(d[OFF+3]), "+f"(d[OFF+4]), "+f"(d[OFF+5]), "+f"(d[OFF+6]), "+f"(d[OFF+7]),
      "+f"(d[OFF+8]), "+f"(d[OFF+9]), "+f"(d[OFF+10]), "+f"(d[OFF+11]), "+f"(d[OFF+12]), "+f"(d[OFF+13]), "+f"(d[OFF+14]), "+f"(d[OFF+15]),
      "+f"(d[OFF+16]), "+f"(d[OFF+17]), "+f"(d[OFF+18]), "+f"(d[OFF+19]), "+f"(d[OFF+20]), "+f"(d[OFF+21]), "+f"(d[OFF+22]), "+f"(d[OFF+23])
    : "r"(a0), "r"(a1), "r"(a2), "r"(a3), "l"(db), "n"(SCD));
}
template<int SCD, int OFF, int TOT> __device__ __forceinline__ void wg_pv_n24(float (&d)[TOT], uint32_t a0, uint32_t a1, uint32_t a2, uint32_t a3, uint64_t db) {
  asm volatile("wgmma.mma_async.sync.aligned.m64n24k16.f32.bf16.bf16 {%0, %1, %2, %3, %4, %5, %6, %7, %8, %9, %10, %11}, {%12,%13,%14,%15}, %16, %17, 1, 1, 1;"
    : "+f"(d[OFF+0]), "+f"(d[OFF+1]), "+f"(d[OFF+2]), "+f"(d[OFF+3]), "+f"(d[OFF+4]), "+f"(d[OFF+5]), "+f"(d[OFF+6]), "+f"(d[OFF+7]),
      "+f"(d[OFF+8]), "+f"(d[OFF+9]), "+f"(d[OFF+10]), "+f"(d[OFF+11])
    : "r"(a0), "r"(a1), "r"(a2), "r"(a3), "l"(db), "n"(SCD));
}
template<int SCD, int OFF, int TOT> __device__ __forceinline__ void wg_qkb_n64(float (&d)[TOT], uint32_t a0, uint32_t a1, uint32_t a2, uint32_t a3, uint64_t db) {
  asm volatile("wgmma.mma_async.sync.aligned.m64n64k16.f32.bf16.bf16 {%0, %1, %2, %3, %4, %5, %6, %7, %8, %9, %10, %11, %12, %13, %14, %15, %16, %17, %18, %19, %20, %21, %22, %23, %24, %25, %26, %27, %28, %29, %30, %31}, {%32,%33,%34,%35}, %36, %37, 1, 1, 0;"
    : "+f"(d[OFF+0]), "+f"(d[OFF+1]), "+f"(d[OFF+2]), "+f"(d[OFF+3]), "+f"(d[OFF+4]), "+f"(d[OFF+5]), "+f"(d[OFF+6]), "+f"(d[OFF+7]),
      "+f"(d[OFF+8]), "+f"(d[OFF+9]), "+f"(d[OFF+10]), "+f"(d[OFF+11]), "+f"(d[OFF+12]), "+f"(d[OFF+13]), "+f"(d[OFF+14]), "+f"(d[OFF+15]),
      "+f"(d[OFF+16]), "+f"(d[OFF+17]), "+f"(d[OFF+18]), "+f"(d[OFF+19]), "+f"(d[OFF+20]), "+f"(d[OFF+21]), "+f"(d[OFF+22]), "+f"(d[OFF+23]),
      "+f"(d[OFF+24]), "+f"(d[OFF+25]), "+f"(d[OFF+26]), "+f"(d[OFF+27]), "+f"(d[OFF+28]), "+f"(d[OFF+29]), "+f"(d[OFF+30]), "+f"(d[OFF+31])
    : "r"(a0), "r"(a1), "r"(a2), "r"(a3), "l"(db), "n"(SCD));
}
template<int N, int SCD, int OFF, int TOT> __device__ __forceinline__ void wg_qk(float (&d)[TOT], const uint32_t (&q)[4], uint64_t db) {
  if constexpr (N == 16) wg_qk_n16<SCD, OFF, TOT>(d, q[0], q[1], q[2], q[3], db);
  if constexpr (N == 24) wg_qk_n24<SCD, OFF, TOT>(d, q[0], q[1], q[2], q[3], db);
  if constexpr (N == 32) wg_qk_n32<SCD, OFF, TOT>(d, q[0], q[1], q[2], q[3], db);
  if constexpr (N == 40) wg_qk_n40<SCD, OFF, TOT>(d, q[0], q[1], q[2], q[3], db);
  if constexpr (N == 48) wg_qk_n48<SCD, OFF, TOT>(d, q[0], q[1], q[2], q[3], db);
}

__device__ __forceinline__ uint32_t exp_mufu(float a, float b) { return pack_bf16(ex2(a), ex2(b)); }
__device__ __forceinline__ uint32_t exp_poly(float a, float b, uint32_t mlo, uint32_t mhi) {
  uint32_t u = __byte_perm(__float_as_uint(a), __float_as_uint(b), 0x6521), mh, e, p;
  asm("lop3.b32 %0, %1, %2, 0x3F003F00, 0xEA;" : "=r"(mh) : "r"(u), "r"(mlo));
  asm("lop3.b32 %0, %1, %2, 0x00020002, 0xEA;" : "=r"(e) : "r"(u), "r"(mhi));
  asm("fma.rn.bf16x2 %0, %1, %2, %3;" : "=r"(p) : "r"(u), "r"(mh), "r"(e));
  return p;
}
constexpr float MAGIC_C = 48948.0625f;
constexpr float QSCALE = 0.25f * 1.4426950408889634f * 8.f;
constexpr float BOUND = 80.f;

__device__ __forceinline__ void softmax_step(const float (&s)[32], uint32_t (&p)[16], uint32_t mlo, uint32_t mhi) {
  constexpr int PP = NP / 4;
  int ip = 0, im = PP;
#pragma unroll
  for (int i = 0; i < 16; i++) {
    if (((i + 1) * PP / 16) > (i * PP / 16)) { p[ip] = exp_poly(s[2 * ip], s[2 * ip + 1], mlo, mhi); ip++; }
    else { p[im] = exp_mufu(s[2 * im], s[2 * im + 1]); im++; }
  }
}
constexpr int64_t VSTEP = 32 - (32 << 16);
__device__ __forceinline__ void issue_qk(float (&s)[32], const uint32_t (&q)[4], uint64_t dk) {
  wg_qk<NM, 0, NP / 2, 32>(s, q, dk + NP * 2);
  wg_qk<NP, 1, 0, 32>(s, q, dk);
}
__device__ __forceinline__ void issue_pv(float (&o)[12], const uint32_t (&p)[16], uint64_t dv) {
#pragma unroll
  for (int c = 0; c < 4; c++) { wg_pv_n24<1, 0, 12>(o, p[4 * c], p[4 * c + 1], p[4 * c + 2], p[4 * c + 3], dv + c * VSTEP); }
}

__device__ __forceinline__ uint32_t wslot(int f) { const int r = f - 5 * ((f * 52) >> 8); return r == 4 ? SM_Q : SM_RING + r * WSLOT; }

struct Params {
  const __nv_bfloat16* gate_w;
  const __nv_bfloat16* b_sp;
  const __nv_bfloat16* w_out;
  const __nv_bfloat16* wo;
  const __nv_bfloat16* w_in;
  const __nv_bfloat16* wq;
  const __nv_bfloat16* wk;
  const __nv_bfloat16* wv;
  uint32_t mlo, mhi;
  __nv_bfloat16* out;
};

__device__ __forceinline__ uint32_t store_o_tile(const float (&o)[12], int bi, int bj, int tau, int tid, uint32_t sb) {
  const int half = tau & 1, hh = tau >> 1, w = tid >> 5, l = tid & 31;
  const int r0 = half * 64 + w * 16 + (l >> 2);
  const float f0 = __fdividef(ldsf(sb + SM_G + r0 * 4), o[8]), f1 = __fdividef(ldsf(sb + SM_G + (r0 + 8) * 4), o[10]);
  uint32_t* dst = reinterpret_cast<uint32_t*>(g_o) + (bi * 8 + bj) * 4096 + (half * 8 + w * 2) * 256 + hh * 64;
  dst[l] = pack_bf16(o[0] * f0, o[1] * f0);
  dst[l + 32] = pack_bf16(o[4] * f0, o[5] * f0);
  dst[l + 256] = pack_bf16(o[2] * f1, o[3] * f1);
  dst[l + 288] = pack_bf16(o[6] * f1, o[7] * f1);
  return ld_back(dst + ((l >> 3) & 1) * 256 + (l & 7) * 8);
}

__global__ void __cluster_dims__(2, 1, 1) __launch_bounds__(NTHREADS, 1)
fused_kernel(const __grid_constant__ CUtensorMap tm_x, const __grid_constant__ CUtensorMap tm_wq,
             const __grid_constant__ CUtensorMap tm_win, const __grid_constant__ CUtensorMap tm_wsp,
             const __grid_constant__ CUtensorMap tm_wout, const __grid_constant__ CUtensorMap tm_wo, const Params prm) {
  extern __shared__ __align__(1024) uint8_t smem_raw[];
  const uint32_t sb = __shfl_sync(0xffffffffu, (uint32_t)__cvta_generic_to_shared(smem_raw), 0);
  const int warp = __shfl_sync(0xffffffffu, (int)(threadIdx.x >> 5), 0);
  const int wg = warp >> 2;
  const int tid = threadIdx.x & 127;
  const int lane = threadIdx.x & 31;
  const int rank = blockIdx.x & 1;
  const int ai = (blockIdx.x >> 4) * 2 + rank, aj = (blockIdx.x >> 1) & 7;
  const int bi = blockIdx.x >> 3, bj = blockIdx.x & 7;
  auto BAR = [&](int k) { return sb + SM_BAR + 8u * k; };

  if (warp == 16) {
    if (lane == 0) {
      mbar_init(BAR(B_XFULL), 1); mbar_init(BAR(B_XFULL + 1), 1);
      asm volatile("fence.mbarrier_init.release.cluster;" ::: "memory");
    }
    __syncwarp();
    e_expect(BAR(B_XFULL), 16384);
    tma2d(sb + SM_K, &tm_x, 0, ai * 128, BAR(B_XFULL));
    e_expect(BAR(B_XFULL + 1), 16384);
    tma2d(sb + SM_K + 16384, &tm_x, 64, ai * 128, BAR(B_XFULL + 1));
    if (lane == 0) TS(36);
  } else if (warp == 18) {
    tm_prefetch(&tm_win);
    tm_prefetch(&tm_wq);
  } else if (warp == 19) {
    l2_prefetch(reinterpret_cast<const uint8_t*>(prm.w_in) + blockIdx.x * 11008, 11008);
    l2_prefetch(reinterpret_cast<const uint8_t*>(prm.wq) + blockIdx.x * 4096, 4096);
  } else if (warp < 16 && lane == 0) {
#pragma unroll
    for (int r = 0; r < 4; r++) {
      const int k = warp + 16 * r;
      uint32_t cnt = 1;
      if (k >= B_XEMPTY && k < B_XEMPTY + 8) cnt = 4;
      if (k >= B_WEMPTY && k < B_WEMPTY + 12) cnt = 4;
      if (k >= B_REMPTY && k < B_REMPTY + 3) cnt = 2;
      if (k == B_ATT) cnt = 6;
      if (k == B_QRDY) cnt = 16;
      if (k == B_KSTAT) cnt = 17;
      if (k >= 2) mbar_init(BAR(k), cnt);
    }
    asm volatile("fence.mbarrier_init.release.cluster;" ::: "memory");
  }
  __syncthreads();
  if (threadIdx.x == 0) TS(35);
  asm volatile("barrier.cluster.arrive.relaxed.aligned;" ::: "memory");
  asm volatile("barrier.cluster.wait.acquire.aligned;" ::: "memory");

  if (wg == 4) {
    asm volatile("setmaxnreg.dec.sync.aligned.u32 24;");
    if (warp == 18) {
#pragma unroll 1
      for (int f = 0; f < 16; f++) {
        if (f == 0 && lane == 0) TS(0);
        if (f == 5 && lane == 0) TS(37);
        if (f >= 5) mbar_wait(BAR(B_WEMPTY + f - 5), 0);
        const uint32_t dst = sb + wslot(f) + rank * 8192, bar = BAR(B_WFULL + f);
        const int k0 = (f & 7) * 64 + rank * 32;
        e_expect(bar, 16384);
        tma3d_mc(dst, &tm_win, 0, k0, f < 8 ? (aj < 6 ? 21 + 3 * aj : 27 + 2 * aj) : (aj < 2 ? 2 * aj : 3 * aj - 2), bar);
        tma2d_mc(dst + 6144, &tm_wq, 64 * aj + (f >> 3) * 32, k0, bar);
      }
      if (lane == 0) TS(1);
    } else if (warp == 19) {
      mbar_wait(BAR(B_XEMPTY + 6), 0);
      const unsigned ep1 = lds32(sb + SM_MISC + 4 * M_EPOCH) + 1;
      wait_ge(&g_zcnt[lane * 32], ep1 * 8);
      __syncwarp();
      e_arrive(BAR(B_ZOK));
      wait_ge(&g_z1cnt[bi * 32], ep1 * 16);
      e_arrive(BAR(B_Z1OK));
    } else if (warp == 16) {
#pragma unroll 1
      for (int c = 2; c < 8; c++) {
        if (c >= 4) mbar_wait(BAR(B_WFULL + c - 4), 0);
        e_expect(BAR(B_XFULL + c), 16384);
        tma2d(sb + SM_K + c * 16384, &tm_x, c * 64, ai * 128, BAR(B_XFULL + c));
      }
      tm_prefetch(&tm_wsp);
      tm_prefetch(&tm_wout);
      tm_prefetch(&tm_wo);
      const int row = bi * 128 + rank * 64;
      mbar_wait(BAR(B_XEMPTY), 0);
      tma2d_pf(&tm_wsp, (bj >> 1) * 64, row);
      tma2d_pf(&tm_wsp, (bj >> 1) * 64 + 256, row);
      mbar_wait(BAR(B_XEMPTY + 7), 0);
      mbar_wait(BAR(B_ZOK), 0);
      const unsigned ep1 = lds32(sb + SM_MISC + 4 * M_EPOCH) + 1;
      fence_async();
      if (lane == 0) TS(2);
      int st = 0, ph = 1;
#pragma unroll 1
      for (int n = 0; n < 46; n++) {
        const uint32_t stg = sb + SM_RING + st * RSTAGE, bar = BAR(B_RFULL + st);
        if (n >= 3) mbar_wait(BAR(B_REMPTY + st), ph);
        if (n < 32) {
          e_expect(bar, 16384 + 11264);
          tma2d_mc(stg + rank * 8192, &tm_wsp, n * 64, row, bar);
          bulk(stg + 16384, reinterpret_cast<const uint8_t*>(g_z2n) + (bj * 32 + n) * 11264, 11264, bar);
          if ((n & 3) == (bj >> 1) && n < 24) tma2d_pf(&tm_wsp, (n + 8) * 64, row);
          if (n == 16) {
            l2_prefetch(reinterpret_cast<const uint8_t*>(prm.w_out) + blockIdx.x * 5504, 5504);
            l2_prefetch(reinterpret_cast<const uint8_t*>(prm.wo) + blockIdx.x * 4096, 4096);
          }
        } else if (n < 43) {
          const int c = n - 32;
          e_expect(bar, 16384 + 8192);
          tma2d(stg + 16384, &tm_wout, 64 * bj, c * 64, bar);
          if (c == 0) { wait_ge(&g_ucnt[bi * 32], ep1 * 8); fence_async(); if (lane == 0) TS(3); }
          bulk_mc(stg + rank * 8192, reinterpret_cast<const uint8_t*>(g_u) + (bi * 11 + c) * 16384 + rank * 8192, 8192, bar);
        }
        if (++st == 3) { st = 0; ph ^= 1; }
      }
      e_expect(BAR(B_WOFULL), 65536);
#pragma unroll 1
      for (int c = 0; c < 8; c++) tma2d(sb + SM_RING + c * 8192, &tm_wo, 64 * bj, c * 64, BAR(B_WOFULL));
      if (lane == 0) TS(4);
#pragma unroll 1
      for (int c = 0; c < 8; c++) e_expect(BAR(B_XFULL + c), 16384);
      mbar_wait(BAR(B_ATT), 0);
#pragma unroll 1
      for (int n = 0; n < SPIN_LIMIT; n++) if ((int)(ld_acquire(&g_ocnt[bi * 32]) - ep1 * 24) >= 0) break;
      fence_async();
      if (lane == 0) TS(5);
#pragma unroll 1
      for (int c = 0; c < 8; c++)
        bulk_mc(sb + SM_K + c * 16384 + rank * 8192, reinterpret_cast<const uint8_t*>(g_o) + (bi * 8 + c) * 16384 + rank * 8192, 8192, BAR(B_XFULL + c));
    } else {
      if (lane == 0) {
        sts32(sb + SM_MISC + 4 * M_EPOCH, atomicAdd(&g_ticket, 1u) / NCTA);
        mbar_arrive(BAR(B_EPOCH));
        TS(71);
      }
      __syncwarp();
      const unsigned ep1 = lds32(sb + SM_MISC + 4 * M_EPOCH) + 1;
      e_expect(BAR(B_KVFULL), KV_BYTES);
      mbar_wait(BAR(B_WFULL + 8), 0);
      uint32_t kn = 0, vb = 0;
#pragma unroll 1
      for (int n = 0; n < SPIN_LIMIT; n++) {
        unsigned long long a, b, c, d;
        asm volatile("ld.relaxed.gpu.global.v2.b64 {%0, %1}, [%2];" : "=l"(a), "=l"(b) : "l"(&g_kvflag[2 * lane]) : "memory");
        asm volatile("ld.relaxed.gpu.global.v2.b64 {%0, %1}, [%2];" : "=l"(c), "=l"(d) : "l"(&g_kvflag[64 + 2 * lane]) : "memory");
        kn = max((uint32_t)a, (uint32_t)c); vb = (uint32_t)b | (uint32_t)d;
        if (__all_sync(0xffffffffu, (uint32_t)(a >> 32) == ep1 && (uint32_t)(b >> 32) == ep1 && (uint32_t)(c >> 32) == ep1 && (uint32_t)(d >> 32) == ep1)) break;
        __nanosleep(100);
      }
      asm volatile("fence.acquire.gpu;" ::: "memory");
      kn = __reduce_max_sync(0xffffffffu, kn);
      vb = __reduce_or_sync(0xffffffffu, vb);
      if (lane == 0) {
        TS(6);
        sts32(sb + SM_MISC + 4 * M_KN2, kn);
        sts32(sb + SM_MISC + 4 * M_VOK, vb == 0xFFFFu ? 1u : 0u);
        mbar_arrive(BAR(B_KSTAT));
      }
      __syncwarp();
      fence_async();
#pragma unroll 1
      for (int c = 0; c < 8; c++) {
        const uint32_t off = c * 16384 + rank * 8192;
        mbar_wait(BAR(B_XEMPTY + c), 0);
        bulk_mc(sb + SM_K + off, reinterpret_cast<const uint8_t*>(g_kimg) + off, 8192, BAR(B_KVFULL));
      }
      if (lane == 0) TS(7);
      mbar_wait(BAR(B_DEC), 0);
      if (!lds32(sb + SM_MISC + 4 * M_FAST)) {
        mbar_wait(BAR(B_KVFULL), 0);
        e_expect(BAR(B_KFB), 65536);
        bulk(sb + SM_K, g_kbf, 65536, BAR(B_KFB));
      }
    }
  } else {
    asm volatile("setmaxnreg.inc.sync.aligned.u32 112;");
    const int w = tid >> 5, g = lane >> 2, t4 = lane & 3, half = wg & 1;
    {
      float acc[64];
      if (wg == 2) {
        const int slot = ai * 4 + (aj >> 1), isv = aj & 1;
        const uint4* wsrc = reinterpret_cast<const uint4*>(isv ? prm.wv : prm.wk) + tid;
        uint4 wr[8];
#pragma unroll
        for (int r = 0; r < 8; r++) wr[r] = __ldg(wsrc + 128 * r);
#pragma unroll
        for (int r = 0; r < 8; r++) sts128(sb + SM_WKV + r * 2048 + (tid >> 1) * 32 + (((tid ^ (tid >> 3)) & 1) << 4), wr[r].x, wr[r].y, wr[r].z, wr[r].w);
        fence_async_smem();
        bar_sync(3, 128);
        float kv[16];
#pragma unroll
        for (int k = 0; k < 16; k++) kv[k] = 0.f;
        regfence(kv);
#pragma unroll 1
        for (int c = 0; c < 8; c++) {
          mbar_wait(BAR(B_XFULL + c), 0);
          const uint64_t da = mkdesc(sb + SM_WKV + c * 2048, 0, 256, 3);
          const uint64_t db = mkdesc(sb + SM_K + c * 16384 + (aj >> 1) * 4096, 16, 1024, 1);
          wg_fence();
#pragma unroll
          for (int k = 0; k < 4; k++) wg_ss_n32t<0, 16>(kv, da + 32 * k, db + 2 * k);
          wg_commit();
        }
        wg_wait<0>();
        regfence(kv);
        if (tid == 0) TS(22);
        const uint32_t sT = sb + SM_WKV, sH = sb + SM_WKV + 4096;
        bar_sync(3, 128);
        {
          const float a = w & 1 ? kv[4] : kv[0], b = w & 1 ? kv[5] : kv[1], c = w & 1 ? kv[6] : kv[2], d = w & 1 ? kv[7] : kv[3];
          const float e = w & 1 ? kv[12] : kv[8], f = w & 1 ? kv[13] : kv[9], h = w & 1 ? kv[14] : kv[10], i = w & 1 ? kv[15] : kv[11];
          const uint32_t lo = pack_bf16(w & 2 ? e : a, w & 2 ? f : b), hi = pack_bf16(w & 2 ? h : c, w & 2 ? i : d);
          const uint32_t p = sT + ((w * 8 + 2 * t4) * 17 + g) * 4;
          sts32(p, lo << 16); sts32(p + 68, lo & 0xFFFF0000u); sts32(p + 32, hi << 16); sts32(p + 100, hi & 0xFFFF0000u);
        }
        bar_sync(3, 128);
        if (tid == 0) TS(64);
        const int tok = (tid & 63) >> 1, hf = tid & 1;
        float f[8];
#pragma unroll
        for (int e = 0; e < 8; e++) f[e] = ldsf(sT + (tok * 17 + hf * 8 + e) * 4);
        uint4 val = make_uint4(pack_bf16(f[0], f[1]), pack_bf16(f[2], f[3]), pack_bf16(f[4], f[5]), pack_bf16(f[6], f[7]));
        uint32_t stat = 0;
        if (isv) {
#pragma unroll
          for (int e = 0; e < 8; e++) {
            if (fabsf(f[e]) >= 9.5367431640625e-07f) stat |= 1u << e;
            if (!(fabsf(f[e]) <= 1073741824.f)) stat |= 1u << (16 - 8 * hf);
          }
          stat = __reduce_or_sync(0xffffffffu, stat << (8 * hf));
        } else {
          float n2 = 0.f;
#pragma unroll
          for (int e = 0; e < 8; e++) n2 = fmaf(f[e], f[e], n2);
          n2 += __shfl_xor_sync(0xffffffffu, n2, 1);
          if (!(n2 <= 3.0e38f)) n2 = 3.0e38f;
          stat = __reduce_max_sync(0xffffffffu, __float_as_uint(n2));
          if (tid < 48) {
            const int d = tid & 15, sg = tid >> 4, j0 = sg == 0 ? 0 : (sg == 1 ? 10 : 22), j1 = sg == 0 ? 10 : (sg == 1 ? 22 : 32);
            const float sc = slot < NP ? 16.f : 0.125f, fb = slot < NP ? 1.f : 0.f;
            float kx[12], run = 0.f;
#pragma unroll
            for (int e = 0; e < 12; e++) kx[e] = ldsf(sT + (min(j0 + e, 31) * 17 + d) * 4);
#pragma unroll
            for (int e = 0; e < 12; e++) {
              const __half hv = __float2half_rn(fmaf(kx[e], sc, -run));
              run = fmaf(__half2float(hv), fb, run);
              if (j0 + e < j1) sts16(sH + ((j0 + e) * 16 + d) * 2, __half_as_ushort(hv));
            }
          }
        }
        if (lane == 0) sts32(sb + SM_MISC + 4 * (M_KVR + w), stat);
        bar_sync(3, 128);
        const uint32_t off = (isv ? SM_V / 16 : 0) + tok * 128 + slot * 2 + (hf ^ ((slot >> 2) & 1));
        uint4* dst = (tid < 64 ? g_kimg : g_kbf) + off;
        if (!isv && tid < 64) val = lds128(sH + tok * 32 + hf * 16);
        uint32_t chk = 0;
        if (tid < 64 || !isv) { *dst = val; chk = ld_back(dst); }
        mbar_wait(BAR(B_EPOCH), 0);
        consume(chk, sb);
        fence_async();
        bar_sync(3, 128);
        if (tid == 0) {
          const uint32_t s0 = lds32(sb + SM_MISC + 4 * M_KVR), s1 = lds32(sb + SM_MISC + 4 * (M_KVR + 1));
          const unsigned long long fl = ((unsigned long long)(lds32(sb + SM_MISC + 4 * M_EPOCH) + 1) << 32) | (isv ? (s0 | s1) : max(s0, s1));
          asm volatile("st.relaxed.gpu.global.b64 [%0], %1;" ::"l"(&g_kvflag[ai * 8 + aj]), "l"(fl) : "memory");
          TS(23);
        }
      } else if (wg == 3) {
        uint4* sW = reinterpret_cast<uint4*>(smem_raw + SM_GW);
        if (tid < 64) sW[tid] = __ldg(reinterpret_cast<const uint4*>(prm.gate_w) + tid);
        sts32(sb + SM_ONES + tid * 4, 0x3F803F80u);
        bar_sync(4, 128);
        const int v = tid & 7, rr = tid >> 3;
        float a[8];
#pragma unroll
        for (int p = 0; p < 8; p++) a[p] = 0.f;
#pragma unroll 1
        for (int c = 0; c < 8; c++) {
          const uint4 gv = sW[c * 8 + v];
          mbar_wait(BAR(B_XFULL + c), 0);
          if (tid == 0) TS(40 + c);
          const uint4* xr = reinterpret_cast<const uint4*>(smem_raw + SM_K + c * 16384 + rr * 128) + (v ^ (rr & 7));
#pragma unroll
          for (int p = 0; p < 8; p++) {
            const uint4 xv = xr[p * 128];
            float s = fmaf(bf_lo(xv.x), bf_lo(gv.x), a[p]), t = bf_hi(xv.x) * bf_hi(gv.x);
            s = fmaf(bf_lo(xv.y), bf_lo(gv.y), s); t = fmaf(bf_hi(xv.y), bf_hi(gv.y), t);
            s = fmaf(bf_lo(xv.z), bf_lo(gv.z), s); t = fmaf(bf_hi(xv.z), bf_hi(gv.z), t);
            s = fmaf(bf_lo(xv.w), bf_lo(gv.w), s); t = fmaf(bf_hi(xv.w), bf_hi(gv.w), t);
            a[p] = s + t;
          }
        }
        float mine = 0.f;
#pragma unroll
        for (int p = 0; p < 8; p++) {
          float s = a[p];
          s += __shfl_xor_sync(0xffffffffu, s, 1); s += __shfl_xor_sync(0xffffffffu, s, 2); s += __shfl_xor_sync(0xffffffffu, s, 4);
          if (v == p) mine = s;
        }
        const float gt = __fdividef(1.f, 1.f + __expf(-mine));
        sts32(sb + SM_G + (rr + 16 * v) * 4, __float_as_uint(gt));
        fence_async_smem();
        bar_sync(4, 128);
        if (aj == 0) g_gate[ai * 128 + tid] = ldsf(sb + SM_G + tid * 4);
        if (tid == 0) TS(8);
      }
#pragma unroll
      for (int k = 0; k < 64; k++) acc[k] = 0.f;
      regfence(acc);
      const int pass = wg >> 1;
#pragma unroll 1
      for (int c = 0; c < 8; c++) {
        mbar_wait(BAR(B_XFULL + c), 0);
        mbar_wait(BAR(B_WFULL + pass * 8 + c), 0);
        if (tid == 0 && half == pass) TS(48 + pass * 8 + c);
        const uint64_t da = mkdesc(sb + SM_K + c * 16384 + half * 8192, 16, 1024, 1);
        const uint64_t db = mkdesc(sb + wslot(pass * 8 + c), 2048, 512, 2);
        wg_fence();
#pragma unroll
        for (int k = 0; k < 4; k++) wg_ss_n128<0, 64>(acc, da + 2 * k, db + (k & 1) * 64 + (k >> 1) * 512);
        wg_commit();
        wg_wait<1>();
        if (tid == 0 && c > 0) {
          if (pass * 8 + c < 12) mbar_arrive_both(BAR(B_WEMPTY + pass * 8 + c - 1));
          if (pass) mbar_arrive_both(BAR(B_XEMPTY + c - 1));
        }
      }
      wg_wait<0>();
      if (tid == 0) mbar_arrive_both(BAR(pass ? B_XEMPTY + 7 : B_WEMPTY + 7));
      regfence(acc);
      if (tid == 0) TS(wg == 0 ? 16 : (wg == 2 ? 24 : (wg == 3 ? 9 : 95)));
      uint32_t qb[8];
      {
        float n2 = 0.f;
#pragma unroll
        for (int k = 0; k < 8; k++) qb[k] = pack_bf16(acc[48 + 2 * k], acc[49 + 2 * k]);
#pragma unroll
        for (int k = 0; k < 4; k++) {
          const uint32_t a = qb[4 * (k >> 1) + (k & 1)], b = qb[4 * (k >> 1) + (k & 1) + 2];
          float s = bf_lo(a) * bf_lo(a);
          s = fmaf(bf_hi(a), bf_hi(a), s); s = fmaf(bf_lo(b), bf_lo(b), s); s = fmaf(bf_hi(b), bf_hi(b), s);
          s += __shfl_xor_sync(0xffffffffu, s, 1); s += __shfl_xor_sync(0xffffffffu, s, 2);
          if (!(s <= 3.0e38f)) s = 3.0e38f;
          n2 = fmaxf(n2, s);
        }
        const uint32_t nmax = __reduce_max_sync(0xffffffffu, __float_as_uint(n2));
        if (lane == 0) { sts32(sb + SM_MISC + 4 * (M_RED + warp), nmax); mbar_arrive(BAR(B_KSTAT)); }
      }
      auto finish_q = [&]() {
        mbar_wait(BAR(B_KSTAT), 0);
        const float qn2 = __uint_as_float(__reduce_max_sync(0xffffffffu, lds32(sb + SM_MISC + 4 * (M_RED + (lane & 15)))));
        const float kn2 = ldsf(sb + SM_MISC + 4 * M_KN2);
        constexpr float SC = QSCALE * 0.125f;
        const bool fast = lds32(sb + SM_MISC + 4 * M_VOK) && qn2 <= 4.0e8f && kn2 <= 4.0e6f && qn2 * kn2 * (SC * SC) <= BOUND * BOUND;
        if (fast) {
#pragma unroll
          for (int k = 0; k < 8; k++) qb[k] = pack_f16(bf_lo(qb[k]) * QSCALE, bf_hi(qb[k]) * QSCALE);
        }
        sts128(sb + SM_Q + wg * 2048 + pass * 4096 + tid * 16, qb[0], qb[1], qb[2], qb[3]);
        sts128(sb + SM_Q + wg * 2048 + pass * 4096 + 4096 + tid * 16, qb[4], qb[5], qb[6], qb[7]);
        if (threadIdx.x == 256) { sts32(sb + SM_MISC + 4 * M_FAST, fast ? 1u : 0u); mbar_arrive(BAR(B_DEC)); }
        __syncwarp();
        if (lane == 0) mbar_arrive(BAR(B_QRDY));
        if (tid == 0 && pass) TS(75 + wg);
      };
      if (pass) finish_q();
#pragma unroll
      for (int k = 0; k < 48; k++) acc[k] = gelu_tanh(acc[k]);
      int fb0, c_lo = 0, c_hi = 12;
      if (wg < 2) { fb0 = aj < 6 ? 12 * aj - 2 : 22 + 8 * aj; if (aj == 0) c_lo = 2; if (aj >= 6) c_hi = 8; }
      else { fb0 = aj < 2 ? 8 * aj : 12 * aj - 8; if (aj < 2) c_hi = 8; if (aj == 7) c_hi = 10; }
      if (wg < 2) {
        const bool lo_ok = c_lo == 0, hi_ok = c_hi == 12;
        float s0 = 0.f, s1 = 0.f;
#pragma unroll
        for (int k = 0; k < 48; k++) {
          if ((k < 8 && !lo_ok) || (k >= 32 && !hi_ok)) acc[k] = 0.f;
          if (k & 2) s1 += acc[k]; else s0 += acc[k];
        }
        s0 += __shfl_xor_sync(0xffffffffu, s0, 1); s0 += __shfl_xor_sync(0xffffffffu, s0, 2);
        s1 += __shfl_xor_sync(0xffffffffu, s1, 1); s1 += __shfl_xor_sync(0xffffffffu, s1, 2);
        const float inv_n = __fdividef(0.125f, (float)(c_hi - c_lo));
        const float m0 = s0 * inv_n, m1 = s1 * inv_n;
        float v0 = 0.f, v1 = 0.f;
#pragma unroll
        for (int k = 0; k < 48; k++) {
          float d = acc[k] - ((k & 2) ? m1 : m0);
          if ((k < 8 && !lo_ok) || (k >= 32 && !hi_ok)) d = 0.f;
          if (k & 2) v1 = fmaf(d, d, v1); else v0 = fmaf(d, d, v0);
        }
        v0 += __shfl_xor_sync(0xffffffffu, v0, 1); v0 += __shfl_xor_sync(0xffffffffu, v0, 2);
        v1 += __shfl_xor_sync(0xffffffffu, v1, 1); v1 += __shfl_xor_sync(0xffffffffu, v1, 2);
        const int r0 = half * 64 + w * 16 + g;
        mbar_wait(BAR(B_EPOCH), 0);
        const unsigned ep1 = lds32(sb + SM_MISC + 4 * M_EPOCH) + 1;
        if (threadIdx.x == 0) TS(67);
        if (t4 < 2) {
          const float m = t4 ? m1 : m0, v = t4 ? v1 : v0;
          asm volatile("st.relaxed.gpu.global.v2.b64 [%0], {%1, %2};" ::"l"(&g_lnstat[(ai * 8 + aj) * 128 + r0 + 8 * t4]),
                       "l"(((unsigned long long)ep1 << 32) | __float_as_uint(m)), "l"(((unsigned long long)ep1 << 32) | __float_as_uint(v)) : "memory");
        }
        float sm[4], sv[4];
        const uint4* lp = &g_lnstat[(ai * 8 + 2 * t4) * 128 + r0];
#pragma unroll 1
        for (int n = 0; n < SPIN_LIMIT; n++) {
          uint32_t tg = ep1;
          if (lane < 8) tg = ld_back(reinterpret_cast<const uint32_t*>(&g_lnstat[(ai * 8 + lane) * 128 + half * 64 + w * 16 + 15]) + 3);
          if (__all_sync(0xffffffffu, tg == ep1)) break;
        }
#pragma unroll 1
        for (int n = 0; n < SPIN_LIMIT; n++) {
          bool ok = true;
#pragma unroll
          for (int e = 0; e < 4; e++) {
            unsigned long long a, b;
            asm volatile("ld.relaxed.gpu.global.v2.b64 {%0, %1}, [%2];" : "=l"(a), "=l"(b) : "l"(lp + (e >> 1) * 128 + (e & 1) * 8) : "memory");
            ok = ok && (uint32_t)(a >> 32) == ep1 && (uint32_t)(b >> 32) == ep1;
            sm[e] = __uint_as_float((uint32_t)a); sv[e] = __uint_as_float((uint32_t)b);
          }
          if (__all_sync(0xffffffffu, ok)) break;
        }
        if (threadIdx.x == 0) TS(68);
        const float na = t4 == 0 ? 80.f : (t4 == 3 ? 64.f : 96.f), nb = t4 == 3 ? 64.f : 96.f;
#pragma unroll
        for (int r = 0; r < 2; r++) {
          float t = fmaf(sm[r], na, sm[2 + r] * nb);
          t += __shfl_xor_sync(0xffffffffu, t, 1); t += __shfl_xor_sync(0xffffffffu, t, 2);
          const float mu = t * (1.f / 688.f);
          const float da = sm[r] - mu, db = sm[2 + r] - mu;
          float m2 = sv[r] + sv[2 + r] + na * da * da + nb * db * db;
          m2 += __shfl_xor_sync(0xffffffffu, m2, 1); m2 += __shfl_xor_sync(0xffffffffu, m2, 2);
          const float rs = rsqrtf(fmaf(m2, 1.f / 688.f, 1e-5f)), sh = -mu * rs;
#pragma unroll
          for (int k = 2 * r; k < 48; k += 4) { acc[k] = fmaf(acc[k], rs, sh); acc[k + 1] = fmaf(acc[k + 1], rs, sh); }
        }
        if (aj == 7) {
          c_hi = 10;
#pragma unroll
          for (int k = 32; k < 40; k++) acc[k] = 0.f;
        }
      }
      uint32_t* zp = wg < 2 ? reinterpret_cast<uint32_t*>(g_z2n) + (ai * 2 + half) * 2816 + w * 704
                            : reinterpret_cast<uint32_t*>(g_z1) + (ai * 88 * 16 + half * 8 + w * 2) * 32;
      const int mul = wg < 2 ? 373 : 0, cstr = wg < 2 ? 32 : 512, rstr = wg < 2 ? 352 : 32;
      auto zoff = [&](int c8) { const int fb = fb0 + c8; return ((fb * mul) >> 12) * (32 * 2816 - 352) + fb * cstr; };
#pragma unroll
      for (int c8 = 0; c8 < 12; c8++) {
        uint32_t* p = zp + zoff(c8) + lane;
        if (c8 >= c_lo && c8 < c_hi) { p[0] = pack_bf16(acc[4 * c8], acc[4 * c8 + 1]); p[rstr] = pack_bf16(acc[4 * c8 + 2], acc[4 * c8 + 3]); }
      }
      if (tid == 0) TS(wg == 0 ? 69 : 78 + wg);
      uint32_t chk = 0;
#pragma unroll
      for (int r = 0; r < 3; r++) {
        const int it = lane + 32 * r, c8 = it >> 3;
        if (c8 >= c_lo && c8 < c_hi) chk ^= ld_back(zp + zoff(c8) + ((it >> 2) & 1) * rstr + (it & 3) * 8);
      }
      if (wg == 3 && aj == 0) chk ^= ld_back(&g_gate[ai * 128 + tid]);
      consume(chk, sb);
      fence_async();
      bar_sync(1 + wg, 128);
      if (tid == 0) { red_relaxed(wg < 2 ? &g_zcnt[(ai * 2 + half) * 32] : &g_z1cnt[ai * 32]); TS(wg < 2 ? 20 + wg : 8 + wg * wg); }
      if (!pass) finish_q();
    }
    if (wg == 3) {
      asm volatile("setmaxnreg.inc.sync.aligned.u32 120;");
      int st = 0, ph = 0;
      {
        float acc[88];
#pragma unroll
        for (int k = 0; k < 88; k++) acc[k] = 0.f;
        regfence(acc);
#pragma unroll 1
        for (int n = 0; n < 32; n++) {
          mbar_wait(BAR(B_RFULL + st), ph);
          const uint64_t da = mkdesc(sb + SM_RING + st * RSTAGE, 16, 1024, 1);
          const uint64_t db = mkdesc(sb + SM_RING + st * RSTAGE + 16384, 1408, 128, 0);
#pragma unroll
          for (int k = 0; k < 4; k++) {
            wg_fence();
            wg_ss_n88<0, 88>(acc, da + 2 * k, db + 176 * k);
            wg_ss_n88<44, 88>(acc, da + 512 + 2 * k, db + 176 * k);
            wg_commit();
            wg_wait<0>();
          }
          if (tid == 0) mbar_arrive_both(BAR(B_REMPTY + st));
          if (++st == 3) { st = 0; ph ^= 1; }
        }
        regfence(acc);
        if (tid == 0) TS(11);
        mbar_wait(BAR(B_Z1OK), 0);
        const uint32_t* z1p = reinterpret_cast<const uint32_t*>(g_z1) + ((bi * 88 + bj * 11) * 16 + w * 2) * 32 + lane;
        uint32_t* up = reinterpret_cast<uint32_t*>(g_u) + bi * 11 * 4096 + w * 512 + lane;
#pragma unroll
        for (int r = 0; r < 4; r++) {
          const int row = bi * 128 + (r >> 1) * 64 + w * 16 + (r & 1) * 8 + g;
          const float og = 1.f - __ldcg(&g_gate[row]), bs = __bfloat162float(prm.b_sp[row]) * og;
          uint32_t zz[11];
#pragma unroll
          for (int c8 = 0; c8 < 11; c8++) zz[c8] = __ldcg(z1p + c8 * 512 + ((r >> 1) * 8 + (r & 1)) * 32);
          if (bj == 7) zz[9] = zz[10] = 0;
#pragma unroll
          for (int c8 = 0; c8 < 11; c8++) {
            const int k = (r >> 1) * 44 + c8 * 4 + (r & 1) * 2, cb = 11 * bj + c8;
            uint32_t v = pack_bf16(fmaf(acc[k], og, bs), fmaf(acc[k + 1], og, bs));
            asm("mul.rn.bf16x2 %0, %0, %1;" : "+r"(v) : "r"(zz[c8]));
            up[cb * 32 + (cb >> 3) * 3840 + ((r >> 1) * 8 + (r & 1)) * 256] = v;
          }
        }
        fence_async();
        bar_sync(4, 128);
        if (tid == 0) { red_release(&g_ucnt[bi * 32]); TS(12); }
      }
      float oc[64];
#pragma unroll
      for (int k = 0; k < 64; k++) oc[k] = 0.f;
      regfence(oc);
#pragma unroll 1
      for (int n = 0; n < 19; n++) {
        uint32_t sa, sw;
        if (n < 11) { mbar_wait(BAR(B_RFULL + st), ph); sa = SM_RING + st * RSTAGE; sw = sa + 16384; }
        else {
          if (n == 11) { if (tid == 0) TS(13); mbar_wait(BAR(B_WOFULL), 0); }
          mbar_wait(BAR(B_XFULL + n - 11), 1); sa = SM_K + (n - 11) * 16384; sw = SM_RING + (n - 11) * 8192;
        }
        const uint64_t da = mkdesc(sb + sa, 128, 1024, 0), db = mkdesc(sb + sw, 8192, 1024, 1);
#pragma unroll
        for (int k = 0; k < 4; k += 2) {
          wg_fence();
          wg_ss_n64<0, 64>(oc, da + 16 * k, db + 128 * k);
          wg_ss_n64<32, 64>(oc, da + 512 + 16 * k, db + 128 * k);
          wg_ss_n64<0, 64>(oc, da + 16 * k + 16, db + 128 * k + 128);
          wg_ss_n64<32, 64>(oc, da + 528 + 16 * k, db + 128 * k + 128);
          wg_commit();
          if (n < 11) wg_wait<0>();
        }
        if (n < 11) {
          if (tid == 0) mbar_arrive_both(BAR(B_REMPTY + st));
          if (++st == 3) { st = 0; ph ^= 1; }
        }
      }
      wg_wait<0>();
      regfence(oc);
      if (tid == 0) TS(14);
      uint32_t* op = reinterpret_cast<uint32_t*>(prm.out) + (bi * 128 + w * 16 + g) * 256 + bj * 32 + t4;
#pragma unroll
      for (int k = 0; k < 64; k += 2) {
        const int hf = k / 32, c8 = (k % 32) / 4, r8 = (k >> 1) & 1;
        op[(hf * 64 + r8 * 8) * 256 + c8 * 4] = pack_bf16(oc[k], oc[k + 1]);
      }
      if (tid == 0) TS(15);
    } else {
      mbar_wait(BAR(B_QRDY), 0);
    if (tid == 0) TS(25 + wg);
    mbar_wait(BAR(B_KVFULL), 0);
    if (tid == 0) TS(28 + wg);
    if (threadIdx.x == 0) GTS(125);
    const uint64_t dk0 = mkdesc(sb + SM_K, 16, 256, 3);
    const uint64_t dv0 = mkdesc(sb + SM_V, SM_ONES - SM_V, 256, 3);
    const int aw = wg == 0 ? 0 : 3 - wg;
    uint32_t chk = 0, pend = 0;
    float o[12], s[32];
    uint32_t q[4], p0[16], p1[16];
    if (lds32(sb + SM_MISC + 4 * M_FAST)) {
      const uint32_t mlo = prm.mlo, mhi = prm.mhi;
      uint64_t dk = dk0, dv = dv0;
#define STEP(PIN, POUT) { wg_fence(); issue_qk(s, q, dk); dk += 128; wg_commit(); issue_pv(o, PIN, dv); dv += (uint64_t)(4 * VSTEP); wg_commit(); \
                          wg_wait<1>(); regfence(s); softmax_step(s, POUT, mlo, mhi); wg_wait<0>(); }
#pragma unroll 1
      for (int sg = aw * 8; sg < aw * 8 + 8; sg++) {
        const int tau = sg / 3, seg = sg - tau * 3;
        int n2 = seg == 1 ? 6 : 5;
#pragma unroll
        for (int k = 0; k < NP / 2; k++) s[k] = MAGIC_C;
        if (sg == aw * 8 || seg == 0) {
          const int j0 = seg == 0 ? 0 : (seg == 1 ? 10 : 22);
          dk = dk0 + 128 * j0;
          dv = dv0 + VSTEP * (4 * j0);
          const uint4 qv = lds128(sb + SM_Q + tau * 2048 + tid * 16);
          q[0] = qv.x; q[1] = qv.y; q[2] = qv.z; q[3] = qv.w;
#pragma unroll
          for (int k = 0; k < 12; k++) o[k] = 0.f;
          regfence(o); regfence(s);
          wg_fence(); issue_qk(s, q, dk); dk += 128; wg_commit();
          wg_wait<0>(); regfence(s);
          softmax_step(s, p0, mlo, mhi);
          STEP(p0, p1);
          n2--;
        }
        regfence(s);
#pragma unroll 1
        for (; n2 > 0; n2--) { STEP(p1, p0); STEP(p0, p1); }
        if (sg == aw * 8 + 7 || seg == 2) {
          wg_fence(); issue_pv(o, p1, dv); dv += (uint64_t)(4 * VSTEP); wg_commit();
          wg_wait<0>(); regfence(o);
          if (sg == 8 || sg == 17) {
            float4* pp = g_part + (blockIdx.x * 2 + (aw - 1)) * 384 + tid;
            pp[0] = make_float4(o[0], o[1], o[2], o[3]); pp[128] = make_float4(o[4], o[5], o[6], o[7]); pp[256] = make_float4(o[8], o[9], o[10], o[11]);
            __threadfence_block();
            bar_arrive(5 + aw, 256);
          } else {
            if (sg == 7 || sg == 15) {
              bar_sync(6 + aw, 256);
              const float4* pp = g_part + (blockIdx.x * 2 + aw) * 384 + tid;
              const float4 a = pp[0], b = pp[128], c = pp[256];
              o[0] += a.x; o[1] += a.y; o[2] += a.z; o[3] += a.w; o[4] += b.x; o[5] += b.y; o[6] += b.z; o[7] += b.w; o[8] += c.x; o[10] += c.z;
            }
            { chk ^= pend; pend = store_o_tile(o, ai, aj, tau, tid, sb); }
          }
        }
      }
#undef STEP
    } else {
      mbar_wait(BAR(B_KFB), 0);
      constexpr float SC = 0.25f * 1.4426950408889634f;
#pragma unroll 1
      for (int tau = wg * 3; tau < wg * 3 + 3 && tau < 8; tau++) {
        const uint4 qv = lds128(sb + SM_Q + tau * 2048 + tid * 16);
        float m0 = -INFINITY, m1 = -INFINITY;
#pragma unroll
        for (int k = 0; k < 12; k++) o[k] = 0.f;
        uint64_t dv = dv0;
#pragma unroll 1
        for (int j = 0; j < 32; j++) {
          regfence(s);
          wg_fence(); wg_qkb_n64<0, 0, 32>(s, qv.x, qv.y, qv.z, qv.w, dk0 + 128 * j); wg_commit();
          wg_wait<0>(); regfence(s);
          float x0 = m0, x1 = m1;
#pragma unroll
          for (int k = 0; k < 32; k++) { s[k] *= SC; if (k & 2) x1 = fmaxf(x1, s[k]); else x0 = fmaxf(x0, s[k]); }
          x0 = fmaxf(x0, __shfl_xor_sync(0xffffffffu, x0, 1)); x0 = fmaxf(x0, __shfl_xor_sync(0xffffffffu, x0, 2));
          x1 = fmaxf(x1, __shfl_xor_sync(0xffffffffu, x1, 1)); x1 = fmaxf(x1, __shfl_xor_sync(0xffffffffu, x1, 2));
          const float c0 = ex2(m0 - x0), c1 = ex2(m1 - x1);
          m0 = x0; m1 = x1;
#pragma unroll
          for (int k = 0; k < 12; k++) o[k] *= (k & 2) ? c1 : c0;
#pragma unroll
          for (int k = 0; k < 16; k++) { const float m = (k & 1) ? m1 : m0; p0[k] = exp_mufu(s[2 * k] - m, s[2 * k + 1] - m); }
          regfence(o);
          wg_fence(); issue_pv(o, p0, dv); dv += (uint64_t)(4 * VSTEP); wg_commit();
          wg_wait<0>(); regfence(o);
        }
        { chk ^= pend; pend = store_o_tile(o, ai, aj, tau, tid, sb); }
      }
    }
    consume(chk ^ pend, sb);
    fence_async();
    bar_sync(1 + wg, 128);
    if (tid == 0) { red_relaxed(&g_ocnt[ai * 32]); mbar_arrive_both(BAR(B_ATT)); TS(31 + wg); if (wg == 0) GTS(124); }
    }
  }
  __syncwarp();
  asm volatile("barrier.cluster.arrive.relaxed;" ::: "memory");
  asm volatile("barrier.cluster.wait;" ::: "memory");
}

typedef CUresult (*EncodeFn)(CUtensorMap*, CUtensorMapDataType, cuuint32_t, void*, const cuuint64_t*, const cuuint64_t*,
                             const cuuint32_t*, const cuuint32_t*, CUtensorMapInterleave, CUtensorMapSwizzle,
                             CUtensorMapL2promotion, CUtensorMapFloatOOBfill);

void make_map(EncodeFn enc, CUtensorMap* tm, const void* base, uint64_t cols, uint64_t rows, uint32_t bc, uint32_t br, CUtensorMapSwizzle sw) {
  cuuint64_t gd[2] = {cols, rows};
  cuuint64_t gs[1] = {cols * 2};
  cuuint32_t bd[2] = {bc, br};
  cuuint32_t es[2] = {1, 1};
  enc(tm, CU_TENSOR_MAP_DATA_TYPE_BFLOAT16, 2, const_cast<void*>(base), gd, gs, bd, es, CU_TENSOR_MAP_INTERLEAVE_NONE, sw,
      CU_TENSOR_MAP_L2_PROMOTION_L2_128B, CU_TENSOR_MAP_FLOAT_OOB_FILL_NONE);
}

}

extern "C" void kernel_launch(void* const* d_in, const int* in_sizes, int n_in, void* d_out, int out_size) {
  (void)in_sizes; (void)n_in; (void)out_size;
  static EncodeFn enc = nullptr;
  if (!enc) {
    void* fn = nullptr;
    cudaDriverEntryPointQueryResult qr;
    cudaGetDriverEntryPoint("cuTensorMapEncodeTiled", &fn, cudaEnableDefault, &qr);
    enc = (EncodeFn)fn;
    cudaFuncSetAttribute(fused_kernel, cudaFuncAttributeMaxDynamicSharedMemorySize, SMEM_BYTES);
  }
  CUtensorMap tx, tq, tin, tsp, tout, to;
  make_map(enc, &tx, d_in[0], 512, 2048, 64, 128, CU_TENSOR_MAP_SWIZZLE_128B);
  make_map(enc, &tq, d_in[1], 512, 512, 32, 32, CU_TENSOR_MAP_SWIZZLE_64B);
  make_map(enc, &to, d_in[4], 512, 512, 64, 64, CU_TENSOR_MAP_SWIZZLE_128B);
  {
    cuuint64_t gd[3] = {32, 512, 43};
    cuuint64_t gs[2] = {1376 * 2, 64};
    cuuint32_t bd[3] = {32, 32, 3};
    cuuint32_t es[3] = {1, 1, 1};
    enc(&tin, CU_TENSOR_MAP_DATA_TYPE_BFLOAT16, 3, d_in[6], gd, gs, bd, es, CU_TENSOR_MAP_INTERLEAVE_NONE, CU_TENSOR_MAP_SWIZZLE_64B,
        CU_TENSOR_MAP_L2_PROMOTION_L2_128B, CU_TENSOR_MAP_FLOAT_OOB_FILL_NONE);
  }
  make_map(enc, &tsp, d_in[7], 2048, 2048, 64, 64, CU_TENSOR_MAP_SWIZZLE_128B);
  make_map(enc, &tout, d_in[9], 512, 688, 64, 64, CU_TENSOR_MAP_SWIZZLE_128B);
  Params prm;
  prm.gate_w = (const __nv_bfloat16*)d_in[10];
  prm.b_sp = (const __nv_bfloat16*)d_in[8];
  prm.w_out = (const __nv_bfloat16*)d_in[9];
  prm.wo = (const __nv_bfloat16*)d_in[4];
  prm.w_in = (const __nv_bfloat16*)d_in[6];
  prm.wq = (const __nv_bfloat16*)d_in[1];
  prm.wk = (const __nv_bfloat16*)d_in[2];
  prm.wv = (const __nv_bfloat16*)d_in[3];
  prm.mlo = 0x007F007Fu;
  prm.mhi = 0xFF80FF80u;
  prm.out = (__nv_bfloat16*)d_out;
  fused_kernel<<<NCTA, NTHREADS, SMEM_BYTES>>>(tx, tq, tin, tsp, tout, to, prm);
}
```

```cpp
#include <cuda_runtime.h>
#include <cuda.h>
#include <cuda_bf16.h>
#include <cuda_fp16.h>
#include <stdint.h>

namespace {

constexpr int NCTA = 128;
constexpr int NTHREADS = 640;
constexpr int NP = 40;
constexpr int NM = 64 - NP;
constexpr int SPIN_LIMIT = 1 << 18;

constexpr uint32_t SM_K = 0;
constexpr uint32_t SM_ONES = 131072;
constexpr uint32_t KV_BYTES = 131072;
constexpr uint32_t SM_BAR = 131584;
constexpr uint32_t SM_RING = 132096;
constexpr uint32_t RSTAGE = 27648;
constexpr uint32_t WSLOT = 16384;
constexpr uint32_t SM_WKV = SM_RING + 4 * WSLOT;
constexpr uint32_t SM_GW = SM_WKV + 16384;
constexpr uint32_t SM_Q = 215040;
constexpr uint32_t SM_G = 231424;
constexpr uint32_t SM_MISC = 231936;
constexpr uint32_t SMEM_BYTES = 232448;

constexpr int B_XFULL = 0, B_XEMPTY = 8, B_WFULL = 16, B_WEMPTY = 32, B_RFULL = 44, B_REMPTY = 47, B_KVFULL = 50,
              B_KFB = 51, B_KSTAT = 52, B_DEC = 53, B_WOFULL = 54, B_EPOCH = 55, B_ZOK = 56, B_Z1OK = 57, B_ATT = 58, B_QRDY = 59, B_LNOK = 60, B_KVB = 61, B_KVC = 62;
constexpr int M_EPOCH = 0, M_KN2 = 1, M_VOK = 2, M_FAST = 3, M_KVR = 4, M_RED = 16;

__device__ uint4 g_kimg[KV_BYTES / 16];
__device__ uint4 g_kbf[65536 / 16];
__device__ unsigned long long g_kvflag[NCTA];
__device__ uint4 g_lnstat[16 * 8 * 128];
__device__ float g_gate[2048];
__device__ uint4 g_z2n[8 * 32 * 11264 / 16];
__device__ uint4 g_z1[16 * 88 * 128];
__device__ uint4 g_u[16 * 11 * 1024];
__device__ uint4 g_o[16 * 8 * 1024];
__device__ float4 g_part[NCTA * 2 * 3 * 128];
__device__ unsigned g_ticket;
__device__ unsigned g_zcnt[32 * 32];
__device__ unsigned g_z1cnt[16 * 32];
__device__ unsigned g_ucnt[16 * 32];
__device__ unsigned g_ocnt[16 * 32];
#define TS(k) do { } while (0)
#define GTS(k) do { } while (0)

__device__ __forceinline__ void mbar_init(uint32_t a, uint32_t c) { asm volatile("mbarrier.init.shared::cta.b64 [%0], %1;" ::"r"(a), "r"(c) : "memory"); }
__device__ __forceinline__ void mbar_arrive(uint32_t a) { asm volatile("mbarrier.arrive.shared::cta.b64 _, [%0];" ::"r"(a) : "memory"); }
__device__ __forceinline__ void mbar_arrive_both(uint32_t a) {
  asm volatile("{\n.reg .b32 ra;\nmapa.shared::cluster.u32 ra, %0, 0;\nmbarrier.arrive.shared::cluster.b64 _, [ra];\n"
               "mapa.shared::cluster.u32 ra, %0, 1;\nmbarrier.arrive.shared::cluster.b64 _, [ra];\n}" ::"r"(a) : "memory");
}
__device__ __forceinline__ void mbar_wait(uint32_t a, uint32_t ph) {
  uint32_t ok;
#pragma unroll 1
  for (int n = 0; n < SPIN_LIMIT; n++) {
    asm volatile("{\n.reg .pred p;\nmbarrier.try_wait.parity.shared::cta.b64 p, [%1], %2;\nselp.u32 %0, 1, 0, p;\n}" : "=r"(ok) : "r"(a), "r"(ph) : "memory");
    if (ok) break;
  }
}
#define ELECT "{\n.reg .pred p;\nelect.sync _|p, 0xffffffff;\n@p "
__device__ __forceinline__ void e_expect(uint32_t a, uint32_t b) { asm volatile(ELECT "mbarrier.arrive.expect_tx.shared::cta.b64 _, [%0], %1;\n}" ::"r"(a), "r"(b) : "memory"); }
__device__ __forceinline__ void e_arrive(uint32_t a) { asm volatile(ELECT "mbarrier.arrive.shared::cta.b64 _, [%0];\n}" ::"r"(a) : "memory"); }
__device__ __forceinline__ void tma2d(uint32_t dst, const CUtensorMap* tm, int c0, int c1, uint32_t bar) {
  asm volatile(ELECT "cp.async.bulk.tensor.2d.shared::cluster.global.mbarrier::complete_tx::bytes [%0], [%1, {%3, %4}], [%2];\n}"
               ::"r"(dst), "l"(tm), "r"(bar), "r"(c0), "r"(c1) : "memory");
}
__device__ __forceinline__ void tma2d_mc(uint32_t dst, const CUtensorMap* tm, int c0, int c1, uint32_t bar) {
  asm volatile(ELECT "cp.async.bulk.tensor.2d.shared::cluster.global.mbarrier::complete_tx::bytes.multicast::cluster [%0], [%1, {%3, %4}], [%2], %5;\n}"
               ::"r"(dst), "l"(tm), "r"(bar), "r"(c0), "r"(c1), "h"((uint16_t)3) : "memory");
}
__device__ __forceinline__ void tma3d(uint32_t dst, const CUtensorMap* tm, int c0, int c1, int c2, uint32_t bar) {
  asm volatile(ELECT "cp.async.bulk.tensor.3d.shared::cluster.global.mbarrier::complete_tx::bytes [%0], [%1, {%3, %4, %5}], [%2];\n}"
               ::"r"(dst), "l"(tm), "r"(bar), "r"(c0), "r"(c1), "r"(c2) : "memory");
}
__device__ __forceinline__ void tma3d_mc(uint32_t dst, const CUtensorMap* tm, int c0, int c1, int c2, uint32_t bar) {
  asm volatile(ELECT "cp.async.bulk.tensor.3d.shared::cluster.global.mbarrier::complete_tx::bytes.multicast::cluster [%0], [%1, {%3, %4, %5}], [%2], %6;\n}"
               ::"r"(dst), "l"(tm), "r"(bar), "r"(c0), "r"(c1), "r"(c2), "h"((uint16_t)3) : "memory");
}
__device__ __forceinline__ void tma2d_pf(const CUtensorMap* tm, int c0, int c1) {
  asm volatile(ELECT "cp.async.bulk.prefetch.tensor.2d.L2.global [%0, {%1, %2}];\n}" ::"l"(tm), "r"(c0), "r"(c1) : "memory");
}
__device__ __forceinline__ void tm_prefetch(const CUtensorMap* tm) { asm volatile(ELECT "prefetch.tensormap [%0];\n}" ::"l"(tm) : "memory"); }
__device__ __forceinline__ void bulk(uint32_t dst, const void* src, uint32_t bytes, uint32_t bar) {
  asm volatile(ELECT "cp.async.bulk.shared::cluster.global.mbarrier::complete_tx::bytes [%0], [%1], %2, [%3];\n}"
               ::"r"(dst), "l"(src), "r"(bytes), "r"(bar) : "memory");
}
__device__ __forceinline__ void bulk_mc(uint32_t dst, const void* src, uint32_t bytes, uint32_t bar) {
  asm volatile(ELECT "cp.async.bulk.shared::cluster.global.mbarrier::complete_tx::bytes.multicast::cluster [%0], [%1], %2, [%3], %4;\n}"
               ::"r"(dst), "l"(src), "r"(bytes), "r"(bar), "h"((uint16_t)3) : "memory");
}
__device__ __forceinline__ void l2_prefetch(const void* src, uint32_t bytes) { asm volatile(ELECT "cp.async.bulk.prefetch.L2.global [%0], %1;\n}" ::"l"(src), "r"(bytes) : "memory"); }
__device__ __forceinline__ void fence_async() { asm volatile("fence.proxy.async.global;" ::: "memory"); }
__device__ __forceinline__ void fence_async_smem() { asm volatile("fence.proxy.async.shared::cta;" ::: "memory"); }
__device__ __forceinline__ void bar_sync(int id, int n) { asm volatile("bar.sync %0, %1;" ::"r"(id), "r"(n) : "memory"); }
__device__ __forceinline__ void bar_arrive(int id, int n) { asm volatile("bar.arrive %0, %1;" ::"r"(id), "r"(n) : "memory"); }
__device__ __forceinline__ void red_release(unsigned* p) { asm volatile("red.release.gpu.global.add.u32 [%0], 1;" ::"l"(p) : "memory"); }
__device__ __forceinline__ void red_relaxed(unsigned* p) { asm volatile("red.relaxed.gpu.global.add.u32 [%0], 1;" ::"l"(p) : "memory"); }
__device__ __forceinline__ uint32_t ld_back(const void* p) { uint32_t v; asm volatile("ld.relaxed.gpu.global.u32 %0, [%1];" : "=r"(v) : "l"(p) : "memory"); return v; }
__device__ __forceinline__ void consume(uint32_t v, uint32_t sb) { if (v == 0xDEADBEEFu) asm volatile("st.shared.u32 [%0], %1;" ::"r"(sb + SM_MISC + 60), "r"(v) : "memory"); }
__device__ __forceinline__ unsigned ld_acquire(const unsigned* p) { unsigned v; asm volatile("ld.acquire.gpu.global.u32 %0, [%1];" : "=r"(v) : "l"(p) : "memory"); return v; }
__device__ __forceinline__ void wait_ge(const unsigned* p, unsigned target) {
#pragma unroll 1
  for (int n = 0; n < SPIN_LIMIT; n++) {
    if ((int)(ld_acquire(p) - target) >= 0) break;
    __nanosleep(100);
  }
}
__device__ __forceinline__ void wg_fence() { asm volatile("wgmma.fence.sync.aligned;" ::: "memory"); }
__device__ __forceinline__ void wg_commit() { asm volatile("wgmma.commit_group.sync.aligned;" ::: "memory"); }
template <int N> __device__ __forceinline__ void wg_wait() { asm volatile("wgmma.wait_group.sync.aligned %0;" ::"n"(N) : "memory"); }
template <int n> __device__ __forceinline__ void regfence(float (&d)[n]) {
#pragma unroll
  for (int i = 0; i < n; i++) asm volatile("" : "+f"(d[i])::"memory");
}
__device__ __forceinline__ uint64_t mkdesc(uint32_t addr, uint32_t lbo, uint32_t sbo, int swz) {
  return (uint64_t)((addr & 0x3FFFF) >> 4) | ((uint64_t)(lbo >> 4) << 16) | ((uint64_t)(sbo >> 4) << 32) | ((uint64_t)swz << 62);
}
__device__ __forceinline__ uint32_t pack_bf16(float lo, float hi) { uint32_t r; asm("cvt.rn.bf16x2.f32 %0, %1, %2;" : "=r"(r) : "f"(hi), "f"(lo)); return r; }
__device__ __forceinline__ uint32_t pack_f16(float lo, float hi) { uint32_t r; asm("cvt.rn.f16x2.f32 %0, %1, %2;" : "=r"(r) : "f"(hi), "f"(lo)); return r; }
__device__ __forceinline__ float bf_lo(uint32_t v) { return __uint_as_float(v << 16); }
__device__ __forceinline__ float bf_hi(uint32_t v) { return __uint_as_float(v & 0xFFFF0000u); }
__device__ __forceinline__ float ex2(float x) { float r; asm("ex2.approx.ftz.f32 %0, %1;" : "=f"(r) : "f"(x)); return r; }
__device__ __forceinline__ float gelu2_tanh(float x) {
  float u = x * fmaf(x * x, 0.0356774081f, 0.7978845608f), t;
  asm("tanh.approx.f32 %0, %1;" : "=f"(t) : "f"(u));
  return fmaf(x, t, x);
}
__device__ __forceinline__ void sts32(uint32_t a, uint32_t v) { asm volatile("st.shared.u32 [%0], %1;" ::"r"(a), "r"(v) : "memory"); }
__device__ __forceinline__ void sts16(uint32_t a, uint16_t v) { asm volatile("st.shared.u16 [%0], %1;" ::"r"(a), "h"(v) : "memory"); }
__device__ __forceinline__ void sts128(uint32_t a, uint32_t x, uint32_t y, uint32_t z, uint32_t w) { asm volatile("st.shared.v4.u32 [%0], {%1,%2,%3,%4};" ::"r"(a), "r"(x), "r"(y), "r"(z), "r"(w) : "memory"); }
__device__ __forceinline__ uint32_t lds32(uint32_t a) { uint32_t v; asm volatile("ld.shared.u32 %0, [%1];" : "=r"(v) : "r"(a) : "memory"); return v; }
__device__ __forceinline__ float ldsf(uint32_t a) { return __uint_as_float(lds32(a)); }
__device__ __forceinline__ uint4 lds128(uint32_t a) { uint4 v; asm volatile("ld.shared.v4.u32 {%0,%1,%2,%3}, [%4];" : "=r"(v.x), "=r"(v.y), "=r"(v.z), "=r"(v.w) : "r"(a) : "memory"); return v; }

template<int OFF, int TOT> __device__ __forceinline__ void wg_ss_n88(float (&d)[TOT], uint64_t da, uint64_t db) {
  asm volatile("wgmma.mma_async.sync.aligned.m64n88k16.f32.bf16.bf16 {%0, %1, %2, %3, %4, %5, %6, %7, %8, %9, %10, %11, %12, %13, %14, %15, %16, %17, %18, %19, %20, %21, %22, %23, %24, %25, %26, %27, %28, %29, %30, %31, %32, %33, %34, %35, %36, %37, %38, %39, %40, %41, %42, %43}, %44, %45, 1, 1, 1, 0, 1;"
    : "+f"(d[OFF+0]), "+f"(d[OFF+1]), "+f"(d[OFF+2]), "+f"(d[OFF+3]), "+f"(d[OFF+4]), "+f"(d[OFF+5]), "+f"(d[OFF+6]), "+f"(d[OFF+7]),
      "+f"(d[OFF+8]), "+f"(d[OFF+9]), "+f"(d[OFF+10]), "+f"(d[OFF+11]), "+f"(d[OFF+12]), "+f"(d[OFF+13]), "+f"(d[OFF+14]), "+f"(d[OFF+15]),
      "+f"(d[OFF+16]), "+f"(d[OFF+17]), "+f"(d[OFF+18]), "+f"(d[OFF+19]), "+f"(d[OFF+20]), "+f"(d[OFF+21]), "+f"(d[OFF+22]), "+f"(d[OFF+23]),
      "+f"(d[OFF+24]), "+f"(d[OFF+25]), "+f"(d[OFF+26]), "+f"(d[OFF+27]), "+f"(d[OFF+28]), "+f"(d[OFF+29]), "+f"(d[OFF+30]), "+f"(d[OFF+31]),
      "+f"(d[OFF+32]), "+f"(d[OFF+33]), "+f"(d[OFF+34]), "+f"(d[OFF+35]), "+f"(d[OFF+36]), "+f"(d[OFF+37]), "+f"(d[OFF+38]), "+f"(d[OFF+39]),
      "+f"(d[OFF+40]), "+f"(d[OFF+41]), "+f"(d[OFF+42]), "+f"(d[OFF+43])
    : "l"(da), "l"(db));
}
template<int OFF, int TOT> __device__ __forceinline__ void wg_ss_n128(float (&d)[TOT], uint64_t da, uint64_t db) {
  asm volatile("wgmma.mma_async.sync.aligned.m64n128k16.f32.bf16.bf16 {%0, %1, %2, %3, %4, %5, %6, %7, %8, %9, %10, %11, %12, %13, %14, %15, %16, %17, %18, %19, %20, %21, %22, %23, %24, %25, %26, %27, %28, %29, %30, %31, %32, %33, %34, %35, %36, %37, %38, %39, %40, %41, %42, %43, %44, %45, %46, %47, %48, %49, %50, %51, %52, %53, %54, %55, %56, %57, %58, %59, %60, %61, %62, %63}, %64, %65, 1, 1, 1, 0, 1;"
    : "+f"(d[OFF+0]), "+f"(d[OFF+1]), "+f"(d[OFF+2]), "+f"(d[OFF+3]), "+f"(d[OFF+4]), "+f"(d[OFF+5]), "+f"(d[OFF+6]), "+f"(d[OFF+7]),
      "+f"(d[OFF+8]), "+f"(d[OFF+9]), "+f"(d[OFF+10]), "+f"(d[OFF+11]), "+f"(d[OFF+12]), "+f"(d[OFF+13]), "+f"(d[OFF+14]), "+f"(d[OFF+15]),
      "+f"(d[OFF+16]), "+f"(d[OFF+17]), "+f"(d[OFF+18]), "+f"(d[OFF+19]), "+f"(d[OFF+20]), "+f"(d[OFF+21]), "+f"(d[OFF+22]), "+f"(d[OFF+23]),
      "+f"(d[OFF+24]), "+f"(d[OFF+25]), "+f"(d[OFF+26]), "+f"(d[OFF+27]), "+f"(d[OFF+28]), "+f"(d[OFF+29]), "+f"(d[OFF+30]), "+f"(d[OFF+31]),
      "+f"(d[OFF+32]), "+f"(d[OFF+33]), "+f"(d[OFF+34]), "+f"(d[OFF+35]), "+f"(d[OFF+36]), "+f"(d[OFF+37]), "+f"(d[OFF+38]), "+f"(d[OFF+39]),
      "+f"(d[OFF+40]), "+f"(d[OFF+41]), "+f"(d[OFF+42]), "+f"(d[OFF+43]), "+f"(d[OFF+44]), "+f"(d[OFF+45]), "+f"(d[OFF+46]), "+f"(d[OFF+47]),
      "+f"(d[OFF+48]), "+f"(d[OFF+49]), "+f"(d[OFF+50]), "+f"(d[OFF+51]), "+f"(d[OFF+52]), "+f"(d[OFF+53]), "+f"(d[OFF+54]), "+f"(d[OFF+55]),
      "+f"(d[OFF+56]), "+f"(d[OFF+57]), "+f"(d[OFF+58]), "+f"(d[OFF+59]), "+f"(d[OFF+60]), "+f"(d[OFF+61]), "+f"(d[OFF+62]), "+f"(d[OFF+63])
    : "l"(da), "l"(db));
}
template<int OFF, int TOT> __device__ __forceinline__ void wg_ss_n64(float (&d)[TOT], uint64_t da, uint64_t db) {
  asm volatile("wgmma.mma_async.sync.aligned.m64n64k16.f32.bf16.bf16 {%0, %1, %2, %3, %4, %5, %6, %7, %8, %9, %10, %11, %12, %13, %14, %15, %16, %17, %18, %19, %20, %21, %22, %23, %24, %25, %26, %27, %28, %29, %30, %31}, %32, %33, 1, 1, 1, 0, 1;"
    : "+f"(d[OFF+0]), "+f"(d[OFF+1]), "+f"(d[OFF+2]), "+f"(d[OFF+3]), "+f"(d[OFF+4]), "+f"(d[OFF+5]), "+f"(d[OFF+6]), "+f"(d[OFF+7]),
      "+f"(d[OFF+8]), "+f"(d[OFF+9]), "+f"(d[OFF+10]), "+f"(d[OFF+11]), "+f"(d[OFF+12]), "+f"(d[OFF+13]), "+f"(d[OFF+14]), "+f"(d[OFF+15]),
      "+f"(d[OFF+16]), "+f"(d[OFF+17]), "+f"(d[OFF+18]), "+f"(d[OFF+19]), "+f"(d[OFF+20]), "+f"(d[OFF+21]), "+f"(d[OFF+22]), "+f"(d[OFF+23]),
      "+f"(d[OFF+24]), "+f"(d[OFF+25]), "+f"(d[OFF+26]), "+f"(d[OFF+27]), "+f"(d[OFF+28]), "+f"(d[OFF+29]), "+f"(d[OFF+30]), "+f"(d[OFF+31])
    : "l"(da), "l"(db));
}
template<int OFF, int TOT> __device__ __forceinline__ void wg_ss_n32t(float (&d)[TOT], uint64_t da, uint64_t db) {
  asm volatile("wgmma.mma_async.sync.aligned.m64n32k16.f32.bf16.bf16 {%0, %1, %2, %3, %4, %5, %6, %7, %8, %9, %10, %11, %12, %13, %14, %15}, %16, %17, 1, 1, 1, 1, 0;"
    : "+f"(d[OFF+0]), "+f"(d[OFF+1]), "+f"(d[OFF+2]), "+f"(d[OFF+3]), "+f"(d[OFF+4]), "+f"(d[OFF+5]), "+f"(d[OFF+6]), "+f"(d[OFF+7]),
      "+f"(d[OFF+8]), "+f"(d[OFF+9]), "+f"(d[OFF+10]), "+f"(d[OFF+11]), "+f"(d[OFF+12]), "+f"(d[OFF+13]), "+f"(d[OFF+14]), "+f"(d[OFF+15])
    : "l"(da), "l"(db));
}
template<int SCD, int OFF, int TOT> __device__ __forceinline__ void wg_qk_n16(float (&d)[TOT], uint32_t a0, uint32_t a1, uint32_t a2, uint32_t a3, uint64_t db) {
  asm volatile("wgmma.mma_async.sync.aligned.m64n16k16.f32.f16.f16 {%0, %1, %2, %3, %4, %5, %6, %7}, {%8,%9,%10,%11}, %12, %13, 1, 1, 0;"
    : "+f"(d[OFF+0]), "+f"(d[OFF+1]), "+f"(d[OFF+2]), "+f"(d[OFF+3]), "+f"(d[OFF+4]), "+f"(d[OFF+5]), "+f"(d[OFF+6]), "+f"(d[OFF+7])
    : "r"(a0), "r"(a1), "r"(a2), "r"(a3), "l"(db), "n"(SCD));
}
template<int SCD, int OFF, int TOT> __device__ __forceinline__ void wg_qk_n24(float (&d)[TOT], uint32_t a0, uint32_t a1, uint32_t a2, uint32_t a3, uint64_t db) {
  asm volatile("wgmma.mma_async.sync.aligned.m64n24k16.f32.f16.f16 {%0, %1, %2, %3, %4, %5, %6, %7, %8, %9, %10, %11}, {%12,%13,%14,%15}, %16, %17, 1, 1, 0;"
    : "+f"(d[OFF+0]), "+f"(d[OFF+1]), "+f"(d[OFF+2]), "+f"(d[OFF+3]), "+f"(d[OFF+4]), "+f"(d[OFF+5]), "+f"(d[OFF+6]), "+f"(d[OFF+7]),
      "+f"(d[OFF+8]), "+f"(d[OFF+9]), "+f"(d[OFF+10]), "+f"(d[OFF+11])
    : "r"(a0), "r"(a1), "r"(a2), "r"(a3), "l"(db), "n"(SCD));
}
template<int SCD, int OFF, int TOT> __device__ __forceinline__ void wg_qk_n32(float (&d)[TOT], uint32_t a0, uint32_t a1, uint32_t a2, uint32_t a3, uint64_t db) {
  asm volatile("wgmma.mma_async.sync.aligned.m64n32k16.f32.f16.f16 {%0, %1, %2, %3, %4, %5, %6, %7, %8, %9, %10, %11, %12, %13, %14, %15}, {%16,%17,%18,%19}, %20, %21, 1, 1, 0;"
    : "+f"(d[OFF+0]), "+f"(d[OFF+1]), "+f"(d[OFF+2]), "+f"(d[OFF+3]), "+f"(d[OFF+4]), "+f"(d[OFF+5]), "+f"(d[OFF+6]), "+f"(d[OFF+7]),
      "+f"(d[OFF+8]), "+f"(d[OFF+9]), "+f"(d[OFF+10]), "+f"(d[OFF+11]), "+f"(d[OFF+12]), "+f"(d[OFF+13]), "+f"(d[OFF+14]), "+f"(d[OFF+15])
    : "r"(a0), "r"(a1), "r"(a2), "r"(a3), "l"(db), "n"(SCD));
}
template<int SCD, int OFF, int TOT> __device__ __forceinline__ void wg_qk_n40(float (&d)[TOT], uint32_t a0, uint32_t a1, uint32_t a2, uint32_t a3, uint64_t db) {
  asm volatile("wgmma.mma_async.sync.aligned.m64n40k16.f32.f16.f16 {%0, %1, %2, %3, %4, %5, %6, %7, %8, %9, %10, %11, %12, %13, %14, %15, %16, %17, %18, %19}, {%20,%21,%22,%23}, %24, %25, 1, 1, 0;"
    : "+f"(d[OFF+0]), "+f"(d[OFF+1]), "+f"(d[OFF+2]), "+f"(d[OFF+3]), "+f"(d[OFF+4]), "+f"(d[OFF+5]), "+f"(d[OFF+6]), "+f"(d[OFF+7]),
      "+f"(d[OFF+8]), "+f"(d[OFF+9]), "+f"(d[OFF+10]), "+f"(d[OFF+11]), "+f"(d[OFF+12]), "+f"(d[OFF+13]), "+f"(d[OFF+14]), "+f"(d[OFF+15]),
      "+f"(d[OFF+16]), "+f"(d[OFF+17]), "+f"(d[OFF+18]), "+f"(d[OFF+19])
    : "r"(a0), "r"(a1), "r"(a2), "r"(a3), "l"(db), "n"(SCD));
}
template<int SCD, int OFF, int TOT> __device__ __forceinline__ void wg_qk_n48(float (&d)[TOT], uint32_t a0, uint32_t a1, uint32_t a2, uint32_t a3, uint64_t db) {
  asm volatile("wgmma.mma_async.sync.aligned.m64n48k16.f32.f16.f16 {%0, %1, %2, %3, %4, %5, %6, %7, %8, %9, %10, %11, %12, %13, %14, %15, %16, %17, %18, %19, %20, %21, %22, %23}, {%24,%25,%26,%27}, %28, %29, 1, 1, 0;"
    : "+f"(d[OFF+0]), "+f"(d[OFF+1]), "+f"(d[OFF+2]), "+f"(d[OFF+3]), "+f"(d[OFF+4]), "+f"(d[OFF+5]), "+f"(d[OFF+6]), "+f"(d[OFF+7]),
      "+f"(d[OFF+8]), "+f"(d[OFF+9]), "+f"(d[OFF+10]), "+f"(d[OFF+11]), "+f"(d[OFF+12]), "+f"(d[OFF+13]), "+f"(d[OFF+14]), "+f"(d[OFF+15]),
      "+f"(d[OFF+16]), "+f"(d[OFF+17]), "+f"(d[OFF+18]), "+f"(d[OFF+19]), "+f"(d[OFF+20]), "+f"(d[OFF+21]), "+f"(d[OFF+22]), "+f"(d[OFF+23])
    : "r"(a0), "r"(a1), "r"(a2), "r"(a3), "l"(db), "n"(SCD));
}
template<int SCD, int OFF, int TOT> __device__ __forceinline__ void wg_pv_n24(float (&d)[TOT], uint32_t a0, uint32_t a1, uint32_t a2, uint32_t a3, uint64_t db) {
  asm volatile("wgmma.mma_async.sync.aligned.m64n24k16.f32.bf16.bf16 {%0, %1, %2, %3, %4, %5, %6, %7, %8, %9, %10, %11}, {%12,%13,%14,%15}, %16, %17, 1, 1, 1;"
    : "+f"(d[OFF+0]), "+f"(d[OFF+1]), "+f"(d[OFF+2]), "+f"(d[OFF+3]), "+f"(d[OFF+4]), "+f"(d[OFF+5]), "+f"(d[OFF+6]), "+f"(d[OFF+7]),
      "+f"(d[OFF+8]), "+f"(d[OFF+9]), "+f"(d[OFF+10]), "+f"(d[OFF+11])
    : "r"(a0), "r"(a1), "r"(a2), "r"(a3), "l"(db), "n"(SCD));
}
template<int SCD, int OFF, int TOT> __device__ __forceinline__ void wg_qkb_n64(float (&d)[TOT], uint32_t a0, uint32_t a1, uint32_t a2, uint32_t a3, uint64_t db) {
  asm volatile("wgmma.mma_async.sync.aligned.m64n64k16.f32.bf16.bf16 {%0, %1, %2, %3, %4, %5, %6, %7, %8, %9, %10, %11, %12, %13, %14, %15, %16, %17, %18, %19, %20, %21, %22, %23, %24, %25, %26, %27, %28, %29, %30, %31}, {%32,%33,%34,%35}, %36, %37, 1, 1, 0;"
    : "+f"(d[OFF+0]), "+f"(d[OFF+1]), "+f"(d[OFF+2]), "+f"(d[OFF+3]), "+f"(d[OFF+4]), "+f"(d[OFF+5]), "+f"(d[OFF+6]), "+f"(d[OFF+7]),
      "+f"(d[OFF+8]), "+f"(d[OFF+9]), "+f"(d[OFF+10]), "+f"(d[OFF+11]), "+f"(d[OFF+12]), "+f"(d[OFF+13]), "+f"(d[OFF+14]), "+f"(d[OFF+15]),
      "+f"(d[OFF+16]), "+f"(d[OFF+17]), "+f"(d[OFF+18]), "+f"(d[OFF+19]), "+f"(d[OFF+20]), "+f"(d[OFF+21]), "+f"(d[OFF+22]), "+f"(d[OFF+23]),
      "+f"(d[OFF+24]), "+f"(d[OFF+25]), "+f"(d[OFF+26]), "+f"(d[OFF+27]), "+f"(d[OFF+28]), "+f"(d[OFF+29]), "+f"(d[OFF+30]), "+f"(d[OFF+31])
    : "r"(a0), "r"(a1), "r"(a2), "r"(a3), "l"(db), "n"(SCD));
}
template<int N, int SCD, int OFF, int TOT> __device__ __forceinline__ void wg_qk(float (&d)[TOT], const uint32_t (&q)[4], uint64_t db) {
  if constexpr (N == 16) wg_qk_n16<SCD, OFF, TOT>(d, q[0], q[1], q[2], q[3], db);
  if constexpr (N == 24) wg_qk_n24<SCD, OFF, TOT>(d, q[0], q[1], q[2], q[3], db);
  if constexpr (N == 32) wg_qk_n32<SCD, OFF, TOT>(d, q[0], q[1], q[2], q[3], db);
  if constexpr (N == 40) wg_qk_n40<SCD, OFF, TOT>(d, q[0], q[1], q[2], q[3], db);
  if constexpr (N == 48) wg_qk_n48<SCD, OFF, TOT>(d, q[0], q[1], q[2], q[3], db);
}

__device__ __forceinline__ uint32_t exp_mufu(float a, float b) { return pack_bf16(ex2(a), ex2(b)); }
__device__ __forceinline__ uint32_t exp_poly(float a, float b, uint32_t mlo, uint32_t mhi) {
  uint32_t u = __byte_perm(__float_as_uint(a), __float_as_uint(b), 0x6521), mh, e, p;
  asm("lop3.b32 %0, %1, %2, 0x3F003F00, 0xEA;" : "=r"(mh) : "r"(u), "r"(mlo));
  asm("lop3.b32 %0, %1, %2, 0x00020002, 0xEA;" : "=r"(e) : "r"(u), "r"(mhi));
  asm("fma.rn.bf16x2 %0, %1, %2, %3;" : "=r"(p) : "r"(u), "r"(mh), "r"(e));
  return p;
}
constexpr float MAGIC_C = 48948.0625f;
constexpr float QSCALE = 0.25f * 1.4426950408889634f * 8.f;
constexpr float BOUND = 80.f;

__device__ __forceinline__ void softmax_step(const float (&s)[32], uint32_t (&p)[16], uint32_t mlo, uint32_t mhi) {
  constexpr int PP = NP / 4;
  int ip = 0, im = PP;
#pragma unroll
  for (int i = 0; i < 16; i++) {
    if (((i + 1) * PP / 16) > (i * PP / 16)) { p[ip] = exp_poly(s[2 * ip], s[2 * ip + 1], mlo, mhi); ip++; }
    else { p[im] = exp_mufu(s[2 * im], s[2 * im + 1]); im++; }
  }
}
constexpr int64_t VSTEP = 32 - (32 << 16);
constexpr uint64_t KSTEP = 256, VSTEP8 = (uint64_t)(8 * VSTEP);
__device__ __forceinline__ void issue_qk(float (&s)[32], const uint32_t (&q)[4], uint64_t dk) {
  wg_qk<NM, 0, NP / 2, 32>(s, q, dk + NP * 2);
  wg_qk<NP, 1, 0, 32>(s, q, dk);
}
__device__ __forceinline__ void issue_pv(float (&o)[12], const uint32_t (&p)[16], uint64_t dv) {
#pragma unroll
  for (int c = 0; c < 4; c++) { wg_pv_n24<1, 0, 12>(o, p[4 * c], p[4 * c + 1], p[4 * c + 2], p[4 * c + 3], dv + c * VSTEP); }
}

__device__ __forceinline__ uint32_t wslot(int f) { const int r = f - 5 * ((f * 52) >> 8); return r == 4 ? SM_Q : SM_RING + r * WSLOT; }

struct Params {
  const __nv_bfloat16* gate_w;
  const __nv_bfloat16* b_sp;
  const __nv_bfloat16* w_out;
  const __nv_bfloat16* wo;
  const __nv_bfloat16* w_in;
  const __nv_bfloat16* wq;
  const __nv_bfloat16* wk;
  const __nv_bfloat16* wv;
  uint32_t mlo, mhi;
  __nv_bfloat16* out;
};

__device__ __forceinline__ uint32_t store_o_tile(const float (&o)[12], int bi, int bj, int tau, int tid, uint32_t sb) {
  const int half = tau & 1, hh = tau >> 1, w = tid >> 5, l = tid & 31;
  const int r0 = half * 64 + w * 16 + (l >> 2);
  const float f0 = __fdividef(ldsf(sb + SM_G + r0 * 4), o[8]), f1 = __fdividef(ldsf(sb + SM_G + (r0 + 8) * 4), o[10]);
  uint32_t* dst = reinterpret_cast<uint32_t*>(g_o) + (bi * 8 + bj) * 4096 + (half * 8 + w * 2) * 256 + hh * 64;
  dst[l] = pack_bf16(o[0] * f0, o[1] * f0);
  dst[l + 32] = pack_bf16(o[4] * f0, o[5] * f0);
  dst[l + 256] = pack_bf16(o[2] * f1, o[3] * f1);
  dst[l + 288] = pack_bf16(o[6] * f1, o[7] * f1);
  return ld_back(dst + ((l >> 3) & 1) * 256 + (l & 7) * 8);
}

__global__ void __cluster_dims__(2, 1, 1) __launch_bounds__(NTHREADS, 1)
fused_kernel(const __grid_constant__ CUtensorMap tm_x, const __grid_constant__ CUtensorMap tm_wq,
             const __grid_constant__ CUtensorMap tm_win, const __grid_constant__ CUtensorMap tm_wsp,
             const __grid_constant__ CUtensorMap tm_wout, const __grid_constant__ CUtensorMap tm_wo, const Params prm) {
  extern __shared__ __align__(1024) uint8_t smem_raw[];
  const uint32_t sb = __shfl_sync(0xffffffffu, (uint32_t)__cvta_generic_to_shared(smem_raw), 0);
  const int warp = __shfl_sync(0xffffffffu, (int)(threadIdx.x >> 5), 0);
  const int wg = warp >> 2;
  const int tid = threadIdx.x & 127;
  const int lane = threadIdx.x & 31;
  const int rank = blockIdx.x & 1;
  const int ai = (blockIdx.x >> 4) * 2 + rank, aj = (blockIdx.x >> 1) & 7;
  const int bi = blockIdx.x >> 3, bj = blockIdx.x & 7;
  auto BAR = [&](int k) { return sb + SM_BAR + 8u * k; };

  if (warp == 16) {
    if (lane == 0) {
      mbar_init(BAR(B_XFULL), 1); mbar_init(BAR(B_XFULL + 1), 1);
      asm volatile("fence.mbarrier_init.release.cluster;" ::: "memory");
    }
    __syncwarp();
    e_expect(BAR(B_XFULL), 16384);
    tma2d(sb + SM_K, &tm_x, 0, ai * 128, BAR(B_XFULL));
    e_expect(BAR(B_XFULL + 1), 16384);
    tma2d(sb + SM_K + 16384, &tm_x, 64, ai * 128, BAR(B_XFULL + 1));
    if (lane == 0) TS(36);
  } else if (warp == 18) {
    if (lane == 0) { mbar_init(BAR(B_WFULL), 1); asm volatile("fence.mbarrier_init.release.cluster;" ::: "memory"); }
    __syncwarp();
    e_expect(BAR(B_WFULL), 16384);
#pragma unroll
    for (int h = 0; h < 2; h++) {
      tma3d(sb + SM_RING + h * 8192, &tm_win, 0, h * 32, aj < 6 ? 21 + 3 * aj : 27 + 2 * aj, BAR(B_WFULL));
      tma2d(sb + SM_RING + h * 8192 + 6144, &tm_wq, 64 * aj, h * 32, BAR(B_WFULL));
    }
  } else if (warp == 19) {
    l2_prefetch(reinterpret_cast<const uint8_t*>(prm.w_in) + blockIdx.x * 11008, 11008);
    l2_prefetch(reinterpret_cast<const uint8_t*>(prm.wq) + blockIdx.x * 4096, 4096);
  } else if (warp < 16 && lane == 0) {
#pragma unroll
    for (int r = 0; r < 4; r++) {
      const int k = warp + 16 * r;
      uint32_t cnt = 1;
      if (k >= B_XEMPTY && k < B_XEMPTY + 8) cnt = 4;
      if (k >= B_WEMPTY && k < B_WEMPTY + 12) cnt = 4;
      if (k >= B_REMPTY && k < B_REMPTY + 3) cnt = 2;
      if (k == B_ATT) cnt = 6;
      if (k == B_QRDY) cnt = 16;
      if (k == B_KSTAT) cnt = 17;
      if (k == B_LNOK) cnt = 8;
      if (k >= 2 && k != B_WFULL) mbar_init(BAR(k), cnt);
    }
    asm volatile("fence.mbarrier_init.release.cluster;" ::: "memory");
  }
  __syncthreads();
  if (threadIdx.x == 0) TS(35);
  asm volatile("barrier.cluster.arrive.relaxed.aligned;" ::: "memory");
  asm volatile("barrier.cluster.wait.acquire.aligned;" ::: "memory");

  if (wg == 4) {
    asm volatile("setmaxnreg.dec.sync.aligned.u32 24;");
    if (warp == 18) {
#pragma unroll 1
      for (int f = 1; f < 16; f++) {
        if (f == 1 && lane == 0) TS(0);
        if (f == 5 && lane == 0) TS(37);
        if (f >= 5) mbar_wait(BAR(B_WEMPTY + f - 5), 0);
        const uint32_t dst = sb + wslot(f) + rank * 8192, bar = BAR(B_WFULL + f);
        const int k0 = (f & 7) * 64 + rank * 32;
        e_expect(bar, 16384);
        tma3d_mc(dst, &tm_win, 0, k0, f < 8 ? (aj < 6 ? 21 + 3 * aj : 27 + 2 * aj) : (aj < 2 ? 2 * aj : 3 * aj - 2), bar);
        tma2d_mc(dst + 6144, &tm_wq, 64 * aj + (f >> 3) * 32, k0, bar);
        if (f < 7) {
          e_expect(BAR(B_XFULL + 1 + f), 16384);
          tma2d(sb + SM_K + (f + 1) * 16384, &tm_x, (f + 1) * 64, ai * 128, BAR(B_XFULL + 1 + f));
        }
      }
      if (lane == 0) TS(1);
    } else if (warp == 19) {
      mbar_wait(BAR(B_XEMPTY + 6), 0);
      const unsigned ep1 = lds32(sb + SM_MISC + 4 * M_EPOCH) + 1;
      wait_ge(&g_zcnt[lane * 32], ep1 * 8);
      __syncwarp();
      e_arrive(BAR(B_ZOK));
      wait_ge(&g_z1cnt[bi * 32], ep1 * 16);
      e_arrive(BAR(B_Z1OK));
    } else if (warp == 16) {
      tm_prefetch(&tm_wsp);
      tm_prefetch(&tm_wout);
      tm_prefetch(&tm_wo);
      const int row = bi * 128 + rank * 64;
      mbar_wait(BAR(B_XEMPTY), 0);
      tma2d_pf(&tm_wsp, (bj >> 1) * 64, row);
      tma2d_pf(&tm_wsp, (bj >> 1) * 64 + 256, row);
      mbar_wait(BAR(B_XEMPTY + 7), 0);
      mbar_wait(BAR(B_ZOK), 0);
      const unsigned ep1 = lds32(sb + SM_MISC + 4 * M_EPOCH) + 1;
      fence_async();
      if (lane == 0) TS(2);
      int st = 0, ph = 1;
#pragma unroll 1
      for (int n = 0; n < 46; n++) {
        const uint32_t stg = sb + SM_RING + st * RSTAGE, bar = BAR(B_RFULL + st);
        if (n >= 3) mbar_wait(BAR(B_REMPTY + st), ph);
        if (n < 32) {
          e_expect(bar, 16384 + 11264);
          tma2d_mc(stg + rank * 8192, &tm_wsp, n * 64, row, bar);
          bulk(stg + 16384, reinterpret_cast<const uint8_t*>(g_z2n) + (bj * 32 + n) * 11264, 11264, bar);
          if ((n & 3) == (bj >> 1) && n < 24) tma2d_pf(&tm_wsp, (n + 8) * 64, row);
          if (n == 16) {
            l2_prefetch(reinterpret_cast<const uint8_t*>(prm.w_out) + blockIdx.x * 5504, 5504);
            l2_prefetch(reinterpret_cast<const uint8_t*>(prm.wo) + blockIdx.x * 4096, 4096);
          }
        } else if (n < 43) {
          const int c = n - 32;
          e_expect(bar, 16384 + 8192);
          tma2d(stg + 16384, &tm_wout, 64 * bj, c * 64, bar);
          if (c == 0) { wait_ge(&g_ucnt[bi * 32], ep1 * 8); fence_async(); if (lane == 0) TS(3); }
          bulk_mc(stg + rank * 8192, reinterpret_cast<const uint8_t*>(g_u) + (bi * 11 + c) * 16384 + rank * 8192, 8192, bar);
        }
        if (++st == 3) { st = 0; ph ^= 1; }
      }
      e_expect(BAR(B_WOFULL), 65536);
#pragma unroll 1
      for (int c = 0; c < 8; c++) tma2d(sb + SM_RING + c * 8192, &tm_wo, 64 * bj, c * 64, BAR(B_WOFULL));
      if (lane == 0) TS(4);
#pragma unroll 1
      for (int c = 0; c < 8; c++) e_expect(BAR(B_XFULL + c), 16384);
      mbar_wait(BAR(B_ATT), 0);
#pragma unroll 1
      for (int n = 0; n < SPIN_LIMIT; n++) if ((int)(ld_acquire(&g_ocnt[bi * 32]) - ep1 * 24) >= 0) break;
      fence_async();
      if (lane == 0) TS(5);
#pragma unroll 1
      for (int c = 0; c < 8; c++)
        bulk_mc(sb + SM_K + c * 16384 + rank * 8192, reinterpret_cast<const uint8_t*>(g_o) + (bi * 8 + c) * 16384 + rank * 8192, 8192, BAR(B_XFULL + c));
    } else {
      if (lane == 0) {
        sts32(sb + SM_MISC + 4 * M_EPOCH, atomicAdd(&g_ticket, 1u) / NCTA);
        mbar_arrive(BAR(B_EPOCH));
        TS(71);
      }
      __syncwarp();
      const unsigned ep1 = lds32(sb + SM_MISC + 4 * M_EPOCH) + 1;
      e_expect(BAR(B_KVFULL), 49152);
      e_expect(BAR(B_KVB), 49152);
      e_expect(BAR(B_KVC), 32768);
      mbar_wait(BAR(B_WFULL + 8), 0);
      uint32_t kn = 0, vb = 0;
#pragma unroll 1
      for (int n = 0; n < SPIN_LIMIT; n++) {
        unsigned long long a, b, c, d;
        asm volatile("ld.relaxed.gpu.global.v2.b64 {%0, %1}, [%2];" : "=l"(a), "=l"(b) : "l"(&g_kvflag[2 * lane]) : "memory");
        asm volatile("ld.relaxed.gpu.global.v2.b64 {%0, %1}, [%2];" : "=l"(c), "=l"(d) : "l"(&g_kvflag[64 + 2 * lane]) : "memory");
        kn = max((uint32_t)a, (uint32_t)c); vb = (uint32_t)b | (uint32_t)d;
        if (__all_sync(0xffffffffu, (uint32_t)(a >> 32) == ep1 && (uint32_t)(b >> 32) == ep1 && (uint32_t)(c >> 32) == ep1 && (uint32_t)(d >> 32) == ep1)) break;
        __nanosleep(100);
      }
      asm volatile("fence.acquire.gpu;" ::: "memory");
      kn = __reduce_max_sync(0xffffffffu, kn);
      vb = __reduce_or_sync(0xffffffffu, vb);
      if (lane == 0) {
        TS(6);
        sts32(sb + SM_MISC + 4 * M_KN2, kn);
        sts32(sb + SM_MISC + 4 * M_VOK, vb == 0xFFFFu ? 1u : 0u);
        mbar_arrive(BAR(B_KSTAT));
      }
      __syncwarp();
      fence_async();
      mbar_wait(BAR(B_LNOK), 0);
#pragma unroll 1
      for (int c = 0; c < 8; c++) {
        const uint32_t off = c * 16384 + rank * 8192;
        mbar_wait(BAR(B_XEMPTY + c), 0);
        bulk_mc(sb + SM_K + off, reinterpret_cast<const uint8_t*>(g_kimg) + off, 8192, BAR(c < 3 ? B_KVFULL : (c < 6 ? B_KVB : B_KVC)));
      }
      if (lane == 0) TS(7);
      mbar_wait(BAR(B_DEC), 0);
      if (!lds32(sb + SM_MISC + 4 * M_FAST)) {
        mbar_wait(BAR(B_KVFULL), 0); mbar_wait(BAR(B_KVB), 0); mbar_wait(BAR(B_KVC), 0);
        e_expect(BAR(B_KFB), 65536);
#pragma unroll 1
        for (int j = 0; j < 32; j++) bulk(sb + SM_K + j * 4096, g_kbf + j * 128, 2048, BAR(B_KFB));
      }
    }
  } else {
    asm volatile("setmaxnreg.inc.sync.aligned.u32 112;");
    const int w = tid >> 5, g = lane >> 2, t4 = lane & 3, half = wg & 1;
    uint32_t pend;
    {
      float acc[64];
      if (wg == 2) {
        const int slot = ai * 4 + (aj >> 1), isv = aj & 1;
        const uint4* wsrc = reinterpret_cast<const uint4*>(isv ? prm.wv : prm.wk) + tid;
        uint4 wr[8];
#pragma unroll
        for (int r = 0; r < 8; r++) wr[r] = __ldg(wsrc + 128 * r);
#pragma unroll
        for (int r = 0; r < 8; r++) sts128(sb + SM_WKV + r * 2048 + (tid >> 1) * 32 + (((tid ^ (tid >> 3)) & 1) << 4), wr[r].x, wr[r].y, wr[r].z, wr[r].w);
        fence_async_smem();
        bar_sync(3, 128);
        float kv[16];
#pragma unroll
        for (int k = 0; k < 16; k++) kv[k] = 0.f;
        regfence(kv);
#pragma unroll 1
        for (int c = 0; c < 8; c++) {
          mbar_wait(BAR(B_XFULL + c), 0);
          const uint64_t da = mkdesc(sb + SM_WKV + c * 2048, 0, 256, 3);
          const uint64_t db = mkdesc(sb + SM_K + c * 16384 + (aj >> 1) * 4096, 16, 1024, 1);
          wg_fence();
#pragma unroll
          for (int k = 0; k < 4; k++) wg_ss_n32t<0, 16>(kv, da + 32 * k, db + 2 * k);
          wg_commit();
        }
        wg_wait<0>();
        regfence(kv);
        if (tid == 0) TS(22);
        const uint32_t sT = sb + SM_WKV, sH = sb + SM_WKV + 4096;
        bar_sync(3, 128);
        {
          const float a = w & 1 ? kv[4] : kv[0], b = w & 1 ? kv[5] : kv[1], c = w & 1 ? kv[6] : kv[2], d = w & 1 ? kv[7] : kv[3];
          const float e = w & 1 ? kv[12] : kv[8], f = w & 1 ? kv[13] : kv[9], h = w & 1 ? kv[14] : kv[10], i = w & 1 ? kv[15] : kv[11];
          const uint32_t lo = pack_bf16(w & 2 ? e : a, w & 2 ? f : b), hi = pack_bf16(w & 2 ? h : c, w & 2 ? i : d);
          const uint32_t p = sT + ((w * 8 + 2 * t4) * 17 + g) * 4;
          sts32(p, lo << 16); sts32(p + 68, lo & 0xFFFF0000u); sts32(p + 32, hi << 16); sts32(p + 100, hi & 0xFFFF0000u);
        }
        bar_sync(3, 128);
        if (tid == 0) TS(64);
        const int tok = (tid & 63) >> 1, hf = tid & 1;
        float f[8];
#pragma unroll
        for (int e = 0; e < 8; e++) f[e] = ldsf(sT + (tok * 17 + hf * 8 + e) * 4);
        uint4 val = make_uint4(pack_bf16(f[0], f[1]), pack_bf16(f[2], f[3]), pack_bf16(f[4], f[5]), pack_bf16(f[6], f[7]));
        uint32_t stat = 0;
        if (isv) {
#pragma unroll
          for (int e = 0; e < 8; e++) {
            if (fabsf(f[e]) >= 9.5367431640625e-07f) stat |= 1u << e;
            if (!(fabsf(f[e]) <= 1073741824.f)) stat |= 1u << (16 - 8 * hf);
          }
          stat = __reduce_or_sync(0xffffffffu, stat << (8 * hf));
        } else {
          float n2 = 0.f;
#pragma unroll
          for (int e = 0; e < 8; e++) n2 = fmaf(f[e], f[e], n2);
          n2 += __shfl_xor_sync(0xffffffffu, n2, 1);
          if (!(n2 <= 3.0e38f)) n2 = 3.0e38f;
          stat = __reduce_max_sync(0xffffffffu, __float_as_uint(n2));
          if (tid < 48) {
            const int d = tid & 15, sg = tid >> 4, j0 = sg == 0 ? 0 : (sg == 1 ? 10 : 22), j1 = sg == 0 ? 10 : (sg == 1 ? 22 : 32);
            const float sc = slot < NP ? 16.f : 0.125f, fb = slot < NP ? 1.f : 0.f;
            float kx[12], run = 0.f;
#pragma unroll
            for (int e = 0; e < 12; e++) kx[e] = ldsf(sT + (min(j0 + e, 31) * 17 + d) * 4);
#pragma unroll
            for (int e = 0; e < 12; e++) {
              const __half hv = __float2half_rn(fmaf(kx[e], sc, -run));
              run = fmaf(__half2float(hv), fb, run);
              if (j0 + e < j1) sts16(sH + ((j0 + e) * 16 + d) * 2, __half_as_ushort(hv));
            }
          }
        }
        if (lane == 0) sts32(sb + SM_MISC + 4 * (M_KVR + w), stat);
        bar_sync(3, 128);
        const uint32_t off = slot * 2 + (hf ^ ((slot >> 2) & 1));
        uint4* dst = tid < 64 ? g_kimg + tok * 256 + isv * 128 + off : g_kbf + tok * 128 + off;
        if (!isv && tid < 64) val = lds128(sH + tok * 32 + hf * 16);
        uint32_t chk = 0;
        if (tid < 64 || !isv) { *dst = val; chk = ld_back(dst); }
        mbar_wait(BAR(B_EPOCH), 0);
        consume(chk, sb);
        fence_async();
        bar_sync(3, 128);
        if (tid == 0) {
          const uint32_t s0 = lds32(sb + SM_MISC + 4 * M_KVR), s1 = lds32(sb + SM_MISC + 4 * (M_KVR + 1));
          const unsigned long long fl = ((unsigned long long)(lds32(sb + SM_MISC + 4 * M_EPOCH) + 1) << 32) | (isv ? (s0 | s1) : max(s0, s1));
          asm volatile("st.relaxed.gpu.global.b64 [%0], %1;" ::"l"(&g_kvflag[ai * 8 + aj]), "l"(fl) : "memory");
          TS(23);
        }
      } else if (wg == 3) {
        uint4* sW = reinterpret_cast<uint4*>(smem_raw + SM_GW);
        if (tid < 64) sW[tid] = __ldg(reinterpret_cast<const uint4*>(prm.gate_w) + tid);
        sts32(sb + SM_ONES + tid * 4, 0x3F803F80u);
        bar_sync(4, 128);
        const int v = tid & 7, rr = tid >> 3;
        float a[8];
#pragma unroll
        for (int p = 0; p < 8; p++) a[p] = 0.f;
#pragma unroll 1
        for (int c = 0; c < 8; c++) {
          const uint4 gv = sW[c * 8 + v];
          mbar_wait(BAR(B_XFULL + c), 0);
          if (tid == 0) TS(40 + c);
          const uint4* xr = reinterpret_cast<const uint4*>(smem_raw + SM_K + c * 16384 + rr * 128) + (v ^ (rr & 7));
#pragma unroll
          for (int p = 0; p < 8; p++) {
            const uint4 xv = xr[p * 128];
            float s = fmaf(bf_lo(xv.x), bf_lo(gv.x), a[p]), t = bf_hi(xv.x) * bf_hi(gv.x);
            s = fmaf(bf_lo(xv.y), bf_lo(gv.y), s); t = fmaf(bf_hi(xv.y), bf_hi(gv.y), t);
            s = fmaf(bf_lo(xv.z), bf_lo(gv.z), s); t = fmaf(bf_hi(xv.z), bf_hi(gv.z), t);
            s = fmaf(bf_lo(xv.w), bf_lo(gv.w), s); t = fmaf(bf_hi(xv.w), bf_hi(gv.w), t);
            a[p] = s + t;
          }
        }
        float mine = 0.f;
#pragma unroll
        for (int p = 0; p < 8; p++) {
          float s = a[p];
          s += __shfl_xor_sync(0xffffffffu, s, 1); s += __shfl_xor_sync(0xffffffffu, s, 2); s += __shfl_xor_sync(0xffffffffu, s, 4);
          if (v == p) mine = s;
        }
        const float gt = __fdividef(1.f, 1.f + __expf(-mine));
        sts32(sb + SM_G + (rr + 16 * v) * 4, __float_as_uint(gt));
        fence_async_smem();
        bar_sync(4, 128);
        if (aj == 0) g_gate[ai * 128 + tid] = ldsf(sb + SM_G + tid * 4);
        if (tid == 0) TS(8);
      }
#pragma unroll
      for (int k = 0; k < 64; k++) acc[k] = 0.f;
      regfence(acc);
      const int pass = wg >> 1;
#pragma unroll 1
      for (int c = 0; c < 8; c++) {
        mbar_wait(BAR(B_XFULL + c), 0);
        mbar_wait(BAR(B_WFULL + pass * 8 + c), 0);
        if (tid == 0 && half == pass) TS(48 + pass * 8 + c);
        const uint64_t da = mkdesc(sb + SM_K + c * 16384 + half * 8192, 16, 1024, 1);
        const uint64_t db = mkdesc(sb + wslot(pass * 8 + c), 2048, 512, 2);
        wg_fence();
#pragma unroll
        for (int k = 0; k < 4; k++) wg_ss_n128<0, 64>(acc, da + 2 * k, db + (k & 1) * 64 + (k >> 1) * 512);
        wg_commit();
        wg_wait<1>();
        if (tid == 0 && c > 0) {
          if (pass * 8 + c < 12) mbar_arrive_both(BAR(B_WEMPTY + pass * 8 + c - 1));
          if (pass) mbar_arrive_both(BAR(B_XEMPTY + c - 1));
        }
      }
      wg_wait<0>();
      if (tid == 0) mbar_arrive_both(BAR(pass ? B_XEMPTY + 7 : B_WEMPTY + 7));
      regfence(acc);
      if (tid == 0) TS(wg == 0 ? 16 : (wg == 2 ? 24 : (wg == 3 ? 9 : 95)));
      uint32_t qb[8];
      {
        float n2 = 0.f;
#pragma unroll
        for (int k = 0; k < 8; k++) qb[k] = pack_bf16(acc[48 + 2 * k], acc[49 + 2 * k]);
#pragma unroll
        for (int k = 0; k < 4; k++) {
          const uint32_t a = qb[4 * (k >> 1) + (k & 1)], b = qb[4 * (k >> 1) + (k & 1) + 2];
          float s = bf_lo(a) * bf_lo(a);
          s = fmaf(bf_hi(a), bf_hi(a), s); s = fmaf(bf_lo(b), bf_lo(b), s); s = fmaf(bf_hi(b), bf_hi(b), s);
          s += __shfl_xor_sync(0xffffffffu, s, 1); s += __shfl_xor_sync(0xffffffffu, s, 2);
          if (!(s <= 3.0e38f)) s = 3.0e38f;
          n2 = fmaxf(n2, s);
        }
        const uint32_t nmax = __reduce_max_sync(0xffffffffu, __float_as_uint(n2));
        if (lane == 0) { sts32(sb + SM_MISC + 4 * (M_RED + warp), nmax); mbar_arrive(BAR(B_KSTAT)); }
      }
      auto finish_q = [&]() {
        mbar_wait(BAR(B_KSTAT), 0);
        const float qn2 = __uint_as_float(__reduce_max_sync(0xffffffffu, lds32(sb + SM_MISC + 4 * (M_RED + (lane & 15)))));
        const float kn2 = ldsf(sb + SM_MISC + 4 * M_KN2);
        constexpr float SC = QSCALE * 0.125f;
        const bool fast = lds32(sb + SM_MISC + 4 * M_VOK) && qn2 <= 4.0e8f && kn2 <= 4.0e6f && qn2 * kn2 * (SC * SC) <= BOUND * BOUND;
        if (fast) {
#pragma unroll
          for (int k = 0; k < 8; k++) qb[k] = pack_f16(bf_lo(qb[k]) * QSCALE, bf_hi(qb[k]) * QSCALE);
        }
        sts128(sb + SM_Q + wg * 2048 + pass * 4096 + tid * 16, qb[0], qb[1], qb[2], qb[3]);
        sts128(sb + SM_Q + wg * 2048 + pass * 4096 + 4096 + tid * 16, qb[4], qb[5], qb[6], qb[7]);
        if (threadIdx.x == 256) { sts32(sb + SM_MISC + 4 * M_FAST, fast ? 1u : 0u); mbar_arrive(BAR(B_DEC)); }
        __syncwarp();
        if (lane == 0) mbar_arrive(BAR(B_QRDY));
        if (tid == 0 && pass) TS(75 + wg);
      };
      if (pass) finish_q();
#pragma unroll
      for (int k = 0; k < 48; k++) acc[k] = gelu2_tanh(acc[k]);
      int fb0, c_lo = 0, c_hi = 12;
      if (wg < 2) { fb0 = aj < 6 ? 12 * aj - 2 : 22 + 8 * aj; if (aj == 0) c_lo = 2; if (aj >= 6) c_hi = 8; }
      else { fb0 = aj < 2 ? 8 * aj : 12 * aj - 8; if (aj < 2) c_hi = 8; if (aj == 7) c_hi = 10; }
      if (wg < 2) {
        float s1[2][3], s2[2][3];
#pragma unroll
        for (int k = 0; k < 48; k++) {
          const int r = (k >> 1) & 1, gq = k < 8 ? 0 : (k < 32 ? 1 : 2);
          if (k - 2 * r == (gq == 0 ? 0 : (gq == 1 ? 8 : 32))) { s1[r][gq] = acc[k]; s2[r][gq] = acc[k] * acc[k]; }
          else { s1[r][gq] += acc[k]; s2[r][gq] = fmaf(acc[k], acc[k], s2[r][gq]); }
        }
        const float inv_n = __fdividef(0.125f, (float)(c_hi - c_lo));
        float mm[2], vv[2];
#pragma unroll
        for (int r = 0; r < 2; r++) {
          float a = s1[r][1], b = s2[r][1];
          if (c_lo == 0) { a += s1[r][0]; b += s2[r][0]; }
          if (c_hi == 12) { a += s1[r][2]; b += s2[r][2]; }
          a += __shfl_xor_sync(0xffffffffu, a, 1); b += __shfl_xor_sync(0xffffffffu, b, 1);
          a += __shfl_xor_sync(0xffffffffu, a, 2); b += __shfl_xor_sync(0xffffffffu, b, 2);
          mm[r] = a * inv_n;
          vv[r] = fmaxf(fmaf(-a, mm[r], b), 0.f);
        }
        const int r0 = half * 64 + w * 16 + g;
        mbar_wait(BAR(B_EPOCH), 0);
        const unsigned ep1 = lds32(sb + SM_MISC + 4 * M_EPOCH) + 1;
        if (threadIdx.x == 0) TS(67);
        if (t4 < 2) {
          const float m = t4 ? mm[1] : mm[0], v = t4 ? vv[1] : vv[0];
          asm volatile("st.relaxed.gpu.global.v2.b64 [%0], {%1, %2};" ::"l"(&g_lnstat[(ai * 8 + aj) * 128 + r0 + 8 * t4]),
                       "l"(((unsigned long long)ep1 << 32) | __float_as_uint(m)), "l"(((unsigned long long)ep1 << 32) | __float_as_uint(v)) : "memory");
        }
        float sm[4], sv[4];
        const uint4* lp = &g_lnstat[(ai * 8 + 2 * t4) * 128 + r0];
#pragma unroll 1
        for (int n = 0; n < SPIN_LIMIT; n++) {
          uint32_t tg = ep1;
          if (lane < 8) tg = ld_back(reinterpret_cast<const uint32_t*>(&g_lnstat[(ai * 8 + lane) * 128 + half * 64 + w * 16 + 15]) + 3);
          if (__all_sync(0xffffffffu, tg == ep1)) break;
        }
#pragma unroll 1
        for (int n = 0; n < SPIN_LIMIT; n++) {
          bool ok = true;
#pragma unroll
          for (int e = 0; e < 4; e++) {
            unsigned long long a, b;
            asm volatile("ld.relaxed.gpu.global.v2.b64 {%0, %1}, [%2];" : "=l"(a), "=l"(b) : "l"(lp + (e >> 1) * 128 + (e & 1) * 8) : "memory");
            ok = ok && (uint32_t)(a >> 32) == ep1 && (uint32_t)(b >> 32) == ep1;
            sm[e] = __uint_as_float((uint32_t)a); sv[e] = __uint_as_float((uint32_t)b);
          }
          if (__all_sync(0xffffffffu, ok)) break;
        }
        if (lane == 0) mbar_arrive(BAR(B_LNOK));
        if (threadIdx.x == 0) TS(68);
        const float na = t4 == 0 ? 80.f : (t4 == 3 ? 64.f : 96.f), nb = t4 == 3 ? 64.f : 96.f;
#pragma unroll
        for (int r = 0; r < 2; r++) {
          float t = fmaf(sm[r], na, sm[2 + r] * nb);
          t += __shfl_xor_sync(0xffffffffu, t, 1); t += __shfl_xor_sync(0xffffffffu, t, 2);
          const float mu = t * (1.f / 688.f);
          const float da = sm[r] - mu, db = sm[2 + r] - mu;
          float m2 = sv[r] + sv[2 + r] + na * da * da + nb * db * db;
          m2 += __shfl_xor_sync(0xffffffffu, m2, 1); m2 += __shfl_xor_sync(0xffffffffu, m2, 2);
          const float rs = rsqrtf(fmaf(m2, 1.f / 688.f, 4e-5f)), sh = -mu * rs;
#pragma unroll
          for (int k = 2 * r; k < 48; k += 4) { acc[k] = fmaf(acc[k], rs, sh); acc[k + 1] = fmaf(acc[k + 1], rs, sh); }
        }
        if (aj == 7) {
          c_hi = 10;
#pragma unroll
          for (int k = 32; k < 40; k++) acc[k] = 0.f;
        }
      }
      uint32_t* zp = wg < 2 ? reinterpret_cast<uint32_t*>(g_z2n) + (ai * 2 + half) * 2816 + w * 704
                            : reinterpret_cast<uint32_t*>(g_z1) + (ai * 88 * 16 + half * 8 + w * 2) * 32;
      const int mul = wg < 2 ? 373 : 0, cstr = wg < 2 ? 32 : 512, rstr = wg < 2 ? 352 : 32;
      auto zoff = [&](int c8) { const int fb = fb0 + c8; return ((fb * mul) >> 12) * (32 * 2816 - 352) + fb * cstr; };
#pragma unroll
      for (int c8 = 0; c8 < 12; c8++) {
        uint32_t* p = zp + zoff(c8) + lane;
        if (c8 >= c_lo && c8 < c_hi) { p[0] = pack_bf16(acc[4 * c8], acc[4 * c8 + 1]); p[rstr] = pack_bf16(acc[4 * c8 + 2], acc[4 * c8 + 3]); }
      }
      if (tid == 0) TS(wg == 0 ? 69 : 78 + wg);
      uint32_t chk = 0;
#pragma unroll
      for (int r = 0; r < 3; r++) {
        const int it = lane + 32 * r, c8 = it >> 3;
        if (c8 >= c_lo && c8 < c_hi) chk ^= ld_back(zp + zoff(c8) + ((it >> 2) & 1) * rstr + (it & 3) * 8);
      }
      if (wg == 3 && aj == 0) chk ^= ld_back(&g_gate[ai * 128 + tid]);
      if (wg != 2) {
        consume(chk, sb);
        fence_async();
        bar_sync(1 + wg, 128);
        if (tid == 0) { red_relaxed(wg < 2 ? &g_zcnt[(ai * 2 + half) * 32] : &g_z1cnt[ai * 32]); TS(wg < 2 ? 20 + wg : 17); }
      }
      pend = chk;
      if (!pass) finish_q();
    }
    if (wg == 3) {
      asm volatile("setmaxnreg.inc.sync.aligned.u32 120;");
      int st = 0, ph = 0;
      {
        float acc[88];
#pragma unroll
        for (int k = 0; k < 88; k++) acc[k] = 0.f;
        regfence(acc);
#pragma unroll 1
        for (int n = 0; n < 32; n++) {
          mbar_wait(BAR(B_RFULL + st), ph);
          const uint64_t da = mkdesc(sb + SM_RING + st * RSTAGE, 16, 1024, 1);
          const uint64_t db = mkdesc(sb + SM_RING + st * RSTAGE + 16384, 1408, 128, 0);
#pragma unroll
          for (int k = 0; k < 4; k++) {
            wg_fence();
            wg_ss_n88<0, 88>(acc, da + 2 * k, db + 176 * k);
            wg_ss_n88<44, 88>(acc, da + 512 + 2 * k, db + 176 * k);
            wg_commit();
            wg_wait<0>();
          }
          if (tid == 0) mbar_arrive_both(BAR(B_REMPTY + st));
          if (++st == 3) { st = 0; ph ^= 1; }
        }
        regfence(acc);
        if (tid == 0) TS(11);
        mbar_wait(BAR(B_Z1OK), 0);
        const uint32_t* z1p = reinterpret_cast<const uint32_t*>(g_z1) + ((bi * 88 + bj * 11) * 16 + w * 2) * 32 + lane;
        uint32_t* up = reinterpret_cast<uint32_t*>(g_u) + bi * 11 * 4096 + w * 512 + lane;
#pragma unroll
        for (int r = 0; r < 4; r++) {
          const int row = bi * 128 + (r >> 1) * 64 + w * 16 + (r & 1) * 8 + g;
          const float og = fmaf(__ldcg(&g_gate[row]), -0.5f, 0.5f), bs = __bfloat162float(prm.b_sp[row]) * og;
          uint32_t zz[11];
#pragma unroll
          for (int c8 = 0; c8 < 11; c8++) zz[c8] = __ldcg(z1p + c8 * 512 + ((r >> 1) * 8 + (r & 1)) * 32);
          if (bj == 7) zz[9] = zz[10] = 0;
#pragma unroll
          for (int c8 = 0; c8 < 11; c8++) {
            const int k = (r >> 1) * 44 + c8 * 4 + (r & 1) * 2, cb = 11 * bj + c8;
            uint32_t v = pack_bf16(fmaf(acc[k], og, bs), fmaf(acc[k + 1], og, bs));
            asm("mul.rn.bf16x2 %0, %0, %1;" : "+r"(v) : "r"(zz[c8]));
            up[cb * 32 + (cb >> 3) * 3840 + ((r >> 1) * 8 + (r & 1)) * 256] = v;
          }
        }
        fence_async();
        bar_sync(4, 128);
        if (tid == 0) { red_release(&g_ucnt[bi * 32]); TS(12); }
      }
      float oc[64];
#pragma unroll
      for (int k = 0; k < 64; k++) oc[k] = 0.f;
      regfence(oc);
#pragma unroll 1
      for (int n = 0; n < 19; n++) {
        uint32_t sa, sw;
        if (n < 11) { mbar_wait(BAR(B_RFULL + st), ph); sa = SM_RING + st * RSTAGE; sw = sa + 16384; }
        else {
          if (n == 11) { if (tid == 0) TS(13); mbar_wait(BAR(B_WOFULL), 0); }
          mbar_wait(BAR(B_XFULL + n - 11), 1); sa = SM_K + (n - 11) * 16384; sw = SM_RING + (n - 11) * 8192;
        }
        const uint64_t da = mkdesc(sb + sa, 128, 1024, 0), db = mkdesc(sb + sw, 8192, 1024, 1);
#pragma unroll
        for (int k = 0; k < 4; k += 2) {
          wg_fence();
          wg_ss_n64<0, 64>(oc, da + 16 * k, db + 128 * k);
          wg_ss_n64<32, 64>(oc, da + 512 + 16 * k, db + 128 * k);
          wg_ss_n64<0, 64>(oc, da + 16 * k + 16, db + 128 * k + 128);
          wg_ss_n64<32, 64>(oc, da + 528 + 16 * k, db + 128 * k + 128);
          wg_commit();
          if (n < 11) wg_wait<0>();
        }
        if (n < 11) {
          if (tid == 0) mbar_arrive_both(BAR(B_REMPTY + st));
          if (++st == 3) { st = 0; ph ^= 1; }
        }
      }
      wg_wait<0>();
      regfence(oc);
      if (tid == 0) TS(14);
      uint32_t* op = reinterpret_cast<uint32_t*>(prm.out) + (bi * 128 + w * 16 + g) * 256 + bj * 32 + t4;
#pragma unroll
      for (int k = 0; k < 64; k += 2) {
        const int hf = k / 32, c8 = (k % 32) / 4, r8 = (k >> 1) & 1;
        op[(hf * 64 + r8 * 8) * 256 + c8 * 4] = pack_bf16(oc[k], oc[k + 1]);
      }
      if (tid == 0) TS(15);
    } else {
      mbar_wait(BAR(B_QRDY), 0);
    if (tid == 0) TS(25 + wg);
    if (tid == 0) TS(28 + wg);
    if (threadIdx.x == 0) GTS(125);
    const uint64_t dk0 = mkdesc(sb + SM_K, 16, 256, 3);
    const uint64_t dv0 = mkdesc(sb + SM_K + 2048, SM_ONES - 2048, 256, 3);
    const int aw = wg == 0 ? 0 : 3 - wg;
    uint32_t chk = 0;
    auto publish_z1 = [&]() { consume(pend, sb); bar_sync(3, 128); if (tid == 0) red_relaxed(&g_z1cnt[ai * 32]); };
    float o[12], s[32];
    uint32_t q[4], p0[16], p1[16];
    if (lds32(sb + SM_MISC + 4 * M_FAST)) {
      const uint32_t mlo = prm.mlo, mhi = prm.mhi;
      uint64_t dk = dk0, dv = dv0;
#define STEP(PIN, POUT) { wg_fence(); issue_qk(s, q, dk); dk += KSTEP; wg_commit(); issue_pv(o, PIN, dv); dv += VSTEP8; wg_commit(); \
                          wg_wait<1>(); regfence(s); softmax_step(s, POUT, mlo, mhi); wg_wait<0>(); }
#pragma unroll 1
      for (int sg = aw * 8; sg < aw * 8 + 8; sg++) {
        const int tau = sg / 3, seg = sg - tau * 3;
        int n2 = seg == 1 ? 6 : 5;
        mbar_wait(BAR(seg ? B_KVB : B_KVFULL), 0);
        mbar_wait(BAR(seg == 2 ? B_KVC : B_KVFULL), 0);
#pragma unroll
        for (int k = 0; k < NP / 2; k++) s[k] = MAGIC_C;
        if (sg == aw * 8 || seg == 0) {
          const int j0 = seg == 0 ? 0 : (seg == 1 ? 10 : 22);
          dk = dk0 + KSTEP * j0;
          dv = dv0 + VSTEP8 * j0;
          const uint4 qv = lds128(sb + SM_Q + tau * 2048 + tid * 16);
          q[0] = qv.x; q[1] = qv.y; q[2] = qv.z; q[3] = qv.w;
#pragma unroll
          for (int k = 0; k < 12; k++) o[k] = 0.f;
          regfence(o); regfence(s);
          wg_fence(); issue_qk(s, q, dk); dk += KSTEP; wg_commit();
          wg_wait<0>(); regfence(s);
          softmax_step(s, p0, mlo, mhi);
          STEP(p0, p1);
          n2--;
        }
        regfence(s);
#pragma unroll 1
        for (; n2 > 0; n2--) { STEP(p1, p0); STEP(p0, p1); }
        if (sg == aw * 8 + 7 || seg == 2) {
          wg_fence(); issue_pv(o, p1, dv); dv += VSTEP8; wg_commit();
          wg_wait<0>(); regfence(o);
          if (sg == 8 || sg == 17) {
            float4* pp = g_part + (blockIdx.x * 2 + (aw - 1)) * 384 + tid;
            pp[0] = make_float4(o[0], o[1], o[2], o[3]); pp[128] = make_float4(o[4], o[5], o[6], o[7]); pp[256] = make_float4(o[8], o[9], o[10], o[11]);
            __threadfence_block();
            if (wg == 2) publish_z1();
            bar_arrive(5 + aw, 256);
          } else {
            if (sg == 7 || sg == 15) {
              bar_sync(6 + aw, 256);
              const float4* pp = g_part + (blockIdx.x * 2 + aw) * 384 + tid;
              const float4 a = pp[0], b = pp[128], c = pp[256];
              o[0] += a.x; o[1] += a.y; o[2] += a.z; o[3] += a.w; o[4] += b.x; o[5] += b.y; o[6] += b.z; o[7] += b.w; o[8] += c.x; o[10] += c.z;
            }
            { chk ^= pend; pend = store_o_tile(o, ai, aj, tau, tid, sb); }
          }
        }
      }
#undef STEP
    } else {
      if (wg == 2) publish_z1();
      mbar_wait(BAR(B_KFB), 0);
      constexpr float SC = 0.25f * 1.4426950408889634f;
#pragma unroll 1
      for (int tau = wg * 3; tau < wg * 3 + 3 && tau < 8; tau++) {
        const uint4 qv = lds128(sb + SM_Q + tau * 2048 + tid * 16);
        float m0 = -INFINITY, m1 = -INFINITY;
#pragma unroll
        for (int k = 0; k < 12; k++) o[k] = 0.f;
        uint64_t dv = dv0;
#pragma unroll 1
        for (int j = 0; j < 32; j++) {
          regfence(s);
          wg_fence(); wg_qkb_n64<0, 0, 32>(s, qv.x, qv.y, qv.z, qv.w, dk0 + KSTEP * j); wg_commit();
          wg_wait<0>(); regfence(s);
          float x0 = m0, x1 = m1;
#pragma unroll
          for (int k = 0; k < 32; k++) { s[k] *= SC; if (k & 2) x1 = fmaxf(x1, s[k]); else x0 = fmaxf(x0, s[k]); }
          x0 = fmaxf(x0, __shfl_xor_sync(0xffffffffu, x0, 1)); x0 = fmaxf(x0, __shfl_xor_sync(0xffffffffu, x0, 2));
          x1 = fmaxf(x1, __shfl_xor_sync(0xffffffffu, x1, 1)); x1 = fmaxf(x1, __shfl_xor_sync(0xffffffffu, x1, 2));
          const float c0 = ex2(m0 - x0), c1 = ex2(m1 - x1);
          m0 = x0; m1 = x1;
#pragma unroll
          for (int k = 0; k < 12; k++) o[k] *= (k & 2) ? c1 : c0;
#pragma unroll
          for (int k = 0; k < 16; k++) { const float m = (k & 1) ? m1 : m0; p0[k] = exp_mufu(s[2 * k] - m, s[2 * k + 1] - m); }
          regfence(o);
          wg_fence(); issue_pv(o, p0, dv); dv += VSTEP8; wg_commit();
          wg_wait<0>(); regfence(o);
        }
        { chk ^= pend; pend = store_o_tile(o, ai, aj, tau, tid, sb); }
      }
    }
    consume(chk ^ pend, sb);
    fence_async();
    bar_sync(1 + wg, 128);
    if (tid == 0) { red_relaxed(&g_ocnt[ai * 32]); mbar_arrive_both(BAR(B_ATT)); TS(31 + wg); if (wg == 0) GTS(124); }
    }
  }
  __syncwarp();
  asm volatile("barrier.cluster.arrive.relaxed;" ::: "memory");
  asm volatile("barrier.cluster.wait;" ::: "memory");
}

typedef CUresult (*EncodeFn)(CUtensorMap*, CUtensorMapDataType, cuuint32_t, void*, const cuuint64_t*, const cuuint64_t*,
                             const cuuint32_t*, const cuuint32_t*, CUtensorMapInterleave, CUtensorMapSwizzle,
                             CUtensorMapL2promotion, CUtensorMapFloatOOBfill);

void make_map(EncodeFn enc, CUtensorMap* tm, const void* base, uint64_t cols, uint64_t rows, uint32_t bc, uint32_t br, CUtensorMapSwizzle sw) {
  cuuint64_t gd[2] = {cols, rows};
  cuuint64_t gs[1] = {cols * 2};
  cuuint32_t bd[2] = {bc, br};
  cuuint32_t es[2] = {1, 1};
  enc(tm, CU_TENSOR_MAP_DATA_TYPE_BFLOAT16, 2, const_cast<void*>(base), gd, gs, bd, es, CU_TENSOR_MAP_INTERLEAVE_NONE, sw,
      CU_TENSOR_MAP_L2_PROMOTION_L2_128B, CU_TENSOR_MAP_FLOAT_OOB_FILL_NONE);
}

}

extern "C" void kernel_launch(void* const* d_in, const int* in_sizes, int n_in, void* d_out, int out_size) {
  (void)in_sizes; (void)n_in; (void)out_size;
  static EncodeFn enc = nullptr;
  if (!enc) {
    void* fn = nullptr;
    cudaDriverEntryPointQueryResult qr;
    cudaGetDriverEntryPoint("cuTensorMapEncodeTiled", &fn, cudaEnableDefault, &qr);
    enc = (EncodeFn)fn;
    cudaFuncSetAttribute(fused_kernel, cudaFuncAttributeMaxDynamicSharedMemorySize, SMEM_BYTES);
  }
  CUtensorMap tx, tq, tin, tsp, tout, to;
  make_map(enc, &tx, d_in[0], 512, 2048, 64, 128, CU_TENSOR_MAP_SWIZZLE_128B);
  make_map(enc, &tq, d_in[1], 512, 512, 32, 32, CU_TENSOR_MAP_SWIZZLE_64B);
  make_map(enc, &to, d_in[4], 512, 512, 64, 64, CU_TENSOR_MAP_SWIZZLE_128B);
  {
    cuuint64_t gd[3] = {32, 512, 43};
    cuuint64_t gs[2] = {1376 * 2, 64};
    cuuint32_t bd[3] = {32, 32, 3};
    cuuint32_t es[3] = {1, 1, 1};
    enc(&tin, CU_TENSOR_MAP_DATA_TYPE_BFLOAT16, 3, d_in[6], gd, gs, bd, es, CU_TENSOR_MAP_INTERLEAVE_NONE, CU_TENSOR_MAP_SWIZZLE_64B,
        CU_TENSOR_MAP_L2_PROMOTION_L2_128B, CU_TENSOR_MAP_FLOAT_OOB_FILL_NONE);
  }
  make_map(enc, &tsp, d_in[7], 2048, 2048, 64, 64, CU_TENSOR_MAP_SWIZZLE_128B);
  make_map(enc, &tout, d_in[9], 512, 688, 64, 64, CU_TENSOR_MAP_SWIZZLE_128B);
  Params prm;
  prm.gate_w = (const __nv_bfloat16*)d_in[10];
  prm.b_sp = (const __nv_bfloat16*)d_in[8];
  prm.w_out = (const __nv_bfloat16*)d_in[9];
  prm.wo = (const __nv_bfloat16*)d_in[4];
  prm.w_in = (const __nv_bfloat16*)d_in[6];
  prm.wq = (const __nv_bfloat16*)d_in[1];
  prm.wk = (const __nv_bfloat16*)d_in[2];
  prm.wv = (const __nv_bfloat16*)d_in[3];
  prm.mlo = 0x007F007Fu;
  prm.mhi = 0xFF80FF80u;
  prm.out = (__nv_bfloat16*)d_out;
  fused_kernel<<<NCTA, NTHREADS, SMEM_BYTES>>>(tx, tq, tin, tsp, tout, to, prm);
}
```

```cpp
#include <cuda_runtime.h>
#include <cuda.h>
#include <cuda_bf16.h>
#include <cuda_fp16.h>
#include <stdint.h>

namespace {

constexpr int NCTA = 128;
constexpr int NTHREADS = 640;
constexpr int NP = 40;
constexpr int NM = 64 - NP;
constexpr int SPIN_LIMIT = 1 << 18;
#define SBATCH 1

constexpr uint32_t SM_K = 0;
constexpr uint32_t SM_ONES = 131072;
constexpr uint32_t KV_BYTES = 131072;
constexpr uint32_t SM_BAR = 131584;
constexpr uint32_t SM_RING = 132096;
constexpr uint32_t RSTAGE = 27648;
constexpr uint32_t WSLOT = 16384;
constexpr uint32_t SM_WKV = SM_RING + 4 * WSLOT;
constexpr uint32_t SM_GW = SM_WKV + 16384;
constexpr uint32_t SM_Q = 215040;
constexpr uint32_t SM_G = 231424;
constexpr uint32_t SM_MISC = 231936;
constexpr uint32_t SMEM_BYTES = 232448;

constexpr int B_XFULL = 0, B_XEMPTY = 8, B_WFULL = 16, B_WEMPTY = 32, B_RFULL = 44, B_REMPTY = 47, B_KVFULL = 50,
              B_KFB = 51, B_KSTAT = 52, B_DEC = 53, B_ZST0 = 43, B_ZST1 = 63, B_WOFULL = 54, B_EPOCH = 55, B_ZOK = 56, B_Z1OK = 57, B_ATT = 58, B_QRDY = 59, B_LNOK = 60, B_KVB = 61, B_KVC = 62;
constexpr int M_EPOCH = 0, M_KN2 = 1, M_VOK = 2, M_FAST = 3, M_KVR = 4, M_RED = 16;

__device__ uint4 g_kimg[KV_BYTES / 16];
__device__ uint4 g_kbf[65536 / 16];
__device__ unsigned long long g_kvflag[NCTA];
__device__ uint4 g_lnstat[16 * 8 * 128];
__device__ float g_gate[2048];
__device__ uint4 g_z2n[8 * 32 * 11264 / 16];
__device__ uint4 g_z1[16 * 88 * 128];
__device__ uint4 g_u[16 * 11 * 1024];
__device__ uint4 g_o[16 * 8 * 1024];
__device__ float4 g_part[NCTA * 2 * 3 * 128];
__device__ unsigned g_ticket;
__device__ unsigned g_zcnt[16 * 32];
__device__ unsigned g_z1cnt[16 * 32];
__device__ unsigned g_ucnt[16 * 32];
__device__ unsigned g_ocnt[16 * 32];
#define TS(k) do { } while (0)
#define GTS(k) do { } while (0)

__device__ __forceinline__ void mbar_init(uint32_t a, uint32_t c) { asm volatile("mbarrier.init.shared::cta.b64 [%0], %1;" ::"r"(a), "r"(c) : "memory"); }
__device__ __forceinline__ void mbar_arrive(uint32_t a) { asm volatile("mbarrier.arrive.shared::cta.b64 _, [%0];" ::"r"(a) : "memory"); }
__device__ __forceinline__ void mbar_arrive_both(uint32_t a) {
  asm volatile("{\n.reg .b32 ra;\nmapa.shared::cluster.u32 ra, %0, 0;\nmbarrier.arrive.shared::cluster.b64 _, [ra];\n"
               "mapa.shared::cluster.u32 ra, %0, 1;\nmbarrier.arrive.shared::cluster.b64 _, [ra];\n}" ::"r"(a) : "memory");
}
__device__ __forceinline__ void mbar_wait(uint32_t a, uint32_t ph) {
  uint32_t ok;
#pragma unroll 1
  for (int n = 0; n < SPIN_LIMIT; n++) {
    asm volatile("{\n.reg .pred p;\nmbarrier.try_wait.parity.shared::cta.b64 p, [%1], %2;\nselp.u32 %0, 1, 0, p;\n}" : "=r"(ok) : "r"(a), "r"(ph) : "memory");
    if (ok) break;
  }
}
#define ELECT "{\n.reg .pred p;\nelect.sync _|p, 0xffffffff;\n@p "
__device__ __forceinline__ void e_expect(uint32_t a, uint32_t b) { asm volatile(ELECT "mbarrier.arrive.expect_tx.shared::cta.b64 _, [%0], %1;\n}" ::"r"(a), "r"(b) : "memory"); }
__device__ __forceinline__ void e_arrive(uint32_t a) { asm volatile(ELECT "mbarrier.arrive.shared::cta.b64 _, [%0];\n}" ::"r"(a) : "memory"); }
__device__ __forceinline__ void tma2d(uint32_t dst, const CUtensorMap* tm, int c0, int c1, uint32_t bar) {
  asm volatile(ELECT "cp.async.bulk.tensor.2d.shared::cluster.global.mbarrier::complete_tx::bytes [%0], [%1, {%3, %4}], [%2];\n}"
               ::"r"(dst), "l"(tm), "r"(bar), "r"(c0), "r"(c1) : "memory");
}
__device__ __forceinline__ void tma2d_mc(uint32_t dst, const CUtensorMap* tm, int c0, int c1, uint32_t bar) {
  asm volatile(ELECT "cp.async.bulk.tensor.2d.shared::cluster.global.mbarrier::complete_tx::bytes.multicast::cluster [%0], [%1, {%3, %4}], [%2], %5;\n}"
               ::"r"(dst), "l"(tm), "r"(bar), "r"(c0), "r"(c1), "h"((uint16_t)3) : "memory");
}
__device__ __forceinline__ void tma3d(uint32_t dst, const CUtensorMap* tm, int c0, int c1, int c2, uint32_t bar) {
  asm volatile(ELECT "cp.async.bulk.tensor.3d.shared::cluster.global.mbarrier::complete_tx::bytes [%0], [%1, {%3, %4, %5}], [%2];\n}"
               ::"r"(dst), "l"(tm), "r"(bar), "r"(c0), "r"(c1), "r"(c2) : "memory");
}
__device__ __forceinline__ void tma3d_mc(uint32_t dst, const CUtensorMap* tm, int c0, int c1, int c2, uint32_t bar) {
  asm volatile(ELECT "cp.async.bulk.tensor.3d.shared::cluster.global.mbarrier::complete_tx::bytes.multicast::cluster [%0], [%1, {%3, %4, %5}], [%2], %6;\n}"
               ::"r"(dst), "l"(tm), "r"(bar), "r"(c0), "r"(c1), "r"(c2), "h"((uint16_t)3) : "memory");
}
__device__ __forceinline__ void tma2d_pf(const CUtensorMap* tm, int c0, int c1) {
  asm volatile(ELECT "cp.async.bulk.prefetch.tensor.2d.L2.global [%0, {%1, %2}];\n}" ::"l"(tm), "r"(c0), "r"(c1) : "memory");
}
__device__ __forceinline__ void tm_prefetch(const CUtensorMap* tm) { asm volatile(ELECT "prefetch.tensormap [%0];\n}" ::"l"(tm) : "memory"); }
__device__ __forceinline__ void bulk(uint32_t dst, const void* src, uint32_t bytes, uint32_t bar) {
  asm volatile(ELECT "cp.async.bulk.shared::cluster.global.mbarrier::complete_tx::bytes [%0], [%1], %2, [%3];\n}"
               ::"r"(dst), "l"(src), "r"(bytes), "r"(bar) : "memory");
}
__device__ __forceinline__ void bulk_mc(uint32_t dst, const void* src, uint32_t bytes, uint32_t bar) {
  asm volatile(ELECT "cp.async.bulk.shared::cluster.global.mbarrier::complete_tx::bytes.multicast::cluster [%0], [%1], %2, [%3], %4;\n}"
               ::"r"(dst), "l"(src), "r"(bytes), "r"(bar), "h"((uint16_t)3) : "memory");
}
__device__ __forceinline__ void l2_prefetch(const void* src, uint32_t bytes) { asm volatile(ELECT "cp.async.bulk.prefetch.L2.global [%0], %1;\n}" ::"l"(src), "r"(bytes) : "memory"); }
__device__ __forceinline__ void fence_async() { asm volatile("fence.proxy.async.global;" ::: "memory"); }
__device__ __forceinline__ void fence_async_smem() { asm volatile("fence.proxy.async.shared::cta;" ::: "memory"); }
__device__ __forceinline__ void bar_sync(int id, int n) { asm volatile("bar.sync %0, %1;" ::"r"(id), "r"(n) : "memory"); }
__device__ __forceinline__ void bar_arrive(int id, int n) { asm volatile("bar.arrive %0, %1;" ::"r"(id), "r"(n) : "memory"); }
__device__ __forceinline__ void red_release(unsigned* p) { asm volatile("red.release.gpu.global.add.u32 [%0], 1;" ::"l"(p) : "memory"); }
__device__ __forceinline__ void red_relaxed(unsigned* p) { asm volatile("red.relaxed.gpu.global.add.u32 [%0], 1;" ::"l"(p) : "memory"); }
__device__ __forceinline__ uint32_t ld_back(const void* p) { uint32_t v; asm volatile("ld.relaxed.gpu.global.u32 %0, [%1];" : "=r"(v) : "l"(p) : "memory"); return v; }
__device__ __forceinline__ void consume(uint32_t v, uint32_t sb) { if (v == 0xDEADBEEFu) asm volatile("st.shared.u32 [%0], %1;" ::"r"(sb + SM_MISC + 60), "r"(v) : "memory"); }
__device__ __forceinline__ unsigned ld_acquire(const unsigned* p) { unsigned v; asm volatile("ld.acquire.gpu.global.u32 %0, [%1];" : "=r"(v) : "l"(p) : "memory"); return v; }
__device__ __forceinline__ void wait_ge(const unsigned* p, unsigned target) {
#pragma unroll 1
  for (int n = 0; n < SPIN_LIMIT; n++) {
    if ((int)(ld_acquire(p) - target) >= 0) break;
    __nanosleep(100);
  }
}
__device__ __forceinline__ void wg_fence() { asm volatile("wgmma.fence.sync.aligned;" ::: "memory"); }
__device__ __forceinline__ void wg_commit() { asm volatile("wgmma.commit_group.sync.aligned;" ::: "memory"); }
template <int N> __device__ __forceinline__ void wg_wait() { asm volatile("wgmma.wait_group.sync.aligned %0;" ::"n"(N) : "memory"); }
template <int n> __device__ __forceinline__ void regfence(float (&d)[n]) {
#pragma unroll
  for (int i = 0; i < n; i++) asm volatile("" : "+f"(d[i])::"memory");
}
__device__ __forceinline__ uint64_t mkdesc(uint32_t addr, uint32_t lbo, uint32_t sbo, int swz) {
  return (uint64_t)((addr & 0x3FFFF) >> 4) | ((uint64_t)(lbo >> 4) << 16) | ((uint64_t)(sbo >> 4) << 32) | ((uint64_t)swz << 62);
}
__device__ __forceinline__ uint32_t pack_bf16(float lo, float hi) { uint32_t r; asm("cvt.rn.bf16x2.f32 %0, %1, %2;" : "=r"(r) : "f"(hi), "f"(lo)); return r; }
__device__ __forceinline__ uint32_t pack_f16(float lo, float hi) { uint32_t r; asm("cvt.rn.f16x2.f32 %0, %1, %2;" : "=r"(r) : "f"(hi), "f"(lo)); return r; }
__device__ __forceinline__ float bf_lo(uint32_t v) { return __uint_as_float(v << 16); }
__device__ __forceinline__ float bf_hi(uint32_t v) { return __uint_as_float(v & 0xFFFF0000u); }
__device__ __forceinline__ float ex2(float x) { float r; asm("ex2.approx.ftz.f32 %0, %1;" : "=f"(r) : "f"(x)); return r; }
__device__ __forceinline__ float gelu2_tanh(float x) {
  float u = x * fmaf(x * x, 0.0356774081f, 0.7978845608f), t;
  asm("tanh.approx.f32 %0, %1;" : "=f"(t) : "f"(u));
  return fmaf(x, t, x);
}
__device__ __forceinline__ void sts32(uint32_t a, uint32_t v) { asm volatile("st.shared.u32 [%0], %1;" ::"r"(a), "r"(v) : "memory"); }
__device__ __forceinline__ void sts16(uint32_t a, uint16_t v) { asm volatile("st.shared.u16 [%0], %1;" ::"r"(a), "h"(v) : "memory"); }
__device__ __forceinline__ void sts128(uint32_t a, uint32_t x, uint32_t y, uint32_t z, uint32_t w) { asm volatile("st.shared.v4.u32 [%0], {%1,%2,%3,%4};" ::"r"(a), "r"(x), "r"(y), "r"(z), "r"(w) : "memory"); }
__device__ __forceinline__ uint32_t lds32(uint32_t a) { uint32_t v; asm volatile("ld.shared.u32 %0, [%1];" : "=r"(v) : "r"(a) : "memory"); return v; }
__device__ __forceinline__ float ldsf(uint32_t a) { return __uint_as_float(lds32(a)); }
__device__ __forceinline__ uint4 lds128(uint32_t a) { uint4 v; asm volatile("ld.shared.v4.u32 {%0,%1,%2,%3}, [%4];" : "=r"(v.x), "=r"(v.y), "=r"(v.z), "=r"(v.w) : "r"(a) : "memory"); return v; }

template<int OFF, int TOT> __device__ __forceinline__ void wg_ss_n88(float (&d)[TOT], uint64_t da, uint64_t db) {
  asm volatile("wgmma.mma_async.sync.aligned.m64n88k16.f32.bf16.bf16 {%0, %1, %2, %3, %4, %5, %6, %7, %8, %9, %10, %11, %12, %13, %14, %15, %16, %17, %18, %19, %20, %21, %22, %23, %24, %25, %26, %27, %28, %29, %30, %31, %32, %33, %34, %35, %36, %37, %38, %39, %40, %41, %42, %43}, %44, %45, 1, 1, 1, 0, 1;"
    : "+f"(d[OFF+0]), "+f"(d[OFF+1]), "+f"(d[OFF+2]), "+f"(d[OFF+3]), "+f"(d[OFF+4]), "+f"(d[OFF+5]), "+f"(d[OFF+6]), "+f"(d[OFF+7]),
      "+f"(d[OFF+8]), "+f"(d[OFF+9]), "+f"(d[OFF+10]), "+f"(d[OFF+11]), "+f"(d[OFF+12]), "+f"(d[OFF+13]), "+f"(d[OFF+14]), "+f"(d[OFF+15]),
      "+f"(d[OFF+16]), "+f"(d[OFF+17]), "+f"(d[OFF+18]), "+f"(d[OFF+19]), "+f"(d[OFF+20]), "+f"(d[OFF+21]), "+f"(d[OFF+22]), "+f"(d[OFF+23]),
      "+f"(d[OFF+24]), "+f"(d[OFF+25]), "+f"(d[OFF+26]), "+f"(d[OFF+27]), "+f"(d[OFF+28]), "+f"(d[OFF+29]), "+f"(d[OFF+30]), "+f"(d[OFF+31]),
      "+f"(d[OFF+32]), "+f"(d[OFF+33]), "+f"(d[OFF+34]), "+f"(d[OFF+35]), "+f"(d[OFF+36]), "+f"(d[OFF+37]), "+f"(d[OFF+38]), "+f"(d[OFF+39]),
      "+f"(d[OFF+40]), "+f"(d[OFF+41]), "+f"(d[OFF+42]), "+f"(d[OFF+43])
    : "l"(da), "l"(db));
}
template<int OFF, int TOT> __device__ __forceinline__ void wg_ss_n128(float (&d)[TOT], uint64_t da, uint64_t db) {
  asm volatile("wgmma.mma_async.sync.aligned.m64n128k16.f32.bf16.bf16 {%0, %1, %2, %3, %4, %5, %6, %7, %8, %9, %10, %11, %12, %13, %14, %15, %16, %17, %18, %19, %20, %21, %22, %23, %24, %25, %26, %27, %28, %29, %30, %31, %32, %33, %34, %35, %36, %37, %38, %39, %40, %41, %42, %43, %44, %45, %46, %47, %48, %49, %50, %51, %52, %53, %54, %55, %56, %57, %58, %59, %60, %61, %62, %63}, %64, %65, 1, 1, 1, 0, 1;"
    : "+f"(d[OFF+0]), "+f"(d[OFF+1]), "+f"(d[OFF+2]), "+f"(d[OFF+3]), "+f"(d[OFF+4]), "+f"(d[OFF+5]), "+f"(d[OFF+6]), "+f"(d[OFF+7]),
      "+f"(d[OFF+8]), "+f"(d[OFF+9]), "+f"(d[OFF+10]), "+f"(d[OFF+11]), "+f"(d[OFF+12]), "+f"(d[OFF+13]), "+f"(d[OFF+14]), "+f"(d[OFF+15]),
      "+f"(d[OFF+16]), "+f"(d[OFF+17]), "+f"(d[OFF+18]), "+f"(d[OFF+19]), "+f"(d[OFF+20]), "+f"(d[OFF+21]), "+f"(d[OFF+22]), "+f"(d[OFF+23]),
      "+f"(d[OFF+24]), "+f"(d[OFF+25]), "+f"(d[OFF+26]), "+f"(d[OFF+27]), "+f"(d[OFF+28]), "+f"(d[OFF+29]), "+f"(d[OFF+30]), "+f"(d[OFF+31]),
      "+f"(d[OFF+32]), "+f"(d[OFF+33]), "+f"(d[OFF+34]), "+f"(d[OFF+35]), "+f"(d[OFF+36]), "+f"(d[OFF+37]), "+f"(d[OFF+38]), "+f"(d[OFF+39]),
      "+f"(d[OFF+40]), "+f"(d[OFF+41]), "+f"(d[OFF+42]), "+f"(d[OFF+43]), "+f"(d[OFF+44]), "+f"(d[OFF+45]), "+f"(d[OFF+46]), "+f"(d[OFF+47]),
      "+f"(d[OFF+48]), "+f"(d[OFF+49]), "+f"(d[OFF+50]), "+f"(d[OFF+51]), "+f"(d[OFF+52]), "+f"(d[OFF+53]), "+f"(d[OFF+54]), "+f"(d[OFF+55]),
      "+f"(d[OFF+56]), "+f"(d[OFF+57]), "+f"(d[OFF+58]), "+f"(d[OFF+59]), "+f"(d[OFF+60]), "+f"(d[OFF+61]), "+f"(d[OFF+62]), "+f"(d[OFF+63])
    : "l"(da), "l"(db));
}
template<int OFF, int TOT> __device__ __forceinline__ void wg_ss_n64(float (&d)[TOT], uint64_t da, uint64_t db) {
  asm volatile("wgmma.mma_async.sync.aligned.m64n64k16.f32.bf16.bf16 {%0, %1, %2, %3, %4, %5, %6, %7, %8, %9, %10, %11, %12, %13, %14, %15, %16, %17, %18, %19, %20, %21, %22, %23, %24, %25, %26, %27, %28, %29, %30, %31}, %32, %33, 1, 1, 1, 0, 1;"
    : "+f"(d[OFF+0]), "+f"(d[OFF+1]), "+f"(d[OFF+2]), "+f"(d[OFF+3]), "+f"(d[OFF+4]), "+f"(d[OFF+5]), "+f"(d[OFF+6]), "+f"(d[OFF+7]),
      "+f"(d[OFF+8]), "+f"(d[OFF+9]), "+f"(d[OFF+10]), "+f"(d[OFF+11]), "+f"(d[OFF+12]), "+f"(d[OFF+13]), "+f"(d[OFF+14]), "+f"(d[OFF+15]),
      "+f"(d[OFF+16]), "+f"(d[OFF+17]), "+f"(d[OFF+18]), "+f"(d[OFF+19]), "+f"(d[OFF+20]), "+f"(d[OFF+21]), "+f"(d[OFF+22]), "+f"(d[OFF+23]),
      "+f"(d[OFF+24]), "+f"(d[OFF+25]), "+f"(d[OFF+26]), "+f"(d[OFF+27]), "+f"(d[OFF+28]), "+f"(d[OFF+29]), "+f"(d[OFF+30]), "+f"(d[OFF+31])
    : "l"(da), "l"(db));
}
template<int OFF, int TOT> __device__ __forceinline__ void wg_ss_n32t(float (&d)[TOT], uint64_t da, uint64_t db) {
  asm volatile("wgmma.mma_async.sync.aligned.m64n32k16.f32.bf16.bf16 {%0, %1, %2, %3, %4, %5, %6, %7, %8, %9, %10, %11, %12, %13, %14, %15}, %16, %17, 1, 1, 1, 1, 0;"
    : "+f"(d[OFF+0]), "+f"(d[OFF+1]), "+f"(d[OFF+2]), "+f"(d[OFF+3]), "+f"(d[OFF+4]), "+f"(d[OFF+5]), "+f"(d[OFF+6]), "+f"(d[OFF+7]),
      "+f"(d[OFF+8]), "+f"(d[OFF+9]), "+f"(d[OFF+10]), "+f"(d[OFF+11]), "+f"(d[OFF+12]), "+f"(d[OFF+13]), "+f"(d[OFF+14]), "+f"(d[OFF+15])
    : "l"(da), "l"(db));
}
template<int OFF, int TOT> __device__ __forceinline__ void wg_ss_n8(float (&d)[TOT], uint64_t da, uint64_t db) {
  asm volatile("wgmma.mma_async.sync.aligned.m64n8k16.f32.bf16.bf16 {%0, %1, %2, %3}, %4, %5, 1, 1, 1, 0, 0;"
    : "+f"(d[OFF+0]), "+f"(d[OFF+1]), "+f"(d[OFF+2]), "+f"(d[OFF+3])
    : "l"(da), "l"(db));
}
template<int SCD, int OFF, int TOT> __device__ __forceinline__ void wg_qk_n16(float (&d)[TOT], uint32_t a0, uint32_t a1, uint32_t a2, uint32_t a3, uint64_t db) {
  asm volatile("wgmma.mma_async.sync.aligned.m64n16k16.f32.f16.f16 {%0, %1, %2, %3, %4, %5, %6, %7}, {%8,%9,%10,%11}, %12, %13, 1, 1, 0;"
    : "+f"(d[OFF+0]), "+f"(d[OFF+1]), "+f"(d[OFF+2]), "+f"(d[OFF+3]), "+f"(d[OFF+4]), "+f"(d[OFF+5]), "+f"(d[OFF+6]), "+f"(d[OFF+7])
    : "r"(a0), "r"(a1), "r"(a2), "r"(a3), "l"(db), "n"(SCD));
}
template<int SCD, int OFF, int TOT> __device__ __forceinline__ void wg_qk_n24(float (&d)[TOT], uint32_t a0, uint32_t a1, uint32_t a2, uint32_t a3, uint64_t db) {
  asm volatile("wgmma.mma_async.sync.aligned.m64n24k16.f32.f16.f16 {%0, %1, %2, %3, %4, %5, %6, %7, %8, %9, %10, %11}, {%12,%13,%14,%15}, %16, %17, 1, 1, 0;"
    : "+f"(d[OFF+0]), "+f"(d[OFF+1]), "+f"(d[OFF+2]), "+f"(d[OFF+3]), "+f"(d[OFF+4]), "+f"(d[OFF+5]), "+f"(d[OFF+6]), "+f"(d[OFF+7]),
      "+f"(d[OFF+8]), "+f"(d[OFF+9]), "+f"(d[OFF+10]), "+f"(d[OFF+11])
    : "r"(a0), "r"(a1), "r"(a2), "r"(a3), "l"(db), "n"(SCD));
}
template<int SCD, int OFF, int TOT> __device__ __forceinline__ void wg_qk_n32(float (&d)[TOT], uint32_t a0, uint32_t a1, uint32_t a2, uint32_t a3, uint64_t db) {
  asm volatile("wgmma.mma_async.sync.aligned.m64n32k16.f32.f16.f16 {%0, %1, %2, %3, %4, %5, %6, %7, %8, %9, %10, %11, %12, %13, %14, %15}, {%16,%17,%18,%19}, %20, %21, 1, 1, 0;"
    : "+f"(d[OFF+0]), "+f"(d[OFF+1]), "+f"(d[OFF+2]), "+f"(d[OFF+3]), "+f"(d[OFF+4]), "+f"(d[OFF+5]), "+f"(d[OFF+6]), "+f"(d[OFF+7]),
      "+f"(d[OFF+8]), "+f"(d[OFF+9]), "+f"(d[OFF+10]), "+f"(d[OFF+11]), "+f"(d[OFF+12]), "+f"(d[OFF+13]), "+f"(d[OFF+14]), "+f"(d[OFF+15])
    : "r"(a0), "r"(a1), "r"(a2), "r"(a3), "l"(db), "n"(SCD));
}
template<int SCD, int OFF, int TOT> __device__ __forceinline__ void wg_qk_n40(float (&d)[TOT], uint32_t a0, uint32_t a1, uint32_t a2, uint32_t a3, uint64_t db) {
  asm volatile("wgmma.mma_async.sync.aligned.m64n40k16.f32.f16.f16 {%0, %1, %2, %3, %4, %5, %6, %7, %8, %9, %10, %11, %12, %13, %14, %15, %16, %17, %18, %19}, {%20,%21,%22,%23}, %24, %25, 1, 1, 0;"
    : "+f"(d[OFF+0]), "+f"(d[OFF+1]), "+f"(d[OFF+2]), "+f"(d[OFF+3]), "+f"(d[OFF+4]), "+f"(d[OFF+5]), "+f"(d[OFF+6]), "+f"(d[OFF+7]),
      "+f"(d[OFF+8]), "+f"(d[OFF+9]), "+f"(d[OFF+10]), "+f"(d[OFF+11]), "+f"(d[OFF+12]), "+f"(d[OFF+13]), "+f"(d[OFF+14]), "+f"(d[OFF+15]),
      "+f"(d[OFF+16]), "+f"(d[OFF+17]), "+f"(d[OFF+18]), "+f"(d[OFF+19])
    : "r"(a0), "r"(a1), "r"(a2), "r"(a3), "l"(db), "n"(SCD));
}
template<int SCD, int OFF, int TOT> __device__ __forceinline__ void wg_qk_n48(float (&d)[TOT], uint32_t a0, uint32_t a1, uint32_t a2, uint32_t a3, uint64_t db) {
  asm volatile("wgmma.mma_async.sync.aligned.m64n48k16.f32.f16.f16 {%0, %1, %2, %3, %4, %5, %6, %7, %8, %9, %10, %11, %12, %13, %14, %15, %16, %17, %18, %19, %20, %21, %22, %23}, {%24,%25,%26,%27}, %28, %29, 1, 1, 0;"
    : "+f"(d[OFF+0]), "+f"(d[OFF+1]), "+f"(d[OFF+2]), "+f"(d[OFF+3]), "+f"(d[OFF+4]), "+f"(d[OFF+5]), "+f"(d[OFF+6]), "+f"(d[OFF+7]),
      "+f"(d[OFF+8]), "+f"(d[OFF+9]), "+f"(d[OFF+10]), "+f"(d[OFF+11]), "+f"(d[OFF+12]), "+f"(d[OFF+13]), "+f"(d[OFF+14]), "+f"(d[OFF+15]),
      "+f"(d[OFF+16]), "+f"(d[OFF+17]), "+f"(d[OFF+18]), "+f"(d[OFF+19]), "+f"(d[OFF+20]), "+f"(d[OFF+21]), "+f"(d[OFF+22]), "+f"(d[OFF+23])
    : "r"(a0), "r"(a1), "r"(a2), "r"(a3), "l"(db), "n"(SCD));
}
template<int SCD, int OFF, int TOT> __device__ __forceinline__ void wg_pv_n24(float (&d)[TOT], uint32_t a0, uint32_t a1, uint32_t a2, uint32_t a3, uint64_t db) {
  asm volatile("wgmma.mma_async.sync.aligned.m64n24k16.f32.bf16.bf16 {%0, %1, %2, %3, %4, %5, %6, %7, %8, %9, %10, %11}, {%12,%13,%14,%15}, %16, %17, 1, 1, 1;"
    : "+f"(d[OFF+0]), "+f"(d[OFF+1]), "+f"(d[OFF+2]), "+f"(d[OFF+3]), "+f"(d[OFF+4]), "+f"(d[OFF+5]), "+f"(d[OFF+6]), "+f"(d[OFF+7]),
      "+f"(d[OFF+8]), "+f"(d[OFF+9]), "+f"(d[OFF+10]), "+f"(d[OFF+11])
    : "r"(a0), "r"(a1), "r"(a2), "r"(a3), "l"(db), "n"(SCD));
}
template<int SCD, int OFF, int TOT> __device__ __forceinline__ void wg_qkb_n64(float (&d)[TOT], uint32_t a0, uint32_t a1, uint32_t a2, uint32_t a3, uint64_t db) {
  asm volatile("wgmma.mma_async.sync.aligned.m64n64k16.f32.bf16.bf16 {%0, %1, %2, %3, %4, %5, %6, %7, %8, %9, %10, %11, %12, %13, %14, %15, %16, %17, %18, %19, %20, %21, %22, %23, %24, %25, %26, %27, %28, %29, %30, %31}, {%32,%33,%34,%35}, %36, %37, 1, 1, 0;"
    : "+f"(d[OFF+0]), "+f"(d[OFF+1]), "+f"(d[OFF+2]), "+f"(d[OFF+3]), "+f"(d[OFF+4]), "+f"(d[OFF+5]), "+f"(d[OFF+6]), "+f"(d[OFF+7]),
      "+f"(d[OFF+8]), "+f"(d[OFF+9]), "+f"(d[OFF+10]), "+f"(d[OFF+11]), "+f"(d[OFF+12]), "+f"(d[OFF+13]), "+f"(d[OFF+14]), "+f"(d[OFF+15]),
      "+f"(d[OFF+16]), "+f"(d[OFF+17]), "+f"(d[OFF+18]), "+f"(d[OFF+19]), "+f"(d[OFF+20]), "+f"(d[OFF+21]), "+f"(d[OFF+22]), "+f"(d[OFF+23]),
      "+f"(d[OFF+24]), "+f"(d[OFF+25]), "+f"(d[OFF+26]), "+f"(d[OFF+27]), "+f"(d[OFF+28]), "+f"(d[OFF+29]), "+f"(d[OFF+30]), "+f"(d[OFF+31])
    : "r"(a0), "r"(a1), "r"(a2), "r"(a3), "l"(db), "n"(SCD));
}
template<int N, int SCD, int OFF, int TOT> __device__ __forceinline__ void wg_qk(float (&d)[TOT], const uint32_t (&q)[4], uint64_t db) {
  if constexpr (N == 16) wg_qk_n16<SCD, OFF, TOT>(d, q[0], q[1], q[2], q[3], db);
  if constexpr (N == 24) wg_qk_n24<SCD, OFF, TOT>(d, q[0], q[1], q[2], q[3], db);
  if constexpr (N == 32) wg_qk_n32<SCD, OFF, TOT>(d, q[0], q[1], q[2], q[3], db);
  if constexpr (N == 40) wg_qk_n40<SCD, OFF, TOT>(d, q[0], q[1], q[2], q[3], db);
  if constexpr (N == 48) wg_qk_n48<SCD, OFF, TOT>(d, q[0], q[1], q[2], q[3], db);
}

__device__ __forceinline__ uint32_t exp_mufu(float a, float b) { return pack_bf16(ex2(a), ex2(b)); }
__device__ __forceinline__ uint32_t exp_poly(float a, float b, uint32_t mlo, uint32_t mhi) {
  uint32_t u = __byte_perm(__float_as_uint(a), __float_as_uint(b), 0x6521), mh, e, p;
  asm("lop3.b32 %0, %1, %2, 0x3F003F00, 0xEA;" : "=r"(mh) : "r"(u), "r"(mlo));
  asm("lop3.b32 %0, %1, %2, 0x00020002, 0xEA;" : "=r"(e) : "r"(u), "r"(mhi));
  asm("fma.rn.bf16x2 %0, %1, %2, %3;" : "=r"(p) : "r"(u), "r"(mh), "r"(e));
  return p;
}
constexpr float MAGIC_C = 48948.0625f;
constexpr float QSCALE = 0.25f * 1.4426950408889634f * 8.f;
constexpr float BOUND = 80.f;

__device__ __forceinline__ void softmax_step(const float (&s)[32], uint32_t (&p)[16], uint32_t mlo, uint32_t mhi) {
  constexpr int PP = NP / 4;
  int ip = 0, im = PP;
#pragma unroll
  for (int i = 0; i < 16; i++) {
    if (((i + 1) * PP / 16) > (i * PP / 16)) { p[ip] = exp_poly(s[2 * ip], s[2 * ip + 1], mlo, mhi); ip++; }
    else { p[im] = exp_mufu(s[2 * im], s[2 * im + 1]); im++; }
  }
}
constexpr int64_t VSTEP = 32 - (32 << 16);
constexpr uint64_t KSTEP = 256, VSTEP8 = (uint64_t)(8 * VSTEP);
__device__ __forceinline__ void issue_qk(float (&s)[32], const uint32_t (&q)[4], uint64_t dk) {
  wg_qk<NM, 0, NP / 2, 32>(s, q, dk + NP * 2);
  wg_qk<NP, 1, 0, 32>(s, q, dk);
}
__device__ __forceinline__ void issue_pv(float (&o)[12], const uint32_t (&p)[16], uint64_t dv) {
#pragma unroll
  for (int c = 0; c < 4; c++) { wg_pv_n24<1, 0, 12>(o, p[4 * c], p[4 * c + 1], p[4 * c + 2], p[4 * c + 3], dv + c * VSTEP); }
}

__device__ __forceinline__ uint32_t wslot(int f) { const int r = f - 5 * ((f * 52) >> 8); return r == 4 ? SM_Q : SM_RING + r * WSLOT; }

struct Params {
  const __nv_bfloat16* gate_w;
  const __nv_bfloat16* b_sp;
  const __nv_bfloat16* w_out;
  const __nv_bfloat16* wo;
  const __nv_bfloat16* w_in;
  const __nv_bfloat16* wq;
  const __nv_bfloat16* wk;
  const __nv_bfloat16* wv;
  uint32_t mlo, mhi;
};

__device__ __forceinline__ uint32_t store_o_tile(const float (&o)[12], int bi, int bj, int tau, int tid, uint32_t sb) {
  const int half = tau & 1, hh = tau >> 1, w = tid >> 5, l = tid & 31;
  const int r0 = half * 64 + w * 16 + (l >> 2);
  const float f0 = __fdividef(ldsf(sb + SM_G + r0 * 4), o[8]), f1 = __fdividef(ldsf(sb + SM_G + (r0 + 8) * 4), o[10]);
  uint32_t* dst = reinterpret_cast<uint32_t*>(g_o) + (bi * 8 + bj) * 4096 + (half * 8 + w * 2) * 256 + hh * 64;
  dst[l] = pack_bf16(o[0] * f0, o[1] * f0);
  dst[l + 32] = pack_bf16(o[4] * f0, o[5] * f0);
  dst[l + 256] = pack_bf16(o[2] * f1, o[3] * f1);
  dst[l + 288] = pack_bf16(o[6] * f1, o[7] * f1);
  return ld_back(dst + ((l >> 3) & 1) * 256 + (l & 7) * 8);
}

__global__ void __cluster_dims__(2, 1, 1) __launch_bounds__(NTHREADS, 1)
fused_kernel(const __grid_constant__ CUtensorMap tm_x, const __grid_constant__ CUtensorMap tm_wq,
             const __grid_constant__ CUtensorMap tm_win, const __grid_constant__ CUtensorMap tm_wsp,
             const __grid_constant__ CUtensorMap tm_wout, const __grid_constant__ CUtensorMap tm_wo,
             const __grid_constant__ CUtensorMap tm_out, const Params prm) {
  extern __shared__ __align__(1024) uint8_t smem_raw[];
  const uint32_t sb = __shfl_sync(0xffffffffu, (uint32_t)__cvta_generic_to_shared(smem_raw), 0);
  const int warp = __shfl_sync(0xffffffffu, (int)(threadIdx.x >> 5), 0);
  const int wg = warp >> 2;
  const int tid = threadIdx.x & 127;
  const int lane = threadIdx.x & 31;
  const int rank = blockIdx.x & 1;
  const int ai = (blockIdx.x >> 4) * 2 + rank, aj = (blockIdx.x >> 1) & 7;
  const int bi = blockIdx.x >> 3, bj = blockIdx.x & 7;
  auto BAR = [&](int k) { return sb + SM_BAR + 8u * k; };

  if (warp == 16) {
    if (lane == 0) {
      mbar_init(BAR(B_XFULL), 1); mbar_init(BAR(B_XFULL + 1), 1);
      asm volatile("fence.mbarrier_init.release.cluster;" ::: "memory");
    }
    __syncwarp();
    e_expect(BAR(B_XFULL), 16384);
    tma2d(sb + SM_K, &tm_x, 0, ai * 128, BAR(B_XFULL));
    e_expect(BAR(B_XFULL + 1), 16384);
    tma2d(sb + SM_K + 16384, &tm_x, 64, ai * 128, BAR(B_XFULL + 1));
    if (lane == 0) TS(36);
  } else if (warp == 18) {
    if (lane == 0) { mbar_init(BAR(B_WFULL), 1); asm volatile("fence.mbarrier_init.release.cluster;" ::: "memory"); }
    __syncwarp();
    e_expect(BAR(B_WFULL), 16384);
#pragma unroll
    for (int h = 0; h < 2; h++) {
      tma3d(sb + SM_RING + h * 8192, &tm_win, 0, h * 32, aj < 6 ? 21 + 3 * aj : 27 + 2 * aj, BAR(B_WFULL));
      tma2d(sb + SM_RING + h * 8192 + 6144, &tm_wq, 64 * aj, h * 32, BAR(B_WFULL));
    }
  } else if (warp == 19) {
    l2_prefetch(reinterpret_cast<const uint8_t*>(prm.w_in) + blockIdx.x * 11008, 11008);
    l2_prefetch(reinterpret_cast<const uint8_t*>(prm.wq) + blockIdx.x * 4096, 4096);
  } else if (warp < 16 && lane == 0) {
#pragma unroll
    for (int r = 0; r < 4; r++) {
      const int k = warp + 16 * r;
      uint32_t cnt = 1;
      if (k >= B_XEMPTY && k < B_XEMPTY + 8) cnt = 4;
      if (k >= B_WEMPTY && k < B_WEMPTY + 11) cnt = 4;
      if (k == B_ZST0 || k == B_ZST1) cnt = 8;
      if (k >= B_REMPTY && k < B_REMPTY + 3) cnt = 2;
      if (k == B_ATT) cnt = 6;
      if (k == B_QRDY) cnt = 16;
      if (k == B_KSTAT) cnt = 17;
      if (k == B_LNOK) cnt = 8;
      if (k >= 2 && k != B_WFULL) mbar_init(BAR(k), cnt);
    }
    asm volatile("fence.mbarrier_init.release.cluster;" ::: "memory");
  }
  __syncthreads();
  if (threadIdx.x == 0) TS(35);
  asm volatile("barrier.cluster.arrive.relaxed.aligned;" ::: "memory");
  asm volatile("barrier.cluster.wait.acquire.aligned;" ::: "memory");

  if (wg == 4) {
    asm volatile("setmaxnreg.dec.sync.aligned.u32 24;");
    if (warp == 18) {
#pragma unroll 1
      for (int f = 1; f < 16; f++) {
        if (f == 1 && lane == 0) TS(0);
        if (f == 5 && lane == 0) TS(37);
        if (f >= 5) mbar_wait(BAR(B_WEMPTY + f - 5), 0);
        const uint32_t dst = sb + wslot(f) + rank * 8192, bar = BAR(B_WFULL + f);
        const int k0 = (f & 7) * 64 + rank * 32;
        e_expect(bar, 16384);
        tma3d_mc(dst, &tm_win, 0, k0, f < 8 ? (aj < 6 ? 21 + 3 * aj : 27 + 2 * aj) : (aj < 2 ? 2 * aj : 3 * aj - 2), bar);
        tma2d_mc(dst + 6144, &tm_wq, 64 * aj + (f >> 3) * 32, k0, bar);
        if (f < 7) {
          e_expect(BAR(B_XFULL + 1 + f), 16384);
          tma2d(sb + SM_K + (f + 1) * 16384, &tm_x, (f + 1) * 64, ai * 128, BAR(B_XFULL + 1 + f));
        }
      }
      if (lane == 0) TS(1);
      mbar_wait(BAR(B_ZST1), 0);
      if (lane == 0) { red_release(&g_z1cnt[ai * 32]); TS(17); }
    } else if (warp == 19) {
      mbar_wait(BAR(B_ZST0), 0);
      if (lane == 0) { red_release(&g_zcnt[ai * 32]); TS(20); }
      __syncwarp();
      const unsigned ep1 = lds32(sb + SM_MISC + 4 * M_EPOCH) + 1;
      wait_ge(&g_zcnt[(lane & 15) * 32], ep1 * 8);
      __syncwarp();
      e_arrive(BAR(B_ZOK));
      wait_ge(&g_z1cnt[bi * 32], ep1 * 8);
      e_arrive(BAR(B_Z1OK));
    } else if (warp == 16) {
      tm_prefetch(&tm_wsp);
      tm_prefetch(&tm_wout);
      tm_prefetch(&tm_wo);
      tm_prefetch(&tm_out);
      const int row = bi * 128 + rank * 64;
      mbar_wait(BAR(B_XEMPTY), 0);
      tma2d_pf(&tm_wsp, (bj >> 1) * 64, row);
      tma2d_pf(&tm_wsp, (bj >> 1) * 64 + 256, row);
      mbar_wait(BAR(B_XEMPTY + 7), 0);
      mbar_wait(BAR(B_ZOK), 0);
      const unsigned ep1 = lds32(sb + SM_MISC + 4 * M_EPOCH) + 1;
      fence_async();
      if (lane == 0) TS(2);
      int st = 0, ph = 1;
#pragma unroll 1
      for (int n = 0; n < 47; n++) {
        const uint32_t stg = sb + SM_RING + st * RSTAGE, bar = BAR(B_RFULL + st);
        if (n >= 3) mbar_wait(BAR(B_REMPTY + st), ph);
        if (n < 32) {
          e_expect(bar, 16384 + 11264);
          tma2d_mc(stg + rank * 8192, &tm_wsp, n * 64, row, bar);
          bulk(stg + 16384, reinterpret_cast<const uint8_t*>(g_z2n) + (bj * 32 + n) * 11264, 11264, bar);
          if ((n & 3) == (bj >> 1) && n < 24) tma2d_pf(&tm_wsp, (n + 8) * 64, row);
          if (n == 16) {
            l2_prefetch(reinterpret_cast<const uint8_t*>(prm.w_out) + blockIdx.x * 5504, 5504);
            l2_prefetch(reinterpret_cast<const uint8_t*>(prm.wo) + blockIdx.x * 4096, 4096);
          }
        } else if (n == 32) {
          mbar_wait(BAR(B_Z1OK), 0);
          fence_async();
          e_expect(bar, 22528 + 512 + 256);
          bulk(stg, g_z1 + (bi * 88 + bj * 11) * 128, 22528, bar);
          bulk(stg + 22528, g_gate + bi * 128, 512, bar);
          bulk(stg + 23040, prm.b_sp + bi * 128, 256, bar);
        } else if (n < 44) {
          const int c = n - 33;
          e_expect(bar, 16384 + 8192);
          tma2d(stg + 16384, &tm_wout, 64 * bj, c * 64, bar);
          if (c == 0) { wait_ge(&g_ucnt[bi * 32], ep1 * 8); fence_async(); if (lane == 0) TS(3); }
          bulk_mc(stg + rank * 8192, reinterpret_cast<const uint8_t*>(g_u) + (bi * 11 + c) * 16384 + rank * 8192, 8192, bar);
        }
        if (++st == 3) { st = 0; ph ^= 1; }
      }
      e_expect(BAR(B_WOFULL), 65536);
#pragma unroll 1
      for (int c = 0; c < 8; c++) tma2d(sb + SM_RING + c * 8192, &tm_wo, 64 * bj, c * 64, BAR(B_WOFULL));
      if (lane == 0) TS(4);
#pragma unroll 1
      for (int c = 0; c < 8; c++) e_expect(BAR(B_XFULL + c), 16384);
      mbar_wait(BAR(B_ATT), 0);
#pragma unroll 1
      for (int n = 0; n < SPIN_LIMIT; n++) if ((int)(ld_acquire(&g_ocnt[bi * 32]) - ep1 * 24) >= 0) break;
      fence_async();
      if (lane == 0) TS(5);
#pragma unroll 1
      for (int c = 0; c < 8; c++)
        bulk_mc(sb + SM_K + c * 16384 + rank * 8192, reinterpret_cast<const uint8_t*>(g_o) + (bi * 8 + c) * 16384 + rank * 8192, 8192, BAR(B_XFULL + c));
    } else {
      if (lane == 0) {
        sts32(sb + SM_MISC + 4 * M_EPOCH, atomicAdd(&g_ticket, 1u) / NCTA);
        mbar_arrive(BAR(B_EPOCH));
        TS(71);
      }
      __syncwarp();
      const unsigned ep1 = lds32(sb + SM_MISC + 4 * M_EPOCH) + 1;
      e_expect(BAR(B_KVFULL), 49152);
      e_expect(BAR(B_KVB), 49152);
      e_expect(BAR(B_KVC), 32768);
      mbar_wait(BAR(B_WFULL + 8), 0);
      uint32_t kn = 0, vb = 0;
#pragma unroll 1
      for (int n = 0; n < SPIN_LIMIT; n++) {
        unsigned long long a, b, c, d;
        asm volatile("ld.relaxed.gpu.global.v2.b64 {%0, %1}, [%2];" : "=l"(a), "=l"(b) : "l"(&g_kvflag[2 * lane]) : "memory");
        asm volatile("ld.relaxed.gpu.global.v2.b64 {%0, %1}, [%2];" : "=l"(c), "=l"(d) : "l"(&g_kvflag[64 + 2 * lane]) : "memory");
        kn = max((uint32_t)a, (uint32_t)c); vb = (uint32_t)b | (uint32_t)d;
        if (__all_sync(0xffffffffu, (uint32_t)(a >> 32) == ep1 && (uint32_t)(b >> 32) == ep1 && (uint32_t)(c >> 32) == ep1 && (uint32_t)(d >> 32) == ep1)) break;
        __nanosleep(100);
      }
      asm volatile("fence.acquire.gpu;" ::: "memory");
      kn = __reduce_max_sync(0xffffffffu, kn);
      vb = __reduce_or_sync(0xffffffffu, vb);
      if (lane == 0) {
        TS(6);
        sts32(sb + SM_MISC + 4 * M_KN2, kn);
        sts32(sb + SM_MISC + 4 * M_VOK, vb == 0xFFFFu ? 1u : 0u);
        mbar_arrive(BAR(B_KSTAT));
      }
      __syncwarp();
      fence_async();
      mbar_wait(BAR(B_LNOK), 0);
#pragma unroll 1
      for (int c = 0; c < 8; c++) {
        const uint32_t off = c * 16384 + rank * 8192;
        mbar_wait(BAR(B_XEMPTY + c), 0);
        bulk_mc(sb + SM_K + off, reinterpret_cast<const uint8_t*>(g_kimg) + off, 8192, BAR(c < 3 ? B_KVFULL : (c < 6 ? B_KVB : B_KVC)));
      }
      if (lane == 0) TS(7);
      mbar_wait(BAR(B_DEC), 0);
      if (!lds32(sb + SM_MISC + 4 * M_FAST)) {
        mbar_wait(BAR(B_KVFULL), 0); mbar_wait(BAR(B_KVB), 0); mbar_wait(BAR(B_KVC), 0);
        e_expect(BAR(B_KFB), 65536);
#pragma unroll 1
        for (int j = 0; j < 32; j++) bulk(sb + SM_K + j * 4096, g_kbf + j * 128, 2048, BAR(B_KFB));
      }
    }
  } else {
    asm volatile("setmaxnreg.inc.sync.aligned.u32 112;");
    const int w = tid >> 5, g = lane >> 2, t4 = lane & 3, half = wg & 1;
    {
      float acc[64];
      if (wg == 2) {
        const int slot = ai * 4 + (aj >> 1), isv = aj & 1;
        const uint4* wsrc = reinterpret_cast<const uint4*>(isv ? prm.wv : prm.wk) + tid;
        uint4 wr[8];
#pragma unroll
        for (int r = 0; r < 8; r++) wr[r] = __ldg(wsrc + 128 * r);
#pragma unroll
        for (int r = 0; r < 8; r++) sts128(sb + SM_WKV + r * 2048 + (tid >> 1) * 32 + (((tid ^ (tid >> 3)) & 1) << 4), wr[r].x, wr[r].y, wr[r].z, wr[r].w);
        fence_async_smem();
        bar_sync(3, 128);
        float kv[16];
#pragma unroll
        for (int k = 0; k < 16; k++) kv[k] = 0.f;
        regfence(kv);
#pragma unroll 1
        for (int c = 0; c < 8; c++) {
          mbar_wait(BAR(B_XFULL + c), 0);
          const uint64_t da = mkdesc(sb + SM_WKV + c * 2048, 0, 256, 3);
          const uint64_t db = mkdesc(sb + SM_K + c * 16384 + (aj >> 1) * 4096, 16, 1024, 1);
          wg_fence();
#pragma unroll
          for (int k = 0; k < 4; k++) wg_ss_n32t<0, 16>(kv, da + 32 * k, db + 2 * k);
          wg_commit();
        }
        wg_wait<0>();
        regfence(kv);
        if (tid == 0) TS(22);
        const uint32_t sT = sb + SM_WKV, sH = sb + SM_WKV + 4096;
        bar_sync(3, 128);
        {
          const float a = w & 1 ? kv[4] : kv[0], b = w & 1 ? kv[5] : kv[1], c = w & 1 ? kv[6] : kv[2], d = w & 1 ? kv[7] : kv[3];
          const float e = w & 1 ? kv[12] : kv[8], f = w & 1 ? kv[13] : kv[9], h = w & 1 ? kv[14] : kv[10], i = w & 1 ? kv[15] : kv[11];
          const uint32_t lo = pack_bf16(w & 2 ? e : a, w & 2 ? f : b), hi = pack_bf16(w & 2 ? h : c, w & 2 ? i : d);
          const uint32_t p = sT + ((w * 8 + 2 * t4) * 17 + g) * 4;
          sts32(p, lo << 16); sts32(p + 68, lo & 0xFFFF0000u); sts32(p + 32, hi << 16); sts32(p + 100, hi & 0xFFFF0000u);
        }
        bar_sync(3, 128);
        if (tid == 0) TS(64);
        const int tok = (tid & 63) >> 1, hf = tid & 1;
        float f[8];
#pragma unroll
        for (int e = 0; e < 8; e++) f[e] = ldsf(sT + (tok * 17 + hf * 8 + e) * 4);
        uint4 val = make_uint4(pack_bf16(f[0], f[1]), pack_bf16(f[2], f[3]), pack_bf16(f[4], f[5]), pack_bf16(f[6], f[7]));
        uint32_t stat = 0;
        if (isv) {
#pragma unroll
          for (int e = 0; e < 8; e++) {
            if (fabsf(f[e]) >= 9.5367431640625e-07f) stat |= 1u << e;
            if (!(fabsf(f[e]) <= 1073741824.f)) stat |= 1u << (16 - 8 * hf);
          }
          stat = __reduce_or_sync(0xffffffffu, stat << (8 * hf));
        } else {
          float n2 = 0.f;
#pragma unroll
          for (int e = 0; e < 8; e++) n2 = fmaf(f[e], f[e], n2);
          n2 += __shfl_xor_sync(0xffffffffu, n2, 1);
          if (!(n2 <= 3.0e38f)) n2 = 3.0e38f;
          stat = __reduce_max_sync(0xffffffffu, __float_as_uint(n2));
          if (tid < 48) {
            const int d = tid & 15, sg = tid >> 4, j0 = sg == 0 ? 0 : (sg == 1 ? 10 : 22), j1 = sg == 0 ? 10 : (sg == 1 ? 22 : 32);
            const float sc = slot < NP ? 16.f : 0.125f, fb = slot < NP ? 1.f : 0.f;
            float kx[12], run = 0.f;
#pragma unroll
            for (int e = 0; e < 12; e++) kx[e] = ldsf(sT + (min(j0 + e, 31) * 17 + d) * 4);
#pragma unroll
            for (int e = 0; e < 12; e++) {
              const __half hv = __float2half_rn(fmaf(kx[e], sc, -run));
              run = fmaf(__half2float(hv), fb, run);
              if (j0 + e < j1) sts16(sH + ((j0 + e) * 16 + d) * 2, __half_as_ushort(hv));
            }
          }
        }
        if (lane == 0) sts32(sb + SM_MISC + 4 * (M_KVR + w), stat);
        bar_sync(3, 128);
        const uint32_t off = slot * 2 + (hf ^ ((slot >> 2) & 1));
        uint4* dst = tid < 64 ? g_kimg + tok * 256 + isv * 128 + off : g_kbf + tok * 128 + off;
        if (!isv && tid < 64) val = lds128(sH + tok * 32 + hf * 16);
        uint32_t chk = 0;
        if (tid < 64 || !isv) { *dst = val; chk = ld_back(dst); }
        mbar_wait(BAR(B_EPOCH), 0);
        consume(chk, sb);
        fence_async();
        bar_sync(3, 128);
        if (tid == 0) {
          const uint32_t s0 = lds32(sb + SM_MISC + 4 * M_KVR), s1 = lds32(sb + SM_MISC + 4 * (M_KVR + 1));
          const unsigned long long fl = ((unsigned long long)(lds32(sb + SM_MISC + 4 * M_EPOCH) + 1) << 32) | (isv ? (s0 | s1) : max(s0, s1));
          asm volatile("st.relaxed.gpu.global.b64 [%0], %1;" ::"l"(&g_kvflag[ai * 8 + aj]), "l"(fl) : "memory");
          TS(23);
        }
      } else if (wg == 3) {
        if (tid < 64) { const uint4 gv = __ldg(reinterpret_cast<const uint4*>(prm.gate_w) + tid); sts128(sb + SM_GW + tid * 16, gv.x, gv.y, gv.z, gv.w); }
        sts32(sb + SM_ONES + tid * 4, 0x3F803F80u);
        fence_async_smem();
        bar_sync(4, 128);
        float ga[8];
#pragma unroll
        for (int k = 0; k < 8; k++) ga[k] = 0.f;
        regfence(ga);
#pragma unroll 1
        for (int c = 0; c < 8; c++) {
          mbar_wait(BAR(B_XFULL + c), 0);
          if (tid == 0) TS(40 + c);
          const uint64_t da = mkdesc(sb + SM_K + c * 16384, 16, 1024, 1), db = mkdesc(sb + SM_GW + c * 128, 16, 128, 0);
          wg_fence();
#pragma unroll
          for (int k = 0; k < 4; k++) { wg_ss_n8<0, 8>(ga, da + 2 * k, db + 2 * k); wg_ss_n8<4, 8>(ga, da + 512 + 2 * k, db + 2 * k); }
          wg_commit();
        }
        wg_wait<0>();
        regfence(ga);
        const float g0 = __shfl_sync(0xffffffffu, ga[0], lane & 28), g1 = __shfl_sync(0xffffffffu, ga[2], lane & 28);
        const float g2 = __shfl_sync(0xffffffffu, ga[4], lane & 28), g3 = __shfl_sync(0xffffffffu, ga[6], lane & 28);
        const float gs = t4 & 2 ? (t4 & 1 ? g3 : g2) : (t4 & 1 ? g1 : g0);
        sts32(sb + SM_G + ((t4 >> 1) * 64 + w * 16 + (t4 & 1) * 8 + g) * 4, __float_as_uint(__fdividef(1.f, 1.f + __expf(-gs))));
        bar_sync(4, 128);
        if (aj == 0) g_gate[ai * 128 + tid] = ldsf(sb + SM_G + tid * 4);
        if (tid == 0) TS(8);
      }
#pragma unroll
      for (int k = 0; k < 64; k++) acc[k] = 0.f;
      regfence(acc);
      const int pass = wg >> 1;
#pragma unroll 1
      for (int c = 0; c < 8; c++) {
        mbar_wait(BAR(B_XFULL + c), 0);
        mbar_wait(BAR(B_WFULL + pass * 8 + c), 0);
        if (tid == 0 && half == pass) TS(48 + pass * 8 + c);
        const uint64_t da = mkdesc(sb + SM_K + c * 16384 + half * 8192, 16, 1024, 1);
        const uint64_t db = mkdesc(sb + wslot(pass * 8 + c), 2048, 512, 2);
        wg_fence();
#pragma unroll
        for (int k = 0; k < 4; k++) wg_ss_n128<0, 64>(acc, da + 2 * k, db + (k & 1) * 64 + (k >> 1) * 512);
        wg_commit();
        wg_wait<1>();
        if (tid == 0 && c > 0) {
          if (pass * 8 + c < 12) mbar_arrive_both(BAR(B_WEMPTY + pass * 8 + c - 1));
          if (pass) mbar_arrive_both(BAR(B_XEMPTY + c - 1));
        }
      }
      wg_wait<0>();
      if (tid == 0) mbar_arrive_both(BAR(pass ? B_XEMPTY + 7 : B_WEMPTY + 7));
      regfence(acc);
      if (tid == 0) TS(wg == 0 ? 16 : (wg == 2 ? 24 : (wg == 3 ? 9 : 95)));
      uint32_t qb[8];
      {
        float n2 = 0.f;
#pragma unroll
        for (int k = 0; k < 8; k++) qb[k] = pack_bf16(acc[48 + 2 * k], acc[49 + 2 * k]);
#pragma unroll
        for (int k = 0; k < 4; k++) {
          const uint32_t a = qb[4 * (k >> 1) + (k & 1)], b = qb[4 * (k >> 1) + (k & 1) + 2];
          float s = bf_lo(a) * bf_lo(a);
          s = fmaf(bf_hi(a), bf_hi(a), s); s = fmaf(bf_lo(b), bf_lo(b), s); s = fmaf(bf_hi(b), bf_hi(b), s);
          s += __shfl_xor_sync(0xffffffffu, s, 1); s += __shfl_xor_sync(0xffffffffu, s, 2);
          if (!(s <= 3.0e38f)) s = 3.0e38f;
          n2 = fmaxf(n2, s);
        }
        const uint32_t nmax = __reduce_max_sync(0xffffffffu, __float_as_uint(n2));
        if (lane == 0) { sts32(sb + SM_MISC + 4 * (M_RED + warp), nmax); mbar_arrive(BAR(B_KSTAT)); }
      }
      auto finish_q = [&]() {
        mbar_wait(BAR(B_KSTAT), 0);
        const float qn2 = __uint_as_float(__reduce_max_sync(0xffffffffu, lds32(sb + SM_MISC + 4 * (M_RED + (lane & 15)))));
        const float kn2 = ldsf(sb + SM_MISC + 4 * M_KN2);
        constexpr float SC = QSCALE * 0.125f;
        const bool fast = lds32(sb + SM_MISC + 4 * M_VOK) && qn2 <= 4.0e8f && kn2 <= 4.0e6f && qn2 * kn2 * (SC * SC) <= BOUND * BOUND;
        if (fast) {
#pragma unroll
          for (int k = 0; k < 8; k++) qb[k] = pack_f16(bf_lo(qb[k]) * QSCALE, bf_hi(qb[k]) * QSCALE);
        }
        sts128(sb + SM_Q + wg * 2048 + pass * 4096 + tid * 16, qb[0], qb[1], qb[2], qb[3]);
        sts128(sb + SM_Q + wg * 2048 + pass * 4096 + 4096 + tid * 16, qb[4], qb[5], qb[6], qb[7]);
        if (threadIdx.x == 256) { sts32(sb + SM_MISC + 4 * M_FAST, fast ? 1u : 0u); mbar_arrive(BAR(B_DEC)); }
        __syncwarp();
        if (lane == 0) mbar_arrive(BAR(B_QRDY));
        if (tid == 0 && pass) TS(75 + wg);
      };
      if (pass) finish_q();
#pragma unroll
      for (int k = 0; k < 48; k++) acc[k] = gelu2_tanh(acc[k]);
      int fb0, c_lo = 0, c_hi = 12;
      if (wg < 2) { fb0 = aj < 6 ? 12 * aj - 2 : 22 + 8 * aj; if (aj == 0) c_lo = 2; if (aj >= 6) c_hi = 8; }
      else { fb0 = aj < 2 ? 8 * aj : 12 * aj - 8; if (aj < 2) c_hi = 8; if (aj == 7) c_hi = 10; }
      if (wg < 2) {
        float s1[2][3], s2[2][3];
#pragma unroll
        for (int k = 0; k < 48; k++) {
          const int r = (k >> 1) & 1, gq = k < 8 ? 0 : (k < 32 ? 1 : 2);
          if (k - 2 * r == (gq == 0 ? 0 : (gq == 1 ? 8 : 32))) { s1[r][gq] = acc[k]; s2[r][gq] = acc[k] * acc[k]; }
          else { s1[r][gq] += acc[k]; s2[r][gq] = fmaf(acc[k], acc[k], s2[r][gq]); }
        }
        const float inv_n = __fdividef(0.125f, (float)(c_hi - c_lo));
        float mm[2], vv[2];
#pragma unroll
        for (int r = 0; r < 2; r++) {
          float a = s1[r][1], b = s2[r][1];
          if (c_lo == 0) { a += s1[r][0]; b += s2[r][0]; }
          if (c_hi == 12) { a += s1[r][2]; b += s2[r][2]; }
          a += __shfl_xor_sync(0xffffffffu, a, 1); b += __shfl_xor_sync(0xffffffffu, b, 1);
          a += __shfl_xor_sync(0xffffffffu, a, 2); b += __shfl_xor_sync(0xffffffffu, b, 2);
          mm[r] = a * inv_n;
          vv[r] = fmaxf(fmaf(-a, mm[r], b), 0.f);
        }
        const int r0 = half * 64 + w * 16 + g;
        mbar_wait(BAR(B_EPOCH), 0);
        const unsigned ep1 = lds32(sb + SM_MISC + 4 * M_EPOCH) + 1;
        if (threadIdx.x == 0) TS(67);
        if (t4 < 2) {
          const float m = t4 ? mm[1] : mm[0], v = t4 ? vv[1] : vv[0];
          asm volatile("st.relaxed.gpu.global.v2.b64 [%0], {%1, %2};" ::"l"(&g_lnstat[(ai * 8 + aj) * 128 + r0 + 8 * t4]),
                       "l"(((unsigned long long)ep1 << 32) | __float_as_uint(m)), "l"(((unsigned long long)ep1 << 32) | __float_as_uint(v)) : "memory");
        }
        float sm[4], sv[4];
        const uint4* lp = &g_lnstat[(ai * 8 + 2 * t4) * 128 + r0];
#pragma unroll 1
        for (int n = 0; n < SPIN_LIMIT; n++) {
          uint32_t tg = ep1;
          if (lane < 8) tg = ld_back(reinterpret_cast<const uint32_t*>(&g_lnstat[(ai * 8 + lane) * 128 + half * 64 + w * 16 + 15]) + 3);
          if (__all_sync(0xffffffffu, tg == ep1)) break;
        }
#pragma unroll 1
        for (int n = 0; n < SPIN_LIMIT; n++) {
          bool ok = true;
#pragma unroll
          for (int e = 0; e < 4; e++) {
            unsigned long long a, b;
            asm volatile("ld.relaxed.gpu.global.v2.b64 {%0, %1}, [%2];" : "=l"(a), "=l"(b) : "l"(lp + (e >> 1) * 128 + (e & 1) * 8) : "memory");
            ok = ok && (uint32_t)(a >> 32) == ep1 && (uint32_t)(b >> 32) == ep1;
            sm[e] = __uint_as_float((uint32_t)a); sv[e] = __uint_as_float((uint32_t)b);
          }
          if (__all_sync(0xffffffffu, ok)) break;
        }
        if (lane == 0) mbar_arrive(BAR(B_LNOK));
        if (threadIdx.x == 0) TS(68);
        const float na = t4 == 0 ? 80.f : (t4 == 3 ? 64.f : 96.f), nb = t4 == 3 ? 64.f : 96.f;
#pragma unroll
        for (int r = 0; r < 2; r++) {
          float t = fmaf(sm[r], na, sm[2 + r] * nb);
          t += __shfl_xor_sync(0xffffffffu, t, 1); t += __shfl_xor_sync(0xffffffffu, t, 2);
          const float mu = t * (1.f / 688.f);
          const float da = sm[r] - mu, db = sm[2 + r] - mu;
          float m2 = sv[r] + sv[2 + r] + na * da * da + nb * db * db;
          m2 += __shfl_xor_sync(0xffffffffu, m2, 1); m2 += __shfl_xor_sync(0xffffffffu, m2, 2);
          const float rs = rsqrtf(fmaf(m2, 1.f / 688.f, 4e-5f)), sh = -mu * rs;
#pragma unroll
          for (int k = 2 * r; k < 48; k += 4) { acc[k] = fmaf(acc[k], rs, sh); acc[k + 1] = fmaf(acc[k + 1], rs, sh); }
        }
        if (aj == 7) {
          c_hi = 10;
#pragma unroll
          for (int k = 32; k < 40; k++) acc[k] = 0.f;
        }
      }
      uint32_t* zp = wg < 2 ? reinterpret_cast<uint32_t*>(g_z2n) + (ai * 2 + half) * 2816 + w * 704
                            : reinterpret_cast<uint32_t*>(g_z1) + (ai * 88 * 16 + half * 8 + w * 2) * 32;
      const int mul = wg < 2 ? 373 : 0, cstr = wg < 2 ? 32 : 512, rstr = wg < 2 ? 352 : 32;
      auto zoff = [&](int c8) { const int fb = fb0 + c8; return ((fb * mul) >> 12) * (32 * 2816 - 352) + fb * cstr; };
#pragma unroll
      for (int c8 = 0; c8 < 12; c8++) {
        uint32_t* p = zp + zoff(c8) + lane;
        if (c8 >= c_lo && c8 < c_hi) { p[0] = pack_bf16(acc[4 * c8], acc[4 * c8 + 1]); p[rstr] = pack_bf16(acc[4 * c8 + 2], acc[4 * c8 + 3]); }
      }
      if (tid == 0) TS(wg == 0 ? 69 : 78 + wg);
      fence_async();
      __syncwarp();
      if (lane == 0) mbar_arrive(BAR(pass ? B_ZST1 : B_ZST0));
      if (!pass) finish_q();
    }
    if (wg == 3) {
      asm volatile("setmaxnreg.inc.sync.aligned.u32 120;");
      int st = 0, ph = 0;
      {
        float acc[88];
#pragma unroll
        for (int k = 0; k < 88; k++) acc[k] = 0.f;
        regfence(acc);
#pragma unroll 1
        for (int n = 0; n < 32; n++) {
          mbar_wait(BAR(B_RFULL + st), ph);
          const uint64_t da = mkdesc(sb + SM_RING + st * RSTAGE, 16, 1024, 1);
          const uint64_t db = mkdesc(sb + SM_RING + st * RSTAGE + 16384, 1408, 128, 0);
#pragma unroll
          for (int k = 0; k < 4; k++) {
            if (k % SBATCH == 0) wg_fence();
            wg_ss_n88<0, 88>(acc, da + 2 * k, db + 176 * k);
            wg_ss_n88<44, 88>(acc, da + 512 + 2 * k, db + 176 * k);
            if (k % SBATCH == SBATCH - 1) { wg_commit(); wg_wait<0>(); }
          }
          if (tid == 0) mbar_arrive_both(BAR(B_REMPTY + st));
          if (++st == 3) { st = 0; ph ^= 1; }
        }
        regfence(acc);
        if (tid == 0) TS(11);
        mbar_wait(BAR(B_RFULL + st), ph);
        const uint8_t* zs = smem_raw + SM_RING + st * RSTAGE;
        uint32_t* up = reinterpret_cast<uint32_t*>(g_u) + bi * 11 * 4096 + w * 512 + lane;
#pragma unroll
        for (int r = 0; r < 4; r++) {
          const int row = (r >> 1) * 64 + w * 16 + (r & 1) * 8 + g;
          const float og = fmaf(reinterpret_cast<const float*>(zs + 22528)[row], -0.5f, 0.5f);
          const float bs = __bfloat162float(reinterpret_cast<const __nv_bfloat16*>(zs + 23040)[row]) * og;
#pragma unroll
          for (int c8 = 0; c8 < 11; c8++) {
            const int k = (r >> 1) * 44 + c8 * 4 + (r & 1) * 2, cb = 11 * bj + c8;
            uint32_t zz = reinterpret_cast<const uint32_t*>(zs)[c8 * 512 + ((r >> 1) * 8 + w * 2 + (r & 1)) * 32 + lane];
            if (c8 >= 9 && bj == 7) zz = 0;
            uint32_t v = pack_bf16(fmaf(acc[k], og, bs), fmaf(acc[k + 1], og, bs));
            asm("mul.rn.bf16x2 %0, %0, %1;" : "+r"(v) : "r"(zz));
            up[cb * 32 + (cb >> 3) * 3840 + ((r >> 1) * 8 + (r & 1)) * 256] = v;
          }
        }
        fence_async_smem();
        fence_async();
        bar_sync(4, 128);
        if (tid == 0) { mbar_arrive_both(BAR(B_REMPTY + st)); red_release(&g_ucnt[bi * 32]); TS(12); }
        if (++st == 3) { st = 0; ph ^= 1; }
      }
      float oc[64];
#pragma unroll
      for (int k = 0; k < 64; k++) oc[k] = 0.f;
      regfence(oc);
#pragma unroll 1
      for (int n = 0; n < 19; n++) {
        uint32_t sa, sw;
        if (n < 11) { mbar_wait(BAR(B_RFULL + st), ph); sa = SM_RING + st * RSTAGE; sw = sa + 16384; }
        else {
          if (n == 11) { if (tid == 0) TS(13); mbar_wait(BAR(B_WOFULL), 0); }
          mbar_wait(BAR(B_XFULL + n - 11), 1); sa = SM_K + (n - 11) * 16384; sw = SM_RING + (n - 11) * 8192;
        }
        const uint64_t da = mkdesc(sb + sa, 128, 1024, 0), db = mkdesc(sb + sw, 8192, 1024, 1);
#pragma unroll
        for (int k = 0; k < 4; k += 2) {
          wg_fence();
          wg_ss_n64<0, 64>(oc, da + 16 * k, db + 128 * k);
          wg_ss_n64<32, 64>(oc, da + 512 + 16 * k, db + 128 * k);
          wg_ss_n64<0, 64>(oc, da + 16 * k + 16, db + 128 * k + 128);
          wg_ss_n64<32, 64>(oc, da + 528 + 16 * k, db + 128 * k + 128);
          wg_commit();
          if (n < 11) wg_wait<0>();
        }
        if (n < 11) {
          if (tid == 0) mbar_arrive_both(BAR(B_REMPTY + st));
          if (++st == 3) { st = 0; ph ^= 1; }
        }
      }
      wg_wait<0>();
      regfence(oc);
      if (tid == 0) TS(14);
#pragma unroll
      for (int hf = 0; hf < 2; hf++) {
        const uint32_t rb = sb + SM_Q + (hf * 64 + w * 16) * 128, ra = rb + (lane & 15) * 128;
#pragma unroll
        for (int c = 0; c < 4; c++) {
          const int k = hf * 32 + c * 8;
          asm volatile("stmatrix.sync.aligned.m8n8.x4.shared.b16 [%0], {%1, %2, %3, %4};" ::"r"(ra + (((2 * c + (lane >> 4)) ^ (lane & 7)) << 4)),
                       "r"(pack_bf16(oc[k], oc[k + 1])), "r"(pack_bf16(oc[k + 2], oc[k + 3])), "r"(pack_bf16(oc[k + 4], oc[k + 5])), "r"(pack_bf16(oc[k + 6], oc[k + 7])) : "memory");
        }
        fence_async_smem();
        __syncwarp();
        asm volatile(ELECT "cp.async.bulk.tensor.2d.global.shared::cta.bulk_group [%0, {%2, %3}], [%1];\n}"
                     ::"l"(&tm_out), "r"(rb), "r"(64 * bj), "r"(bi * 128 + hf * 64 + w * 16) : "memory");
      }
      asm volatile("cp.async.bulk.commit_group;" ::: "memory");
      asm volatile("cp.async.bulk.wait_group.read 0;" ::: "memory");
      if (tid == 0) TS(15);
    } else {
      mbar_wait(BAR(B_QRDY), 0);
    if (tid == 0) TS(25 + wg);
    if (tid == 0) TS(28 + wg);
    if (threadIdx.x == 0) GTS(125);
    const uint64_t dk0 = mkdesc(sb + SM_K, 16, 256, 3);
    const uint64_t dv0 = mkdesc(sb + SM_K + 2048, SM_ONES - 2048, 256, 3);
    const int aw = wg == 0 ? 0 : 3 - wg;
    uint32_t chk = 0, pend = 0;
    float o[12], s[32];
    uint32_t q[4], p0[16], p1[16];
    if (lds32(sb + SM_MISC + 4 * M_FAST)) {
      const uint32_t mlo = prm.mlo, mhi = prm.mhi;
      uint64_t dk = dk0, dv = dv0;
#define STEP(PIN, POUT) { wg_fence(); issue_qk(s, q, dk); dk += KSTEP; wg_commit(); issue_pv(o, PIN, dv); dv += VSTEP8; wg_commit(); \
                          wg_wait<1>(); regfence(s); softmax_step(s, POUT, mlo, mhi); wg_wait<0>(); }
#pragma unroll 1
      for (int sg = aw * 8; sg < aw * 8 + 8; sg++) {
        const int tau = sg / 3, seg = sg - tau * 3;
        int n2 = seg == 1 ? 6 : 5;
        mbar_wait(BAR(seg ? B_KVB : B_KVFULL), 0);
        mbar_wait(BAR(seg == 2 ? B_KVC : B_KVFULL), 0);
#pragma unroll
        for (int k = 0; k < NP / 2; k++) s[k] = MAGIC_C;
        if (sg == aw * 8 || seg == 0) {
          const int j0 = seg == 0 ? 0 : (seg == 1 ? 10 : 22);
          dk = dk0 + KSTEP * j0;
          dv = dv0 + VSTEP8 * j0;
          const uint4 qv = lds128(sb + SM_Q + tau * 2048 + tid * 16);
          q[0] = qv.x; q[1] = qv.y; q[2] = qv.z; q[3] = qv.w;
#pragma unroll
          for (int k = 0; k < 12; k++) o[k] = 0.f;
          regfence(o); regfence(s);
          wg_fence(); issue_qk(s, q, dk); dk += KSTEP; wg_commit();
          wg_wait<0>(); regfence(s);
          softmax_step(s, p0, mlo, mhi);
          STEP(p0, p1);
          n2--;
        }
        regfence(s);
#pragma unroll 1
        for (; n2 > 0; n2--) { STEP(p1, p0); STEP(p0, p1); }
        if (sg == aw * 8 + 7 || seg == 2) {
          wg_fence(); issue_pv(o, p1, dv); dv += VSTEP8; wg_commit();
          wg_wait<0>(); regfence(o);
          if (sg == 8 || sg == 17) {
            float4* pp = g_part + (blockIdx.x * 2 + (aw - 1)) * 384 + tid;
            pp[0] = make_float4(o[0], o[1], o[2], o[3]); pp[128] = make_float4(o[4], o[5], o[6], o[7]); pp[256] = make_float4(o[8], o[9], o[10], o[11]);
            __threadfence_block();
            bar_arrive(5 + aw, 256);
          } else {
            if (sg == 7 || sg == 15) {
              bar_sync(6 + aw, 256);
              const float4* pp = g_part + (blockIdx.x * 2 + aw) * 384 + tid;
              const float4 a = pp[0], b = pp[128], c = pp[256];
              o[0] += a.x; o[1] += a.y; o[2] += a.z; o[3] += a.w; o[4] += b.x; o[5] += b.y; o[6] += b.z; o[7] += b.w; o[8] += c.x; o[10] += c.z;
            }
            { chk ^= pend; pend = store_o_tile(o, ai, aj, tau, tid, sb); }
          }
        }
      }
#undef STEP
    } else {
      mbar_wait(BAR(B_KFB), 0);
      constexpr float SC = 0.25f * 1.4426950408889634f;
#pragma unroll 1
      for (int tau = wg * 3; tau < wg * 3 + 3 && tau < 8; tau++) {
        const uint4 qv = lds128(sb + SM_Q + tau * 2048 + tid * 16);
        float m0 = -INFINITY, m1 = -INFINITY;
#pragma unroll
        for (int k = 0; k < 12; k++) o[k] = 0.f;
        uint64_t dv = dv0;
#pragma unroll 1
        for (int j = 0; j < 32; j++) {
          regfence(s);
          wg_fence(); wg_qkb_n64<0, 0, 32>(s, qv.x, qv.y, qv.z, qv.w, dk0 + KSTEP * j); wg_commit();
          wg_wait<0>(); regfence(s);
          float x0 = m0, x1 = m1;
#pragma unroll
          for (int k = 0; k < 32; k++) { s[k] *= SC; if (k & 2) x1 = fmaxf(x1, s[k]); else x0 = fmaxf(x0, s[k]); }
          x0 = fmaxf(x0, __shfl_xor_sync(0xffffffffu, x0, 1)); x0 = fmaxf(x0, __shfl_xor_sync(0xffffffffu, x0, 2));
          x1 = fmaxf(x1, __shfl_xor_sync(0xffffffffu, x1, 1)); x1 = fmaxf(x1, __shfl_xor_sync(0xffffffffu, x1, 2));
          const float c0 = ex2(m0 - x0), c1 = ex2(m1 - x1);
          m0 = x0; m1 = x1;
#pragma unroll
          for (int k = 0; k < 12; k++) o[k] *= (k & 2) ? c1 : c0;
#pragma unroll
          for (int k = 0; k < 16; k++) { const float m = (k & 1) ? m1 : m0; p0[k] = exp_mufu(s[2 * k] - m, s[2 * k + 1] - m); }
          regfence(o);
          wg_fence(); issue_pv(o, p0, dv); dv += VSTEP8; wg_commit();
          wg_wait<0>(); regfence(o);
        }
        { chk ^= pend; pend = store_o_tile(o, ai, aj, tau, tid, sb); }
      }
    }
    consume(chk ^ pend, sb);
    fence_async();
    bar_sync(1 + wg, 128);
    if (tid == 0) { red_relaxed(&g_ocnt[ai * 32]); mbar_arrive_both(BAR(B_ATT)); TS(31 + wg); if (wg == 0) GTS(124); }
    }
  }
  __syncwarp();
  asm volatile("barrier.cluster.arrive.relaxed;" ::: "memory");
  asm volatile("barrier.cluster.wait;" ::: "memory");
}

typedef CUresult (*EncodeFn)(CUtensorMap*, CUtensorMapDataType, cuuint32_t, void*, const cuuint64_t*, const cuuint64_t*,
                             const cuuint32_t*, const cuuint32_t*, CUtensorMapInterleave, CUtensorMapSwizzle,
                             CUtensorMapL2promotion, CUtensorMapFloatOOBfill);

void make_map(EncodeFn enc, CUtensorMap* tm, const void* base, uint64_t cols, uint64_t rows, uint32_t bc, uint32_t br, CUtensorMapSwizzle sw) {
  cuuint64_t gd[2] = {cols, rows};
  cuuint64_t gs[1] = {cols * 2};
  cuuint32_t bd[2] = {bc, br};
  cuuint32_t es[2] = {1, 1};
  enc(tm, CU_TENSOR_MAP_DATA_TYPE_BFLOAT16, 2, const_cast<void*>(base), gd, gs, bd, es, CU_TENSOR_MAP_INTERLEAVE_NONE, sw,
      CU_TENSOR_MAP_L2_PROMOTION_L2_128B, CU_TENSOR_MAP_FLOAT_OOB_FILL_NONE);
}

}

extern "C" void kernel_launch(void* const* d_in, const int* in_sizes, int n_in, void* d_out, int out_size) {
  (void)in_sizes; (void)n_in; (void)out_size;
  static EncodeFn enc = nullptr;
  if (!enc) {
    void* fn = nullptr;
    cudaDriverEntryPointQueryResult qr;
    cudaGetDriverEntryPoint("cuTensorMapEncodeTiled", &fn, cudaEnableDefault, &qr);
    enc = (EncodeFn)fn;
    cudaFuncSetAttribute(fused_kernel, cudaFuncAttributeMaxDynamicSharedMemorySize, SMEM_BYTES);
  }
  CUtensorMap tx, tq, tin, tsp, tout, to, ty;
  make_map(enc, &ty, d_out, 512, 2048, 64, 16, CU_TENSOR_MAP_SWIZZLE_128B);
  make_map(enc, &tx, d_in[0], 512, 2048, 64, 128, CU_TENSOR_MAP_SWIZZLE_128B);
  make_map(enc, &tq, d_in[1], 512, 512, 32, 32, CU_TENSOR_MAP_SWIZZLE_64B);
  make_map(enc, &to, d_in[4], 512, 512, 64, 64, CU_TENSOR_MAP_SWIZZLE_128B);
  {
    cuuint64_t gd[3] = {32, 512, 43};
    cuuint64_t gs[2] = {1376 * 2, 64};
    cuuint32_t bd[3] = {32, 32, 3};
    cuuint32_t es[3] = {1, 1, 1};
    enc(&tin, CU_TENSOR_MAP_DATA_TYPE_BFLOAT16, 3, d_in[6], gd, gs, bd, es, CU_TENSOR_MAP_INTERLEAVE_NONE, CU_TENSOR_MAP_SWIZZLE_64B,
        CU_TENSOR_MAP_L2_PROMOTION_L2_128B, CU_TENSOR_MAP_FLOAT_OOB_FILL_NONE);
  }
  make_map(enc, &tsp, d_in[7], 2048, 2048, 64, 64, CU_TENSOR_MAP_SWIZZLE_128B);
  make_map(enc, &tout, d_in[9], 512, 688, 64, 64, CU_TENSOR_MAP_SWIZZLE_128B);
  Params prm;
  prm.gate_w = (const __nv_bfloat16*)d_in[10];
  prm.b_sp = (const __nv_bfloat16*)d_in[8];
  prm.w_out = (const __nv_bfloat16*)d_in[9];
  prm.wo = (const __nv_bfloat16*)d_in[4];
  prm.w_in = (const __nv_bfloat16*)d_in[6];
  prm.wq = (const __nv_bfloat16*)d_in[1];
  prm.wk = (const __nv_bfloat16*)d_in[2];
  prm.wv = (const __nv_bfloat16*)d_in[3];
  prm.mlo = 0x007F007Fu;
  prm.mhi = 0xFF80FF80u;
  fused_kernel<<<NCTA, NTHREADS, SMEM_BYTES>>>(tx, tq, tin, tsp, tout, to, ty, prm);
}
```

```cpp
#include <cuda_runtime.h>
#include <cuda.h>
#include <cuda_bf16.h>
#include <cuda_fp16.h>
#include <stdint.h>

namespace {

constexpr int NCTA = 128;
constexpr int NTHREADS = 640;
constexpr int NP = 40;
constexpr int SPIN_LIMIT = 1 << 18;
#define SBATCH 1

constexpr uint32_t SM_K = 0;
constexpr uint32_t SM_ONES = 131072;
constexpr uint32_t KV_BYTES = 131072;
constexpr uint32_t SM_BAR = 131584;
constexpr uint32_t SM_RING = 132096;
constexpr uint32_t RSTAGE = 27648;
constexpr uint32_t WSLOT = 16384;
constexpr uint32_t SM_WKV = SM_RING + 4 * WSLOT;
constexpr uint32_t SM_GW = SM_WKV + 16384;
constexpr uint32_t SM_Q = 215040;
constexpr uint32_t SM_G = 231424;
constexpr uint32_t SM_MISC = 231936;
constexpr uint32_t SMEM_BYTES = 232448;

constexpr int B_XFULL = 0, B_XEMPTY = 8, B_WFULL = 16, B_WEMPTY = 32, B_RFULL = 44, B_REMPTY = 47, B_KVFULL = 50,
              B_KFB = 51, B_KSTAT = 52, B_DEC = 53, B_ZST0 = 43, B_ZST1 = 63, B_WOFULL = 54, B_EPOCH = 55, B_ZOK = 56, B_Z1OK = 57, B_ATT = 58, B_QRDY = 59, B_LNOK = 60, B_KVB = 61, B_KVC = 62;
constexpr int M_EPOCH = 0, M_KN2 = 1, M_VOK = 2, M_FAST = 3, M_KVR = 4, M_RED = 16;

__device__ uint4 g_kimg[KV_BYTES / 16];
__device__ uint4 g_kbf[65536 / 16];
__device__ unsigned long long g_kvflag[NCTA];
__device__ uint4 g_lnstat[16 * 8 * 128];
__device__ float g_gate[2048];
__device__ uint4 g_z2n[8 * 32 * 11264 / 16];
__device__ uint4 g_z1[16 * 88 * 128];
__device__ uint4 g_u[16 * 11 * 1024];
__device__ uint4 g_o[16 * 8 * 1024];
__device__ float4 g_part[NCTA * 2 * 3 * 128];
__device__ unsigned g_ticket;
__device__ unsigned g_zcnt[16 * 32];
__device__ unsigned g_z1cnt[16 * 32];
__device__ unsigned g_ucnt[16 * 32];
__device__ unsigned g_ocnt[16 * 32];
#define TS(k) do { } while (0)
#define GTS(k) do { } while (0)

__device__ __forceinline__ void mbar_init(uint32_t a, uint32_t c) { asm volatile("mbarrier.init.shared::cta.b64 [%0], %1;" ::"r"(a), "r"(c) : "memory"); }
__device__ __forceinline__ void mbar_arrive(uint32_t a) { asm volatile("mbarrier.arrive.shared::cta.b64 _, [%0];" ::"r"(a) : "memory"); }
__device__ __forceinline__ void mbar_arrive_both(uint32_t a) {
  asm volatile("{\n.reg .b32 ra;\nmapa.shared::cluster.u32 ra, %0, 0;\nmbarrier.arrive.shared::cluster.b64 _, [ra];\n"
               "mapa.shared::cluster.u32 ra, %0, 1;\nmbarrier.arrive.shared::cluster.b64 _, [ra];\n}" ::"r"(a) : "memory");
}
__device__ __forceinline__ void mbar_wait(uint32_t a, uint32_t ph) {
  uint32_t ok;
#pragma unroll 1
  for (int n = 0; n < SPIN_LIMIT; n++) {
    asm volatile("{\n.reg .pred p;\nmbarrier.try_wait.parity.shared::cta.b64 p, [%1], %2;\nselp.u32 %0, 1, 0, p;\n}" : "=r"(ok) : "r"(a), "r"(ph) : "memory");
    if (ok) break;
  }
}
#define ELECT "{\n.reg .pred p;\nelect.sync _|p, 0xffffffff;\n@p "
__device__ __forceinline__ void e_expect(uint32_t a, uint32_t b) { asm volatile(ELECT "mbarrier.arrive.expect_tx.shared::cta.b64 _, [%0], %1;\n}" ::"r"(a), "r"(b) : "memory"); }
__device__ __forceinline__ void e_arrive(uint32_t a) { asm volatile(ELECT "mbarrier.arrive.shared::cta.b64 _, [%0];\n}" ::"r"(a) : "memory"); }
__device__ __forceinline__ void tma2d(uint32_t dst, const CUtensorMap* tm, int c0, int c1, uint32_t bar) {
  asm volatile(ELECT "cp.async.bulk.tensor.2d.shared::cluster.global.mbarrier::complete_tx::bytes [%0], [%1, {%3, %4}], [%2];\n}"
               ::"r"(dst), "l"(tm), "r"(bar), "r"(c0), "r"(c1) : "memory");
}
__device__ __forceinline__ void tma2d_mc(uint32_t dst, const CUtensorMap* tm, int c0, int c1, uint32_t bar) {
  asm volatile(ELECT "cp.async.bulk.tensor.2d.shared::cluster.global.mbarrier::complete_tx::bytes.multicast::cluster [%0], [%1, {%3, %4}], [%2], %5;\n}"
               ::"r"(dst), "l"(tm), "r"(bar), "r"(c0), "r"(c1), "h"((uint16_t)3) : "memory");
}
__device__ __forceinline__ void tma3d(uint32_t dst, const CUtensorMap* tm, int c0, int c1, int c2, uint32_t bar) {
  asm volatile(ELECT "cp.async.bulk.tensor.3d.shared::cluster.global.mbarrier::complete_tx::bytes [%0], [%1, {%3, %4, %5}], [%2];\n}"
               ::"r"(dst), "l"(tm), "r"(bar), "r"(c0), "r"(c1), "r"(c2) : "memory");
}
__device__ __forceinline__ void tma3d_mc(uint32_t dst, const CUtensorMap* tm, int c0, int c1, int c2, uint32_t bar) {
  asm volatile(ELECT "cp.async.bulk.tensor.3d.shared::cluster.global.mbarrier::complete_tx::bytes.multicast::cluster [%0], [%1, {%3, %4, %5}], [%2], %6;\n}"
               ::"r"(dst), "l"(tm), "r"(bar), "r"(c0), "r"(c1), "r"(c2), "h"((uint16_t)3) : "memory");
}
__device__ __forceinline__ void tma2d_pf(const CUtensorMap* tm, int c0, int c1) {
  asm volatile(ELECT "cp.async.bulk.prefetch.tensor.2d.L2.global [%0, {%1, %2}];\n}" ::"l"(tm), "r"(c0), "r"(c1) : "memory");
}
__device__ __forceinline__ void tm_prefetch(const CUtensorMap* tm) { asm volatile(ELECT "prefetch.tensormap [%0];\n}" ::"l"(tm) : "memory"); }
__device__ __forceinline__ void bulk(uint32_t dst, const void* src, uint32_t bytes, uint32_t bar) {
  asm volatile(ELECT "cp.async.bulk.shared::cluster.global.mbarrier::complete_tx::bytes [%0], [%1], %2, [%3];\n}"
               ::"r"(dst), "l"(src), "r"(bytes), "r"(bar) : "memory");
}
__device__ __forceinline__ void bulk_mc(uint32_t dst, const void* src, uint32_t bytes, uint32_t bar) {
  asm volatile(ELECT "cp.async.bulk.shared::cluster.global.mbarrier::complete_tx::bytes.multicast::cluster [%0], [%1], %2, [%3], %4;\n}"
               ::"r"(dst), "l"(src), "r"(bytes), "r"(bar), "h"((uint16_t)3) : "memory");
}
__device__ __forceinline__ void l2_prefetch(const void* src, uint32_t bytes) { asm volatile(ELECT "cp.async.bulk.prefetch.L2.global [%0], %1;\n}" ::"l"(src), "r"(bytes) : "memory"); }
__device__ __forceinline__ void fence_async() { asm volatile("fence.proxy.async.global;" ::: "memory"); }
__device__ __forceinline__ void fence_async_smem() { asm volatile("fence.proxy.async.shared::cta;" ::: "memory"); }
__device__ __forceinline__ void bar_sync(int id, int n) { asm volatile("bar.sync %0, %1;" ::"r"(id), "r"(n) : "memory"); }
__device__ __forceinline__ void bar_arrive(int id, int n) { asm volatile("bar.arrive %0, %1;" ::"r"(id), "r"(n) : "memory"); }
__device__ __forceinline__ void red_release(unsigned* p) { asm volatile("red.release.gpu.global.add.u32 [%0], 1;" ::"l"(p) : "memory"); }
__device__ __forceinline__ void red_relaxed(unsigned* p) { asm volatile("red.relaxed.gpu.global.add.u32 [%0], 1;" ::"l"(p) : "memory"); }
__device__ __forceinline__ uint32_t ld_back(const void* p) { uint32_t v; asm volatile("ld.relaxed.gpu.global.u32 %0, [%1];" : "=r"(v) : "l"(p) : "memory"); return v; }
__device__ __forceinline__ void consume(uint32_t v, uint32_t sb) { if (v == 0xDEADBEEFu) asm volatile("st.shared.u32 [%0], %1;" ::"r"(sb + SM_MISC + 60), "r"(v) : "memory"); }
__device__ __forceinline__ unsigned ld_acquire(const unsigned* p) { unsigned v; asm volatile("ld.acquire.gpu.global.u32 %0, [%1];" : "=r"(v) : "l"(p) : "memory"); return v; }
__device__ __forceinline__ void wait_ge(const unsigned* p, unsigned target) {
#pragma unroll 1
  for (int n = 0; n < SPIN_LIMIT; n++) {
    if ((int)(ld_acquire(p) - target) >= 0) break;
    __nanosleep(100);
  }
}
__device__ __forceinline__ void wg_fence() { asm volatile("wgmma.fence.sync.aligned;" ::: "memory"); }
__device__ __forceinline__ void wg_commit() { asm volatile("wgmma.commit_group.sync.aligned;" ::: "memory"); }
template <int N> __device__ __forceinline__ void wg_wait() { asm volatile("wgmma.wait_group.sync.aligned %0;" ::"n"(N) : "memory"); }
template <int n> __device__ __forceinline__ void regfence(float (&d)[n]) {
#pragma unroll
  for (int i = 0; i < n; i++) asm volatile("" : "+f"(d[i])::"memory");
}
__device__ __forceinline__ uint64_t mkdesc(uint32_t addr, uint32_t lbo, uint32_t sbo, int swz) {
  return (uint64_t)((addr & 0x3FFFF) >> 4) | ((uint64_t)(lbo >> 4) << 16) | ((uint64_t)(sbo >> 4) << 32) | ((uint64_t)swz << 62);
}
__device__ __forceinline__ uint32_t pack_bf16(float lo, float hi) { uint32_t r; asm("cvt.rn.bf16x2.f32 %0, %1, %2;" : "=r"(r) : "f"(hi), "f"(lo)); return r; }
__device__ __forceinline__ uint32_t pack_f16(float lo, float hi) { uint32_t r; asm("cvt.rn.f16x2.f32 %0, %1, %2;" : "=r"(r) : "f"(hi), "f"(lo)); return r; }
__device__ __forceinline__ float bf_lo(uint32_t v) { return __uint_as_float(v << 16); }
__device__ __forceinline__ float bf_hi(uint32_t v) { return __uint_as_float(v & 0xFFFF0000u); }
__device__ __forceinline__ float ex2(float x) { float r; asm("ex2.approx.ftz.f32 %0, %1;" : "=f"(r) : "f"(x)); return r; }
__device__ __forceinline__ float gelu2_tanh(float x) {
  float u = x * fmaf(x * x, 0.0356774081f, 0.7978845608f), t;
  asm("tanh.approx.f32 %0, %1;" : "=f"(t) : "f"(u));
  return fmaf(x, t, x);
}
__device__ __forceinline__ void sts32(uint32_t a, uint32_t v) { asm volatile("st.shared.u32 [%0], %1;" ::"r"(a), "r"(v) : "memory"); }
__device__ __forceinline__ void sts16(uint32_t a, uint16_t v) { asm volatile("st.shared.u16 [%0], %1;" ::"r"(a), "h"(v) : "memory"); }
__device__ __forceinline__ void sts128(uint32_t a, uint32_t x, uint32_t y, uint32_t z, uint32_t w) { asm volatile("st.shared.v4.u32 [%0], {%1,%2,%3,%4};" ::"r"(a), "r"(x), "r"(y), "r"(z), "r"(w) : "memory"); }
__device__ __forceinline__ uint32_t lds32(uint32_t a) { uint32_t v; asm volatile("ld.shared.u32 %0, [%1];" : "=r"(v) : "r"(a) : "memory"); return v; }
__device__ __forceinline__ float ldsf(uint32_t a) { return __uint_as_float(lds32(a)); }
__device__ __forceinline__ uint4 lds128(uint32_t a) { uint4 v; asm volatile("ld.shared.v4.u32 {%0,%1,%2,%3}, [%4];" : "=r"(v.x), "=r"(v.y), "=r"(v.z), "=r"(v.w) : "r"(a) : "memory"); return v; }

template<int OFF, int TOT> __device__ __forceinline__ void wg_ss_n88(float (&d)[TOT], uint64_t da, uint64_t db) {
  asm volatile("wgmma.mma_async.sync.aligned.m64n88k16.f32.bf16.bf16 {%0, %1, %2, %3, %4, %5, %6, %7, %8, %9, %10, %11, %12, %13, %14, %15, %16, %17, %18, %19, %20, %21, %22, %23, %24, %25, %26, %27, %28, %29, %30, %31, %32, %33, %34, %35, %36, %37, %38, %39, %40, %41, %42, %43}, %44, %45, 1, 1, 1, 0, 1;"
    : "+f"(d[OFF+0]), "+f"(d[OFF+1]), "+f"(d[OFF+2]), "+f"(d[OFF+3]), "+f"(d[OFF+4]), "+f"(d[OFF+5]), "+f"(d[OFF+6]), "+f"(d[OFF+7]),
      "+f"(d[OFF+8]), "+f"(d[OFF+9]), "+f"(d[OFF+10]), "+f"(d[OFF+11]), "+f"(d[OFF+12]), "+f"(d[OFF+13]), "+f"(d[OFF+14]), "+f"(d[OFF+15]),
      "+f"(d[OFF+16]), "+f"(d[OFF+17]), "+f"(d[OFF+18]), "+f"(d[OFF+19]), "+f"(d[OFF+20]), "+f"(d[OFF+21]), "+f"(d[OFF+22]), "+f"(d[OFF+23]),
      "+f"(d[OFF+24]), "+f"(d[OFF+25]), "+f"(d[OFF+26]), "+f"(d[OFF+27]), "+f"(d[OFF+28]), "+f"(d[OFF+29]), "+f"(d[OFF+30]), "+f"(d[OFF+31]),
      "+f"(d[OFF+32]), "+f"(d[OFF+33]), "+f"(d[OFF+34]), "+f"(d[OFF+35]), "+f"(d[OFF+36]), "+f"(d[OFF+37]), "+f"(d[OFF+38]), "+f"(d[OFF+39]),
      "+f"(d[OFF+40]), "+f"(d[OFF+41]), "+f"(d[OFF+42]), "+f"(d[OFF+43])
    : "l"(da), "l"(db));
}
template<int OFF, int TOT> __device__ __forceinline__ void wg_ss_n128(float (&d)[TOT], uint64_t da, uint64_t db) {
  asm volatile("wgmma.mma_async.sync.aligned.m64n128k16.f32.bf16.bf16 {%0, %1, %2, %3, %4, %5, %6, %7, %8, %9, %10, %11, %12, %13, %14, %15, %16, %17, %18, %19, %20, %21, %22, %23, %24, %25, %26, %27, %28, %29, %30, %31, %32, %33, %34, %35, %36, %37, %38, %39, %40, %41, %42, %43, %44, %45, %46, %47, %48, %49, %50, %51, %52, %53, %54, %55, %56, %57, %58, %59, %60, %61, %62, %63}, %64, %65, 1, 1, 1, 0, 1;"
    : "+f"(d[OFF+0]), "+f"(d[OFF+1]), "+f"(d[OFF+2]), "+f"(d[OFF+3]), "+f"(d[OFF+4]), "+f"(d[OFF+5]), "+f"(d[OFF+6]), "+f"(d[OFF+7]),
      "+f"(d[OFF+8]), "+f"(d[OFF+9]), "+f"(d[OFF+10]), "+f"(d[OFF+11]), "+f"(d[OFF+12]), "+f"(d[OFF+13]), "+f"(d[OFF+14]), "+f"(d[OFF+15]),
      "+f"(d[OFF+16]), "+f"(d[OFF+17]), "+f"(d[OFF+18]), "+f"(d[OFF+19]), "+f"(d[OFF+20]), "+f"(d[OFF+21]), "+f"(d[OFF+22]), "+f"(d[OFF+23]),
      "+f"(d[OFF+24]), "+f"(d[OFF+25]), "+f"(d[OFF+26]), "+f"(d[OFF+27]), "+f"(d[OFF+28]), "+f"(d[OFF+29]), "+f"(d[OFF+30]), "+f"(d[OFF+31]),
      "+f"(d[OFF+32]), "+f"(d[OFF+33]), "+f"(d[OFF+34]), "+f"(d[OFF+35]), "+f"(d[OFF+36]), "+f"(d[OFF+37]), "+f"(d[OFF+38]), "+f"(d[OFF+39]),
      "+f"(d[OFF+40]), "+f"(d[OFF+41]), "+f"(d[OFF+42]), "+f"(d[OFF+43]), "+f"(d[OFF+44]), "+f"(d[OFF+45]), "+f"(d[OFF+46]), "+f"(d[OFF+47]),
      "+f"(d[OFF+48]), "+f"(d[OFF+49]), "+f"(d[OFF+50]), "+f"(d[OFF+51]), "+f"(d[OFF+52]), "+f"(d[OFF+53]), "+f"(d[OFF+54]), "+f"(d[OFF+55]),
      "+f"(d[OFF+56]), "+f"(d[OFF+57]), "+f"(d[OFF+58]), "+f"(d[OFF+59]), "+f"(d[OFF+60]), "+f"(d[OFF+61]), "+f"(d[OFF+62]), "+f"(d[OFF+63])
    : "l"(da), "l"(db));
}
template<int OFF, int TOT> __device__ __forceinline__ void wg_ss_n64(float (&d)[TOT], uint64_t da, uint64_t db) {
  asm volatile("wgmma.mma_async.sync.aligned.m64n64k16.f32.bf16.bf16 {%0, %1, %2, %3, %4, %5, %6, %7, %8, %9, %10, %11, %12, %13, %14, %15, %16, %17, %18, %19, %20, %21, %22, %23, %24, %25, %26, %27, %28, %29, %30, %31}, %32, %33, 1, 1, 1, 0, 1;"
    : "+f"(d[OFF+0]), "+f"(d[OFF+1]), "+f"(d[OFF+2]), "+f"(d[OFF+3]), "+f"(d[OFF+4]), "+f"(d[OFF+5]), "+f"(d[OFF+6]), "+f"(d[OFF+7]),
      "+f"(d[OFF+8]), "+f"(d[OFF+9]), "+f"(d[OFF+10]), "+f"(d[OFF+11]), "+f"(d[OFF+12]), "+f"(d[OFF+13]), "+f"(d[OFF+14]), "+f"(d[OFF+15]),
      "+f"(d[OFF+16]), "+f"(d[OFF+17]), "+f"(d[OFF+18]), "+f"(d[OFF+19]), "+f"(d[OFF+20]), "+f"(d[OFF+21]), "+f"(d[OFF+22]), "+f"(d[OFF+23]),
      "+f"(d[OFF+24]), "+f"(d[OFF+25]), "+f"(d[OFF+26]), "+f"(d[OFF+27]), "+f"(d[OFF+28]), "+f"(d[OFF+29]), "+f"(d[OFF+30]), "+f"(d[OFF+31])
    : "l"(da), "l"(db));
}
template<int OFF, int TOT> __device__ __forceinline__ void wg_ss_n32t(float (&d)[TOT], uint64_t da, uint64_t db) {
  asm volatile("wgmma.mma_async.sync.aligned.m64n32k16.f32.bf16.bf16 {%0, %1, %2, %3, %4, %5, %6, %7, %8, %9, %10, %11, %12, %13, %14, %15}, %16, %17, 1, 1, 1, 1, 0;"
    : "+f"(d[OFF+0]), "+f"(d[OFF+1]), "+f"(d[OFF+2]), "+f"(d[OFF+3]), "+f"(d[OFF+4]), "+f"(d[OFF+5]), "+f"(d[OFF+6]), "+f"(d[OFF+7]),
      "+f"(d[OFF+8]), "+f"(d[OFF+9]), "+f"(d[OFF+10]), "+f"(d[OFF+11]), "+f"(d[OFF+12]), "+f"(d[OFF+13]), "+f"(d[OFF+14]), "+f"(d[OFF+15])
    : "l"(da), "l"(db));
}
template<int OFF, int TOT> __device__ __forceinline__ void wg_ss_n8(float (&d)[TOT], uint64_t da, uint64_t db) {
  asm volatile("wgmma.mma_async.sync.aligned.m64n8k16.f32.bf16.bf16 {%0, %1, %2, %3}, %4, %5, 1, 1, 1, 0, 0;"
    : "+f"(d[OFF+0]), "+f"(d[OFF+1]), "+f"(d[OFF+2]), "+f"(d[OFF+3])
    : "l"(da), "l"(db));
}
template<int SCD, int OFF, int TOT> __device__ __forceinline__ void wg_qk_n64(float (&d)[TOT], uint32_t a0, uint32_t a1, uint32_t a2, uint32_t a3, uint64_t db) {
  asm volatile("wgmma.mma_async.sync.aligned.m64n64k16.f32.f16.f16 {%0, %1, %2, %3, %4, %5, %6, %7, %8, %9, %10, %11, %12, %13, %14, %15, %16, %17, %18, %19, %20, %21, %22, %23, %24, %25, %26, %27, %28, %29, %30, %31}, {%32,%33,%34,%35}, %36, %37, 1, 1, 0;"
    : "+f"(d[OFF+0]), "+f"(d[OFF+1]), "+f"(d[OFF+2]), "+f"(d[OFF+3]), "+f"(d[OFF+4]), "+f"(d[OFF+5]), "+f"(d[OFF+6]), "+f"(d[OFF+7]),
      "+f"(d[OFF+8]), "+f"(d[OFF+9]), "+f"(d[OFF+10]), "+f"(d[OFF+11]), "+f"(d[OFF+12]), "+f"(d[OFF+13]), "+f"(d[OFF+14]), "+f"(d[OFF+15]),
      "+f"(d[OFF+16]), "+f"(d[OFF+17]), "+f"(d[OFF+18]), "+f"(d[OFF+19]), "+f"(d[OFF+20]), "+f"(d[OFF+21]), "+f"(d[OFF+22]), "+f"(d[OFF+23]),
      "+f"(d[OFF+24]), "+f"(d[OFF+25]), "+f"(d[OFF+26]), "+f"(d[OFF+27]), "+f"(d[OFF+28]), "+f"(d[OFF+29]), "+f"(d[OFF+30]), "+f"(d[OFF+31])
    : "r"(a0), "r"(a1), "r"(a2), "r"(a3), "l"(db), "n"(SCD));
}
template<int SCD, int OFF, int TOT> __device__ __forceinline__ void wg_pv_n24(float (&d)[TOT], uint32_t a0, uint32_t a1, uint32_t a2, uint32_t a3, uint64_t db) {
  asm volatile("wgmma.mma_async.sync.aligned.m64n24k16.f32.bf16.bf16 {%0, %1, %2, %3, %4, %5, %6, %7, %8, %9, %10, %11}, {%12,%13,%14,%15}, %16, %17, 1, 1, 1;"
    : "+f"(d[OFF+0]), "+f"(d[OFF+1]), "+f"(d[OFF+2]), "+f"(d[OFF+3]), "+f"(d[OFF+4]), "+f"(d[OFF+5]), "+f"(d[OFF+6]), "+f"(d[OFF+7]),
      "+f"(d[OFF+8]), "+f"(d[OFF+9]), "+f"(d[OFF+10]), "+f"(d[OFF+11])
    : "r"(a0), "r"(a1), "r"(a2), "r"(a3), "l"(db), "n"(SCD));
}
template<int SCD, int OFF, int TOT> __device__ __forceinline__ void wg_qkb_n64(float (&d)[TOT], uint32_t a0, uint32_t a1, uint32_t a2, uint32_t a3, uint64_t db) {
  asm volatile("wgmma.mma_async.sync.aligned.m64n64k16.f32.bf16.bf16 {%0, %1, %2, %3, %4, %5, %6, %7, %8, %9, %10, %11, %12, %13, %14, %15, %16, %17, %18, %19, %20, %21, %22, %23, %24, %25, %26, %27, %28, %29, %30, %31}, {%32,%33,%34,%35}, %36, %37, 1, 1, 0;"
    : "+f"(d[OFF+0]), "+f"(d[OFF+1]), "+f"(d[OFF+2]), "+f"(d[OFF+3]), "+f"(d[OFF+4]), "+f"(d[OFF+5]), "+f"(d[OFF+6]), "+f"(d[OFF+7]),
      "+f"(d[OFF+8]), "+f"(d[OFF+9]), "+f"(d[OFF+10]), "+f"(d[OFF+11]), "+f"(d[OFF+12]), "+f"(d[OFF+13]), "+f"(d[OFF+14]), "+f"(d[OFF+15]),
      "+f"(d[OFF+16]), "+f"(d[OFF+17]), "+f"(d[OFF+18]), "+f"(d[OFF+19]), "+f"(d[OFF+20]), "+f"(d[OFF+21]), "+f"(d[OFF+22]), "+f"(d[OFF+23]),
      "+f"(d[OFF+24]), "+f"(d[OFF+25]), "+f"(d[OFF+26]), "+f"(d[OFF+27]), "+f"(d[OFF+28]), "+f"(d[OFF+29]), "+f"(d[OFF+30]), "+f"(d[OFF+31])
    : "r"(a0), "r"(a1), "r"(a2), "r"(a3), "l"(db), "n"(SCD));
}

__device__ __forceinline__ uint32_t exp_mufu(float a, float b) { return pack_bf16(ex2(a), ex2(b)); }
__device__ __forceinline__ uint32_t exp_poly(float a, float b, uint32_t mlo, uint32_t mhi) {
  uint32_t u = __byte_perm(__float_as_uint(a), __float_as_uint(b), 0x6521), mh, e, p;
  asm("lop3.b32 %0, %1, %2, 0x3F003F00, 0xEA;" : "=r"(mh) : "r"(u), "r"(mlo));
  asm("lop3.b32 %0, %1, %2, 0x00020002, 0xEA;" : "=r"(e) : "r"(u), "r"(mhi));
  asm("fma.rn.bf16x2 %0, %1, %2, %3;" : "=r"(p) : "r"(u), "r"(mh), "r"(e));
  return p;
}
constexpr float MAGIC_C = 48948.0625f;
constexpr float QSCALE = 0.25f * 1.4426950408889634f * 8.f;
constexpr float BOUND = 80.f;

__device__ __forceinline__ void softmax_step(const float (&s)[32], uint32_t (&p)[16], uint32_t mlo, uint32_t mhi) {
  constexpr int PP = NP / 4;
  int ip = 0, im = PP;
#pragma unroll
  for (int i = 0; i < 16; i++) {
    if (((i + 1) * PP / 16) > (i * PP / 16)) { p[ip] = exp_poly(s[2 * ip], s[2 * ip + 1], mlo, mhi); ip++; }
    else { p[im] = exp_mufu(s[2 * im], s[2 * im + 1]); im++; }
  }
}
constexpr int64_t VSTEP = 32 - (32 << 16);
constexpr uint64_t KSTEP = 256, VSTEP8 = (uint64_t)(8 * VSTEP);
__device__ __forceinline__ void issue_qk(float (&s)[32], const uint32_t (&q)[4], uint64_t dk) { wg_qk_n64<1, 0, 32>(s, q[0], q[1], q[2], q[3], dk); }
__device__ __forceinline__ void issue_pv(float (&o)[12], const uint32_t (&p)[16], uint64_t dv) {
#pragma unroll
  for (int c = 0; c < 4; c++) { wg_pv_n24<1, 0, 12>(o, p[4 * c], p[4 * c + 1], p[4 * c + 2], p[4 * c + 3], dv + c * VSTEP); }
}

__device__ __forceinline__ uint32_t wslot(int f) { const int r = f - 5 * ((f * 52) >> 8); return r == 4 ? SM_Q : SM_RING + r * WSLOT; }

struct Params {
  const __nv_bfloat16* gate_w;
  const __nv_bfloat16* b_sp;
  const __nv_bfloat16* w_out;
  const __nv_bfloat16* wo;
  const __nv_bfloat16* w_in;
  const __nv_bfloat16* wq;
  const __nv_bfloat16* wk;
  const __nv_bfloat16* wv;
  uint32_t mlo, mhi;
};

__device__ __forceinline__ float rcp(float x) { float r; asm("rcp.approx.ftz.f32 %0, %1;" : "=f"(r) : "f"(x)); return r; }
__device__ __forceinline__ uint32_t store_o_tile(const float (&o)[12], uint32_t* obase, uint32_t gbase, int tau, int lane) {
  const float f0 = ldsf(gbase + (tau & 1) * 256) * rcp(o[8]), f1 = ldsf(gbase + (tau & 1) * 256 + 32) * rcp(o[10]);
  uint32_t* dst = obase + (tau & 1) * 2048 + (tau >> 1) * 64;
  dst[0] = pack_bf16(o[0] * f0, o[1] * f0);
  dst[32] = pack_bf16(o[4] * f0, o[5] * f0);
  dst[256] = pack_bf16(o[2] * f1, o[3] * f1);
  dst[288] = pack_bf16(o[6] * f1, o[7] * f1);
  return ld_back(dst + ((lane >> 3) & 1) * 256 + (lane & 7) * 8 - lane);
}

__global__ void __cluster_dims__(2, 1, 1) __launch_bounds__(NTHREADS, 1)
fused_kernel(const __grid_constant__ CUtensorMap tm_x, const __grid_constant__ CUtensorMap tm_wq,
             const __grid_constant__ CUtensorMap tm_win, const __grid_constant__ CUtensorMap tm_wsp,
             const __grid_constant__ CUtensorMap tm_wout, const __grid_constant__ CUtensorMap tm_wo,
             const __grid_constant__ CUtensorMap tm_out, const Params prm) {
  extern __shared__ __align__(1024) uint8_t smem_raw[];
  const uint32_t sb = __shfl_sync(0xffffffffu, (uint32_t)__cvta_generic_to_shared(smem_raw), 0);
  const int warp = __shfl_sync(0xffffffffu, (int)(threadIdx.x >> 5), 0);
  const int wg = warp >> 2;
  const int tid = threadIdx.x & 127;
  const int lane = threadIdx.x & 31;
  const int rank = blockIdx.x & 1;
  const int ai = (blockIdx.x >> 4) * 2 + rank, aj = (blockIdx.x >> 1) & 7;
  const int bi = blockIdx.x >> 3, bj = blockIdx.x & 7;
  auto BAR = [&](int k) { return sb + SM_BAR + 8u * k; };

  if (warp == 16) {
    if (lane == 0) {
      mbar_init(BAR(B_XFULL), 1); mbar_init(BAR(B_XFULL + 1), 1);
      asm volatile("fence.mbarrier_init.release.cluster;" ::: "memory");
    }
    __syncwarp();
    e_expect(BAR(B_XFULL), 16384);
    tma2d(sb + SM_K, &tm_x, 0, ai * 128, BAR(B_XFULL));
    e_expect(BAR(B_XFULL + 1), 16384);
    tma2d(sb + SM_K + 16384, &tm_x, 64, ai * 128, BAR(B_XFULL + 1));
    if (lane == 0) TS(36);
  } else if (warp == 18) {
    if (lane == 0) { mbar_init(BAR(B_WFULL), 1); asm volatile("fence.mbarrier_init.release.cluster;" ::: "memory"); }
    __syncwarp();
    e_expect(BAR(B_WFULL), 16384);
#pragma unroll
    for (int h = 0; h < 2; h++) {
      tma3d(sb + SM_RING + h * 8192, &tm_win, 0, h * 32, aj < 6 ? 21 + 3 * aj : 27 + 2 * aj, BAR(B_WFULL));
      tma2d(sb + SM_RING + h * 8192 + 6144, &tm_wq, 64 * aj, h * 32, BAR(B_WFULL));
    }
  } else if (warp == 19) {
    l2_prefetch(reinterpret_cast<const uint8_t*>(prm.w_in) + blockIdx.x * 11008, 11008);
    l2_prefetch(reinterpret_cast<const uint8_t*>(prm.wq) + blockIdx.x * 4096, 4096);
  } else if (warp < 16 && lane == 0) {
#pragma unroll
    for (int r = 0; r < 4; r++) {
      const int k = warp + 16 * r;
      uint32_t cnt = 1;
      if (k >= B_XEMPTY && k < B_XEMPTY + 8) cnt = 4;
      if (k >= B_WEMPTY && k < B_WEMPTY + 11) cnt = 4;
      if (k == B_ZST0 || k == B_ZST1) cnt = 8;
      if (k >= B_REMPTY && k < B_REMPTY + 3) cnt = 2;
      if (k == B_ATT) cnt = 6;
      if (k == B_QRDY) cnt = 16;
      if (k == B_KSTAT) cnt = 17;
      if (k == B_LNOK) cnt = 8;
      if (k == B_WOFULL) cnt = 3;
      if (k >= 2 && k != B_WFULL) mbar_init(BAR(k), cnt);
    }
    asm volatile("fence.mbarrier_init.release.cluster;" ::: "memory");
  }
  __syncthreads();
  if (threadIdx.x == 0) TS(35);
  asm volatile("barrier.cluster.arrive.relaxed.aligned;" ::: "memory");
  asm volatile("barrier.cluster.wait.acquire.aligned;" ::: "memory");

  if (wg == 4) {
    asm volatile("setmaxnreg.dec.sync.aligned.u32 24;");
    if (warp == 18) {
#pragma unroll 1
      for (int f = 1; f < 16; f++) {
        if (f == 1 && lane == 0) TS(0);
        if (f == 5 && lane == 0) TS(37);
        if (f >= 5) mbar_wait(BAR(B_WEMPTY + f - 5), 0);
        const uint32_t dst = sb + wslot(f) + rank * 8192, bar = BAR(B_WFULL + f);
        const int k0 = (f & 7) * 64 + rank * 32;
        e_expect(bar, 16384);
        tma3d_mc(dst, &tm_win, 0, k0, f < 8 ? (aj < 6 ? 21 + 3 * aj : 27 + 2 * aj) : (aj < 2 ? 2 * aj : 3 * aj - 2), bar);
        tma2d_mc(dst + 6144, &tm_wq, 64 * aj + (f >> 3) * 32, k0, bar);
        if (f < 7) {
          e_expect(BAR(B_XFULL + 1 + f), 16384);
          tma2d(sb + SM_K + (f + 1) * 16384, &tm_x, (f + 1) * 64, ai * 128, BAR(B_XFULL + 1 + f));
        }
      }
      if (lane == 0) TS(1);
    } else if (warp == 19) {
      mbar_wait(BAR(B_ZST0), 0);
      if (lane == 0) { red_release(&g_zcnt[ai * 32]); TS(20); }
      __syncwarp();
      const unsigned ep1 = lds32(sb + SM_MISC + 4 * M_EPOCH) + 1;
      wait_ge(&g_zcnt[(lane & 15) * 32], ep1 * 8);
      __syncwarp();
      e_arrive(BAR(B_ZOK));
      mbar_wait(BAR(B_ZST1), 0);
      if (lane == 0) { red_release(&g_z1cnt[ai * 32]); TS(17); }
      __syncwarp();
      l2_prefetch(reinterpret_cast<const uint8_t*>(prm.w_out) + blockIdx.x * 5504, 5504);
      l2_prefetch(reinterpret_cast<const uint8_t*>(prm.wo) + blockIdx.x * 4096, 4096);
      wait_ge(&g_z1cnt[bi * 32], ep1 * 8);
      e_arrive(BAR(B_Z1OK));
    } else if (warp == 16) {
      tm_prefetch(&tm_wsp);
      tm_prefetch(&tm_wout);
      tm_prefetch(&tm_wo);
      tm_prefetch(&tm_out);
      mbar_wait(BAR(B_XEMPTY), 0);
      tma2d_pf(&tm_wsp, (bj >> 1) * 64, bi * 128 + rank * 64);
      tma2d_pf(&tm_wsp, (bj >> 1) * 64 + 256, bi * 128 + rank * 64);
    } else {
      if (lane == 0) {
        sts32(sb + SM_MISC + 4 * M_EPOCH, atomicAdd(&g_ticket, 1u) / NCTA);
        mbar_arrive(BAR(B_EPOCH));
        TS(71);
      }
      __syncwarp();
      const unsigned ep1 = lds32(sb + SM_MISC + 4 * M_EPOCH) + 1;
      e_expect(BAR(B_KVFULL), 49152);
      e_expect(BAR(B_KVB), 49152);
      e_expect(BAR(B_KVC), 32768);
      mbar_wait(BAR(B_WFULL + 8), 0);
      uint32_t kn = 0, vb = 0;
#pragma unroll 1
      for (int n = 0; n < SPIN_LIMIT; n++) {
        unsigned long long a, b, c, d;
        asm volatile("ld.relaxed.gpu.global.v2.b64 {%0, %1}, [%2];" : "=l"(a), "=l"(b) : "l"(&g_kvflag[2 * lane]) : "memory");
        asm volatile("ld.relaxed.gpu.global.v2.b64 {%0, %1}, [%2];" : "=l"(c), "=l"(d) : "l"(&g_kvflag[64 + 2 * lane]) : "memory");
        kn = max((uint32_t)a, (uint32_t)c); vb = (uint32_t)b | (uint32_t)d;
        if (__all_sync(0xffffffffu, (uint32_t)(a >> 32) == ep1 && (uint32_t)(b >> 32) == ep1 && (uint32_t)(c >> 32) == ep1 && (uint32_t)(d >> 32) == ep1)) break;
        __nanosleep(100);
      }
      asm volatile("fence.acquire.gpu;" ::: "memory");
      kn = __reduce_max_sync(0xffffffffu, kn);
      vb = __reduce_or_sync(0xffffffffu, vb);
      if (lane == 0) {
        TS(6);
        sts32(sb + SM_MISC + 4 * M_KN2, kn);
        sts32(sb + SM_MISC + 4 * M_VOK, vb == 0xFFFFu ? 1u : 0u);
        mbar_arrive(BAR(B_KSTAT));
      }
      __syncwarp();
      fence_async();
      mbar_wait(BAR(B_LNOK), 0);
#pragma unroll 1
      for (int c = 0; c < 8; c++) {
        const uint32_t off = c * 16384 + rank * 8192;
        mbar_wait(BAR(B_XEMPTY + c), 0);
        bulk_mc(sb + SM_K + off, reinterpret_cast<const uint8_t*>(g_kimg) + off, 8192, BAR(c < 3 ? B_KVFULL : (c < 6 ? B_KVB : B_KVC)));
      }
      if (lane == 0) TS(7);
      mbar_wait(BAR(B_DEC), 0);
      if (!lds32(sb + SM_MISC + 4 * M_FAST)) {
        mbar_wait(BAR(B_KVFULL), 0); mbar_wait(BAR(B_KVB), 0); mbar_wait(BAR(B_KVC), 0);
        e_expect(BAR(B_KFB), 65536);
#pragma unroll 1
        for (int j = 0; j < 32; j++) bulk(sb + SM_K + j * 4096, g_kbf + j * 128, 2048, BAR(B_KFB));
      }
    }
    const unsigned ep1 = lds32(sb + SM_MISC + 4 * M_EPOCH) + 1;
    if (warp < 19) {
      const int st = warp - 16, row = bi * 128 + rank * 64;
      const uint32_t stg = sb + SM_RING + st * RSTAGE, full = BAR(B_RFULL + st), empty = BAR(B_REMPTY + st);
      mbar_wait(BAR(B_XEMPTY + 7), 0);
      mbar_wait(BAR(B_ZOK), 0);
      fence_async();
      if (threadIdx.x == 512) TS(2);
      const uint8_t* zsrc = reinterpret_cast<const uint8_t*>(g_z2n) + (bj * 32 + st) * 11264;
      int n = st, ph = 1;
#pragma unroll 1
      for (; n < 32; n += 3, zsrc += 3 * 11264, ph ^= 1) {
        mbar_wait(empty, ph);
        e_expect(full, 16384 + 11264);
        tma2d_mc(stg + rank * 8192, &tm_wsp, n * 64, row, full);
        bulk(stg + 16384, zsrc, 11264, full);
        if ((n & 3) == (bj >> 1) && n < 24) tma2d_pf(&tm_wsp, (n + 8) * 64, row);
      }
      if (n == 32) {
        mbar_wait(empty, ph);
        mbar_wait(BAR(B_Z1OK), 0);
        fence_async();
        e_expect(full, 22528 + 512 + 256);
        bulk(stg, g_z1 + (bi * 88 + bj * 11) * 128, 22528, full);
        bulk(stg + 22528, g_gate + bi * 128, 512, full);
        bulk(stg + 23040, prm.b_sp + bi * 128, 256, full);
        n += 3; ph ^= 1;
      }
      bool first = true;
#pragma unroll 1
      for (; n < 44; n += 3, ph ^= 1) {
        mbar_wait(empty, ph);
        e_expect(full, 16384 + 8192);
        tma2d(stg + 16384, &tm_wout, 64 * bj, (n - 33) * 64, full);
        if (first) { wait_ge(&g_ucnt[bi * 32], ep1 * 8); fence_async(); first = false; if (threadIdx.x == 512) TS(3); }
        bulk_mc(stg + rank * 8192, reinterpret_cast<const uint8_t*>(g_u) + (bi * 11 + n - 33) * 16384 + rank * 8192, 8192, full);
      }
      mbar_wait(empty, ph);
      e_expect(BAR(B_WOFULL), st == 2 ? 16384 : 24576);
#pragma unroll 1
      for (int c = 3 * st; c < 3 * st + 3 && c < 8; c++) tma2d(stg + (c - 3 * st) * 8192, &tm_wo, 64 * bj, c * 64, BAR(B_WOFULL));
      if (threadIdx.x == 512) TS(4);
    }
    const int c0 = (warp - 16);
    e_expect(BAR(B_XFULL + c0), 16384);
    e_expect(BAR(B_XFULL + c0 + 4), 16384);
    mbar_wait(BAR(B_ATT), 0);
#pragma unroll 1
    for (int n = 0; n < SPIN_LIMIT; n++) if ((int)(ld_acquire(&g_ocnt[bi * 32]) - ep1 * 24) >= 0) break;
    fence_async();
    if (threadIdx.x == 512) TS(5);
    const uint32_t ooff = c0 * 16384 + rank * 8192;
    bulk_mc(sb + SM_K + ooff, reinterpret_cast<const uint8_t*>(g_o) + bi * 131072 + ooff, 8192, BAR(B_XFULL + c0));
    bulk_mc(sb + SM_K + ooff + 65536, reinterpret_cast<const uint8_t*>(g_o) + bi * 131072 + ooff + 65536, 8192, BAR(B_XFULL + c0 + 4));
  } else {
    asm volatile("setmaxnreg.inc.sync.aligned.u32 112;");
    const int w = tid >> 5, g = lane >> 2, t4 = lane & 3, half = wg & 1;
    {
      float acc[64];
      if (wg == 2) {
        const int slot = ai * 4 + (aj >> 1), isv = aj & 1;
        const uint4* wsrc = reinterpret_cast<const uint4*>(isv ? prm.wv : prm.wk) + tid;
        uint4 wr[8];
#pragma unroll
        for (int r = 0; r < 8; r++) wr[r] = __ldg(wsrc + 128 * r);
#pragma unroll
        for (int r = 0; r < 8; r++) sts128(sb + SM_WKV + r * 2048 + (tid >> 1) * 32 + (((tid ^ (tid >> 3)) & 1) << 4), wr[r].x, wr[r].y, wr[r].z, wr[r].w);
        fence_async_smem();
        bar_sync(3, 128);
        float kv[16];
#pragma unroll
        for (int k = 0; k < 16; k++) kv[k] = 0.f;
        regfence(kv);
#pragma unroll 1
        for (int c = 0; c < 8; c++) {
          mbar_wait(BAR(B_XFULL + c), 0);
          const uint64_t da = mkdesc(sb + SM_WKV + c * 2048, 0, 256, 3);
          const uint64_t db = mkdesc(sb + SM_K + c * 16384 + (aj >> 1) * 4096, 16, 1024, 1);
          wg_fence();
#pragma unroll
          for (int k = 0; k < 4; k++) wg_ss_n32t<0, 16>(kv, da + 32 * k, db + 2 * k);
          wg_commit();
        }
        wg_wait<0>();
        regfence(kv);
        if (tid == 0) TS(22);
        const uint32_t sT = sb + SM_WKV, sH = sb + SM_WKV + 4096;
        bar_sync(3, 128);
        {
          const float a = w & 1 ? kv[4] : kv[0], b = w & 1 ? kv[5] : kv[1], c = w & 1 ? kv[6] : kv[2], d = w & 1 ? kv[7] : kv[3];
          const float e = w & 1 ? kv[12] : kv[8], f = w & 1 ? kv[13] : kv[9], h = w & 1 ? kv[14] : kv[10], i = w & 1 ? kv[15] : kv[11];
          const uint32_t lo = pack_bf16(w & 2 ? e : a, w & 2 ? f : b), hi = pack_bf16(w & 2 ? h : c, w & 2 ? i : d);
          const uint32_t p = sT + ((w * 8 + 2 * t4) * 17 + g) * 4;
          sts32(p, lo << 16); sts32(p + 68, lo & 0xFFFF0000u); sts32(p + 32, hi << 16); sts32(p + 100, hi & 0xFFFF0000u);
        }
        bar_sync(3, 128);
        if (tid == 0) TS(64);
        const int tok = (tid & 63) >> 1, hf = tid & 1;
        float f[8];
#pragma unroll
        for (int e = 0; e < 8; e++) f[e] = ldsf(sT + (tok * 17 + hf * 8 + e) * 4);
        uint4 val = make_uint4(pack_bf16(f[0], f[1]), pack_bf16(f[2], f[3]), pack_bf16(f[4], f[5]), pack_bf16(f[6], f[7]));
        uint32_t stat = 0;
        if (isv) {
#pragma unroll
          for (int e = 0; e < 8; e++) {
            if (fabsf(f[e]) >= 9.5367431640625e-07f) stat |= 1u << e;
            if (!(fabsf(f[e]) <= 1073741824.f)) stat |= 1u << (16 - 8 * hf);
          }
          stat = __reduce_or_sync(0xffffffffu, stat << (8 * hf));
        } else {
          float n2 = 0.f;
#pragma unroll
          for (int e = 0; e < 8; e++) n2 = fmaf(f[e], f[e], n2);
          n2 += __shfl_xor_sync(0xffffffffu, n2, 1);
          if (!(n2 <= 3.0e38f)) n2 = 3.0e38f;
          stat = __reduce_max_sync(0xffffffffu, __float_as_uint(n2));
          if (tid < 48) {
            const int d = tid & 15, sg = tid >> 4, j0 = sg == 0 ? 0 : (sg == 1 ? 10 : 22), j1 = sg == 0 ? 10 : (sg == 1 ? 22 : 32);
            const float sc = slot < NP ? 16.f : 0.125f;
            float kx[12], run = 0.f;
#pragma unroll
            for (int e = 0; e < 12; e++) kx[e] = ldsf(sT + (min(j0 + e, 31) * 17 + d) * 4);
#pragma unroll
            for (int e = 0; e < 12; e++) {
              const __half hv = __float2half_rn(fmaf(kx[e], sc, -run));
              run += __half2float(hv);
              if (j0 + e < j1) sts16(sH + ((j0 + e) * 16 + d) * 2, __half_as_ushort(hv));
            }
          }
        }
        if (lane == 0) sts32(sb + SM_MISC + 4 * (M_KVR + w), stat);
        bar_sync(3, 128);
        const uint32_t off = slot * 2 + (hf ^ ((slot >> 2) & 1));
        uint4* dst = tid < 64 ? g_kimg + tok * 256 + isv * 128 + off : g_kbf + tok * 128 + off;
        if (!isv && tid < 64) val = lds128(sH + tok * 32 + hf * 16);
        uint32_t chk = 0;
        if (tid < 64 || !isv) { *dst = val; chk = ld_back(dst); }
        mbar_wait(BAR(B_EPOCH), 0);
        consume(chk, sb);
        fence_async();
        bar_sync(3, 128);
        if (tid == 0) {
          const uint32_t s0 = lds32(sb + SM_MISC + 4 * M_KVR), s1 = lds32(sb + SM_MISC + 4 * (M_KVR + 1));
          const unsigned long long fl = ((unsigned long long)(lds32(sb + SM_MISC + 4 * M_EPOCH) + 1) << 32) | (isv ? (s0 | s1) : max(s0, s1));
          asm volatile("st.relaxed.gpu.global.b64 [%0], %1;" ::"l"(&g_kvflag[ai * 8 + aj]), "l"(fl) : "memory");
          TS(23);
        }
      } else if (wg == 3) {
        if (tid < 64) { const uint4 gv = __ldg(reinterpret_cast<const uint4*>(prm.gate_w) + tid); sts128(sb + SM_GW + tid * 16, gv.x, gv.y, gv.z, gv.w); }
        sts32(sb + SM_ONES + tid * 4, 0x3F803F80u);
        fence_async_smem();
        bar_sync(4, 128);
        float ga[8];
#pragma unroll
        for (int k = 0; k < 8; k++) ga[k] = 0.f;
        regfence(ga);
#pragma unroll 1
        for (int c = 0; c < 8; c++) {
          mbar_wait(BAR(B_XFULL + c), 0);
          if (tid == 0) TS(40 + c);
          const uint64_t da = mkdesc(sb + SM_K + c * 16384, 16, 1024, 1), db = mkdesc(sb + SM_GW + c * 128, 16, 128, 0);
          wg_fence();
#pragma unroll
          for (int k = 0; k < 4; k++) { wg_ss_n8<0, 8>(ga, da + 2 * k, db + 2 * k); wg_ss_n8<4, 8>(ga, da + 512 + 2 * k, db + 2 * k); }
          wg_commit();
        }
        wg_wait<0>();
        regfence(ga);
        const float g0 = __shfl_sync(0xffffffffu, ga[0], lane & 28), g1 = __shfl_sync(0xffffffffu, ga[2], lane & 28);
        const float g2 = __shfl_sync(0xffffffffu, ga[4], lane & 28), g3 = __shfl_sync(0xffffffffu, ga[6], lane & 28);
        const float gs = t4 & 2 ? (t4 & 1 ? g3 : g2) : (t4 & 1 ? g1 : g0);
        sts32(sb + SM_G + ((t4 >> 1) * 64 + w * 16 + (t4 & 1) * 8 + g) * 4, __float_as_uint(__fdividef(1.f, 1.f + __expf(-gs))));
        bar_sync(4, 128);
        if (aj == 0) g_gate[ai * 128 + tid] = ldsf(sb + SM_G + tid * 4);
        if (tid == 0) TS(8);
      }
#pragma unroll
      for (int k = 0; k < 64; k++) acc[k] = 0.f;
      regfence(acc);
      const int pass = wg >> 1;
#pragma unroll 1
      for (int c = 0; c < 8; c++) {
        mbar_wait(BAR(B_XFULL + c), 0);
        mbar_wait(BAR(B_WFULL + pass * 8 + c), 0);
        if (tid == 0 && half == pass) TS(48 + pass * 8 + c);
        const uint64_t da = mkdesc(sb + SM_K + c * 16384 + half * 8192, 16, 1024, 1);
        const uint64_t db = mkdesc(sb + wslot(pass * 8 + c), 2048, 512, 2);
        wg_fence();
#pragma unroll
        for (int k = 0; k < 4; k++) wg_ss_n128<0, 64>(acc, da + 2 * k, db + (k & 1) * 64 + (k >> 1) * 512);
        wg_commit();
        wg_wait<1>();
        if (tid == 0 && c > 0) {
          if (pass * 8 + c < 12) mbar_arrive_both(BAR(B_WEMPTY + pass * 8 + c - 1));
          if (pass) mbar_arrive_both(BAR(B_XEMPTY + c - 1));
        }
      }
      wg_wait<0>();
      if (tid == 0) mbar_arrive_both(BAR(pass ? B_XEMPTY + 7 : B_WEMPTY + 7));
      regfence(acc);
      if (tid == 0) TS(wg == 0 ? 16 : (wg == 2 ? 24 : (wg == 3 ? 9 : 95)));
      uint32_t qb[8];
      {
        float n2 = 0.f;
#pragma unroll
        for (int k = 0; k < 8; k++) qb[k] = pack_bf16(acc[48 + 2 * k], acc[49 + 2 * k]);
#pragma unroll
        for (int k = 0; k < 4; k++) {
          const uint32_t a = qb[4 * (k >> 1) + (k & 1)], b = qb[4 * (k >> 1) + (k & 1) + 2];
          float s = bf_lo(a) * bf_lo(a);
          s = fmaf(bf_hi(a), bf_hi(a), s); s = fmaf(bf_lo(b), bf_lo(b), s); s = fmaf(bf_hi(b), bf_hi(b), s);
          s += __shfl_xor_sync(0xffffffffu, s, 1); s += __shfl_xor_sync(0xffffffffu, s, 2);
          if (!(s <= 3.0e38f)) s = 3.0e38f;
          n2 = fmaxf(n2, s);
        }
        const uint32_t nmax = __reduce_max_sync(0xffffffffu, __float_as_uint(n2));
        if (lane == 0) { sts32(sb + SM_MISC + 4 * (M_RED + warp), nmax); mbar_arrive(BAR(B_KSTAT)); }
      }
      auto finish_q = [&]() {
        mbar_wait(BAR(B_KSTAT), 0);
        const float qn2 = __uint_as_float(__reduce_max_sync(0xffffffffu, lds32(sb + SM_MISC + 4 * (M_RED + (lane & 15)))));
        const float kn2 = ldsf(sb + SM_MISC + 4 * M_KN2);
        constexpr float SC = QSCALE * 0.125f;
        const bool fast = lds32(sb + SM_MISC + 4 * M_VOK) && qn2 <= 4.0e8f && kn2 <= 4.0e6f && qn2 * kn2 * (SC * SC) <= BOUND * BOUND;
        if (fast) {
#pragma unroll
          for (int k = 0; k < 8; k++) qb[k] = pack_f16(bf_lo(qb[k]) * QSCALE, bf_hi(qb[k]) * QSCALE);
        }
        sts128(sb + SM_Q + wg * 2048 + pass * 4096 + tid * 16, qb[0], qb[1], qb[2], qb[3]);
        sts128(sb + SM_Q + wg * 2048 + pass * 4096 + 4096 + tid * 16, qb[4], qb[5], qb[6], qb[7]);
        if (threadIdx.x == 256) { sts32(sb + SM_MISC + 4 * M_FAST, fast ? 1u : 0u); mbar_arrive(BAR(B_DEC)); }
        __syncwarp();
        if (lane == 0) mbar_arrive(BAR(B_QRDY));
        if (tid == 0 && pass) TS(75 + wg);
      };
      if (pass) finish_q();
#pragma unroll
      for (int k = 0; k < 48; k++) acc[k] = gelu2_tanh(acc[k]);
      int fb0, c_lo = 0, c_hi = 12;
      if (wg < 2) { fb0 = aj < 6 ? 12 * aj - 2 : 22 + 8 * aj; if (aj == 0) c_lo = 2; if (aj >= 6) c_hi = 8; }
      else { fb0 = aj < 2 ? 8 * aj : 12 * aj - 8; if (aj < 2) c_hi = 8; if (aj == 7) c_hi = 10; }
      if (wg < 2) {
        float s1[2][3], s2[2][3];
#pragma unroll
        for (int k = 0; k < 48; k++) {
          const int r = (k >> 1) & 1, gq = k < 8 ? 0 : (k < 32 ? 1 : 2);
          if (k - 2 * r == (gq == 0 ? 0 : (gq == 1 ? 8 : 32))) { s1[r][gq] = acc[k]; s2[r][gq] = acc[k] * acc[k]; }
          else { s1[r][gq] += acc[k]; s2[r][gq] = fmaf(acc[k], acc[k], s2[r][gq]); }
        }
        const float inv_n = __fdividef(0.125f, (float)(c_hi - c_lo));
        float mm[2], vv[2];
#pragma unroll
        for (int r = 0; r < 2; r++) {
          float a = s1[r][1], b = s2[r][1];
          if (c_lo == 0) { a += s1[r][0]; b += s2[r][0]; }
          if (c_hi == 12) { a += s1[r][2]; b += s2[r][2]; }
          a += __shfl_xor_sync(0xffffffffu, a, 1); b += __shfl_xor_sync(0xffffffffu, b, 1);
          a += __shfl_xor_sync(0xffffffffu, a, 2); b += __shfl_xor_sync(0xffffffffu, b, 2);
          mm[r] = a * inv_n;
          vv[r] = fmaxf(fmaf(-a, mm[r], b), 0.f);
        }
        const int r0 = half * 64 + w * 16 + g;
        mbar_wait(BAR(B_EPOCH), 0);
        const unsigned ep1 = lds32(sb + SM_MISC + 4 * M_EPOCH) + 1;
        if (threadIdx.x == 0) TS(67);
        if (t4 < 2) {
          const float m = t4 ? mm[1] : mm[0], v = t4 ? vv[1] : vv[0];
          asm volatile("st.relaxed.gpu.global.v2.b64 [%0], {%1, %2};" ::"l"(&g_lnstat[(ai * 8 + aj) * 128 + r0 + 8 * t4]),
                       "l"(((unsigned long long)ep1 << 32) | __float_as_uint(m)), "l"(((unsigned long long)ep1 << 32) | __float_as_uint(v)) : "memory");
        }
        float sm[4], sv[4];
        const uint4* lp = &g_lnstat[(ai * 8 + 2 * t4) * 128 + r0];
#pragma unroll 1
        for (int n = 0; n < SPIN_LIMIT; n++) {
          uint32_t tg = ep1;
          if (lane < 8) tg = ld_back(reinterpret_cast<const uint32_t*>(&g_lnstat[(ai * 8 + lane) * 128 + half * 64 + w * 16 + 15]) + 3);
          if (__all_sync(0xffffffffu, tg == ep1)) break;
        }
#pragma unroll 1
        for (int n = 0; n < SPIN_LIMIT; n++) {
          bool ok = true;
#pragma unroll
          for (int e = 0; e < 4; e++) {
            unsigned long long a, b;
            asm volatile("ld.relaxed.gpu.global.v2.b64 {%0, %1}, [%2];" : "=l"(a), "=l"(b) : "l"(lp + (e >> 1) * 128 + (e & 1) * 8) : "memory");
            ok = ok && (uint32_t)(a >> 32) == ep1 && (uint32_t)(b >> 32) == ep1;
            sm[e] = __uint_as_float((uint32_t)a); sv[e] = __uint_as_float((uint32_t)b);
          }
          if (__all_sync(0xffffffffu, ok)) break;
        }
        if (lane == 0) mbar_arrive(BAR(B_LNOK));
        if (threadIdx.x == 0) TS(68);
        const float na = t4 == 0 ? 80.f : (t4 == 3 ? 64.f : 96.f), nb = t4 == 3 ? 64.f : 96.f;
#pragma unroll
        for (int r = 0; r < 2; r++) {
          float t = fmaf(sm[r], na, sm[2 + r] * nb);
          t += __shfl_xor_sync(0xffffffffu, t, 1); t += __shfl_xor_sync(0xffffffffu, t, 2);
          const float mu = t * (1.f / 688.f);
          const float da = sm[r] - mu, db = sm[2 + r] - mu;
          float m2 = sv[r] + sv[2 + r] + na * da * da + nb * db * db;
          m2 += __shfl_xor_sync(0xffffffffu, m2, 1); m2 += __shfl_xor_sync(0xffffffffu, m2, 2);
          const float rs = rsqrtf(fmaf(m2, 1.f / 688.f, 4e-5f)), sh = -mu * rs;
#pragma unroll
          for (int k = 2 * r; k < 48; k += 4) { acc[k] = fmaf(acc[k], rs, sh); acc[k + 1] = fmaf(acc[k + 1], rs, sh); }
        }
        if (aj == 7) {
          c_hi = 10;
#pragma unroll
          for (int k = 32; k < 40; k++) acc[k] = 0.f;
        }
      }
      uint32_t* zp = wg < 2 ? reinterpret_cast<uint32_t*>(g_z2n) + (ai * 2 + half) * 2816 + w * 704
                            : reinterpret_cast<uint32_t*>(g_z1) + (ai * 88 * 16 + half * 8 + w * 2) * 32;
      const int mul = wg < 2 ? 373 : 0, cstr = wg < 2 ? 32 : 512, rstr = wg < 2 ? 352 : 32;
      auto zoff = [&](int c8) { const int fb = fb0 + c8; return ((fb * mul) >> 12) * (32 * 2816 - 352) + fb * cstr; };
#pragma unroll
      for (int c8 = 0; c8 < 12; c8++) {
        uint32_t* p = zp + zoff(c8) + lane;
        if (c8 >= c_lo && c8 < c_hi) { p[0] = pack_bf16(acc[4 * c8], acc[4 * c8 + 1]); p[rstr] = pack_bf16(acc[4 * c8 + 2], acc[4 * c8 + 3]); }
      }
      if (tid == 0) TS(wg == 0 ? 69 : 78 + wg);
      fence_async();
      __syncwarp();
      if (lane == 0) mbar_arrive(BAR(pass ? B_ZST1 : B_ZST0));
      if (!pass) finish_q();
    }
    if (wg == 3) {
      asm volatile("setmaxnreg.inc.sync.aligned.u32 120;");
      int st = 0, ph = 0;
      {
        float acc[88];
#pragma unroll
        for (int k = 0; k < 88; k++) acc[k] = 0.f;
        regfence(acc);
        const uint64_t da0 = mkdesc(sb + SM_RING, 16, 1024, 1), db0 = mkdesc(sb + SM_RING + 16384, 1408, 128, 0);
        uint32_t rel;
        asm("mapa.shared::cluster.u32 %0, %1, %2;" : "=r"(rel) : "r"(BAR(B_REMPTY)), "r"(lane & 1));
        uint64_t da = da0, db = db0;
#pragma unroll 1
        for (int n = 0; n < 32; n++) {
          mbar_wait(BAR(B_RFULL) + st, ph);
#pragma unroll
          for (int k = 0; k < 4; k++) {
            if (k % SBATCH == 0) wg_fence();
            wg_ss_n88<0, 88>(acc, da + 2 * k, db + 176 * k);
            wg_ss_n88<44, 88>(acc, da + (512 + 2 * k), db + 176 * k);
            if (k % SBATCH == SBATCH - 1) { wg_commit(); wg_wait<0>(); }
          }
          if (tid < 2) asm volatile("mbarrier.arrive.shared::cluster.b64 _, [%0];" ::"r"(rel + st) : "memory");
          st += 8; da += RSTAGE / 16; db += RSTAGE / 16;
          if (st == 24) { st = 0; ph ^= 1; da = da0; db = db0; }
        }
        st = 2; ph = 0;
        regfence(acc);
        if (tid == 0) TS(11);
        mbar_wait(BAR(B_RFULL + st), ph);
        const uint8_t* zs = smem_raw + SM_RING + st * RSTAGE;
        uint32_t zmask = bj == 7 ? 0u : 0xFFFFFFFFu;
        asm volatile("" : "+r"(zmask));
        uint32_t* up = reinterpret_cast<uint32_t*>(g_u) + bi * 11 * 4096 + w * 512 + lane;
#pragma unroll
        for (int r = 0; r < 4; r++) {
          const int row = (r >> 1) * 64 + w * 16 + (r & 1) * 8 + g;
          const float og = fmaf(reinterpret_cast<const float*>(zs + 22528)[row], -0.5f, 0.5f);
          const float bs = __bfloat162float(reinterpret_cast<const __nv_bfloat16*>(zs + 23040)[row]) * og;
#pragma unroll
          for (int c8 = 0; c8 < 11; c8++) {
            const int k = (r >> 1) * 44 + c8 * 4 + (r & 1) * 2, cb = 11 * bj + c8;
            uint32_t zz = reinterpret_cast<const uint32_t*>(zs)[c8 * 512 + ((r >> 1) * 8 + w * 2 + (r & 1)) * 32 + lane];
            if (c8 >= 9) zz &= zmask;
            uint32_t v = pack_bf16(fmaf(acc[k], og, bs), fmaf(acc[k + 1], og, bs));
            asm("mul.rn.bf16x2 %0, %0, %1;" : "+r"(v) : "r"(zz));
            up[cb * 32 + (cb >> 3) * 3840 + ((r >> 1) * 8 + (r & 1)) * 256] = v;
          }
        }
        fence_async_smem();
        fence_async();
        bar_sync(4, 128);
        if (tid == 0) { mbar_arrive_both(BAR(B_REMPTY + st)); red_release(&g_ucnt[bi * 32]); TS(12); }
        if (++st == 3) { st = 0; ph ^= 1; }
      }
      float oc[64];
#pragma unroll
      for (int k = 0; k < 64; k++) oc[k] = 0.f;
      regfence(oc);
#pragma unroll 1
      for (int n = 0; n < 19; n++) {
        uint32_t sa, sw;
        if (n < 11) { mbar_wait(BAR(B_RFULL + st), ph); sa = SM_RING + st * RSTAGE; sw = sa + 16384; }
        else {
          if (n == 11) { if (tid == 0) TS(13); mbar_wait(BAR(B_WOFULL), 0); }
          mbar_wait(BAR(B_XFULL + n - 11), 1); sa = SM_K + (n - 11) * 16384; sw = SM_RING + (n - 11) * 8192 + ((n - 11) * 43 >> 7) * (RSTAGE - 24576);
        }
        const uint64_t da = mkdesc(sb + sa, 128, 1024, 0), db = mkdesc(sb + sw, 8192, 1024, 1);
#pragma unroll
        for (int k = 0; k < 4; k += 2) {
          wg_fence();
          wg_ss_n64<0, 64>(oc, da + 16 * k, db + 128 * k);
          wg_ss_n64<32, 64>(oc, da + 512 + 16 * k, db + 128 * k);
          wg_ss_n64<0, 64>(oc, da + 16 * k + 16, db + 128 * k + 128);
          wg_ss_n64<32, 64>(oc, da + 528 + 16 * k, db + 128 * k + 128);
          wg_commit();
          if (n < 11) wg_wait<0>();
        }
        if (n < 11) {
          if (tid == 0) mbar_arrive_both(BAR(B_REMPTY + st));
          if (++st == 3) { st = 0; ph ^= 1; }
        }
      }
      wg_wait<0>();
      regfence(oc);
      if (tid == 0) TS(14);
#pragma unroll
      for (int hf = 0; hf < 2; hf++) {
        const uint32_t rb = sb + SM_Q + (hf * 64 + w * 16) * 128, ra = rb + (lane & 15) * 128;
#pragma unroll
        for (int c = 0; c < 4; c++) {
          const int k = hf * 32 + c * 8;
          asm volatile("stmatrix.sync.aligned.m8n8.x4.shared.b16 [%0], {%1, %2, %3, %4};" ::"r"(ra + (((2 * c + (lane >> 4)) ^ (lane & 7)) << 4)),
                       "r"(pack_bf16(oc[k], oc[k + 1])), "r"(pack_bf16(oc[k + 2], oc[k + 3])), "r"(pack_bf16(oc[k + 4], oc[k + 5])), "r"(pack_bf16(oc[k + 6], oc[k + 7])) : "memory");
        }
        fence_async_smem();
        __syncwarp();
        asm volatile(ELECT "cp.async.bulk.tensor.2d.global.shared::cta.bulk_group [%0, {%2, %3}], [%1];\n}"
                     ::"l"(&tm_out), "r"(rb), "r"(64 * bj), "r"(bi * 128 + hf * 64 + w * 16) : "memory");
      }
      asm volatile("cp.async.bulk.commit_group;" ::: "memory");
      asm volatile("cp.async.bulk.wait_group.read 0;" ::: "memory");
      if (tid == 0) TS(15);
    } else {
      mbar_wait(BAR(B_QRDY), 0);
    if (tid == 0) TS(25 + wg);
    if (tid == 0) TS(28 + wg);
    if (threadIdx.x == 0) GTS(125);
    const uint64_t dk0 = mkdesc(sb + SM_K, 16, 256, 3);
    const uint64_t dv0 = mkdesc(sb + SM_K + 2048, SM_ONES - 2048, 256, 3);
    const int aw = wg == 0 ? 0 : 3 - wg;
    uint32_t chk = 0, pend = 0;
    uint32_t* const obase = reinterpret_cast<uint32_t*>(g_o) + (ai * 8 + aj) * 4096 + w * 512 + lane;
    const uint32_t gbase = sb + SM_G + (w * 16 + g) * 4;
    float o[12], s[32];
    uint32_t q[4], p0[16], p1[16];
    if (lds32(sb + SM_MISC + 4 * M_FAST)) {
      const uint32_t mlo = prm.mlo, mhi = prm.mhi;
      uint64_t dk = dk0, dv = dv0;
#define STEP(PIN, POUT) { wg_fence(); issue_qk(s, q, dk); dk += KSTEP; wg_commit(); issue_pv(o, PIN, dv); dv += VSTEP8; wg_commit(); \
                          wg_wait<1>(); regfence(s); softmax_step(s, POUT, mlo, mhi); wg_wait<0>(); }
      int tau = aw * 3 - (aw > 0), seg = (3 - aw) % 3;
      float4* part = g_part + blockIdx.x * 768 + tid;
#pragma unroll 1
      for (int it = 0; it < 8; it++) {
        int n2 = seg == 1 ? 6 : 5;
        if (it < 3) {
          mbar_wait(BAR(seg ? B_KVB : B_KVFULL), 0);
          mbar_wait(BAR(seg == 2 ? B_KVC : B_KVFULL), 0);
        }
#pragma unroll
        for (int k = 0; k < 32; k++) s[k] = k < NP / 2 ? MAGIC_C : 0.f;
        if (it == 0 || seg == 0) {
          const int j0 = seg == 0 ? 0 : (seg == 1 ? 10 : 22);
          dk = dk0 + KSTEP * j0;
          dv = dv0 + VSTEP8 * j0;
          const uint4 qv = lds128(sb + SM_Q + tau * 2048 + tid * 16);
          q[0] = qv.x; q[1] = qv.y; q[2] = qv.z; q[3] = qv.w;
          if (it + aw > 5 && aw < 2 && tau == aw * 3 + 2) {
            bar_sync(6 + aw, 256);
            const float4 a = part[aw * 384], b = part[aw * 384 + 128], c = part[aw * 384 + 256];
            o[0] = a.x; o[1] = a.y; o[2] = a.z; o[3] = a.w; o[4] = b.x; o[5] = b.y; o[6] = b.z; o[7] = b.w; o[8] = c.x; o[9] = c.y; o[10] = c.z; o[11] = c.w;
          } else {
#pragma unroll
            for (int k = 0; k < 12; k++) o[k] = 0.f;
          }
          regfence(s);
          wg_fence(); issue_qk(s, q, dk); dk += KSTEP; wg_commit();
          wg_wait<0>(); regfence(s);
          softmax_step(s, p0, mlo, mhi);
          regfence(o);
          STEP(p0, p1);
          n2--;
        }
        regfence(s);
#pragma unroll 1
        for (; n2 > 0; n2--) { STEP(p1, p0); STEP(p0, p1); }
        if (it == 7 || seg == 2) {
          wg_fence(); issue_pv(o, p1, dv); wg_commit();
          wg_wait<0>(); regfence(o);
          if (it < aw) {
            float4* pp = part + (aw - 1) * 384;
            pp[0] = make_float4(o[0], o[1], o[2], o[3]); pp[128] = make_float4(o[4], o[5], o[6], o[7]); pp[256] = make_float4(o[8], o[9], o[10], o[11]);
            __threadfence_block();
            bar_arrive(5 + aw, 256);
          } else {
            chk ^= pend; pend = store_o_tile(o, obase, gbase, tau, lane);
          }
        }
        if (++seg == 3) { seg = 0; tau++; }
      }
#undef STEP
    } else {
      mbar_wait(BAR(B_KFB), 0);
      constexpr float SC = 0.25f * 1.4426950408889634f;
#pragma unroll 1
      for (int tau = wg * 3; tau < wg * 3 + 3 && tau < 8; tau++) {
        const uint4 qv = lds128(sb + SM_Q + tau * 2048 + tid * 16);
        float m0 = -INFINITY, m1 = -INFINITY;
#pragma unroll
        for (int k = 0; k < 12; k++) o[k] = 0.f;
        uint64_t dv = dv0;
#pragma unroll 1
        for (int j = 0; j < 32; j++) {
          regfence(s);
          wg_fence(); wg_qkb_n64<0, 0, 32>(s, qv.x, qv.y, qv.z, qv.w, dk0 + KSTEP * j); wg_commit();
          wg_wait<0>(); regfence(s);
          float x0 = m0, x1 = m1;
#pragma unroll
          for (int k = 0; k < 32; k++) { s[k] *= SC; if (k & 2) x1 = fmaxf(x1, s[k]); else x0 = fmaxf(x0, s[k]); }
          x0 = fmaxf(x0, __shfl_xor_sync(0xffffffffu, x0, 1)); x0 = fmaxf(x0, __shfl_xor_sync(0xffffffffu, x0, 2));
          x1 = fmaxf(x1, __shfl_xor_sync(0xffffffffu, x1, 1)); x1 = fmaxf(x1, __shfl_xor_sync(0xffffffffu, x1, 2));
          const float c0 = ex2(m0 - x0), c1 = ex2(m1 - x1);
          m0 = x0; m1 = x1;
#pragma unroll
          for (int k = 0; k < 12; k++) o[k] *= (k & 2) ? c1 : c0;
#pragma unroll
          for (int k = 0; k < 16; k++) { const float m = (k & 1) ? m1 : m0; p0[k] = exp_mufu(s[2 * k] - m, s[2 * k + 1] - m); }
          regfence(o);
          wg_fence(); issue_pv(o, p0, dv); dv += VSTEP8; wg_commit();
          wg_wait<0>(); regfence(o);
        }
        { chk ^= pend; pend = store_o_tile(o, obase, gbase, tau, lane); }
      }
    }
    consume(chk ^ pend, sb);
    fence_async();
    bar_sync(1 + wg, 128);
    if (tid == 0) { red_relaxed(&g_ocnt[ai * 32]); mbar_arrive_both(BAR(B_ATT)); TS(31 + wg); if (wg == 0) GTS(124); }
    }
  }
  __syncwarp();
  asm volatile("barrier.cluster.arrive.relaxed;" ::: "memory");
  asm volatile("barrier.cluster.wait;" ::: "memory");
}

typedef CUresult (*EncodeFn)(CUtensorMap*, CUtensorMapDataType, cuuint32_t, void*, const cuuint64_t*, const cuuint64_t*,
                             const cuuint32_t*, const cuuint32_t*, CUtensorMapInterleave, CUtensorMapSwizzle,
                             CUtensorMapL2promotion, CUtensorMapFloatOOBfill);

void make_map(EncodeFn enc, CUtensorMap* tm, const void* base, uint64_t cols, uint64_t rows, uint32_t bc, uint32_t br, CUtensorMapSwizzle sw) {
  cuuint64_t gd[2] = {cols, rows};
  cuuint64_t gs[1] = {cols * 2};
  cuuint32_t bd[2] = {bc, br};
  cuuint32_t es[2] = {1, 1};
  enc(tm, CU_TENSOR_MAP_DATA_TYPE_BFLOAT16, 2, const_cast<void*>(base), gd, gs, bd, es, CU_TENSOR_MAP_INTERLEAVE_NONE, sw,
      CU_TENSOR_MAP_L2_PROMOTION_L2_128B, CU_TENSOR_MAP_FLOAT_OOB_FILL_NONE);
}

}

extern "C" void kernel_launch(void* const* d_in, const int* in_sizes, int n_in, void* d_out, int out_size) {
  (void)in_sizes; (void)n_in; (void)out_size;
  static EncodeFn enc = nullptr;
  if (!enc) {
    void* fn = nullptr;
    cudaDriverEntryPointQueryResult qr;
    cudaGetDriverEntryPoint("cuTensorMapEncodeTiled", &fn, cudaEnableDefault, &qr);
    enc = (EncodeFn)fn;
    cudaFuncSetAttribute(fused_kernel, cudaFuncAttributeMaxDynamicSharedMemorySize, SMEM_BYTES);
  }
  CUtensorMap tx, tq, tin, tsp, tout, to, ty;
  make_map(enc, &ty, d_out, 512, 2048, 64, 16, CU_TENSOR_MAP_SWIZZLE_128B);
  make_map(enc, &tx, d_in[0], 512, 2048, 64, 128, CU_TENSOR_MAP_SWIZZLE_128B);
  make_map(enc, &tq, d_in[1], 512, 512, 32, 32, CU_TENSOR_MAP_SWIZZLE_64B);
  make_map(enc, &to, d_in[4], 512, 512, 64, 64, CU_TENSOR_MAP_SWIZZLE_128B);
  {
    cuuint64_t gd[3] = {32, 512, 43};
    cuuint64_t gs[2] = {1376 * 2, 64};
    cuuint32_t bd[3] = {32, 32, 3};
    cuuint32_t es[3] = {1, 1, 1};
    enc(&tin, CU_TENSOR_MAP_DATA_TYPE_BFLOAT16, 3, d_in[6], gd, gs, bd, es, CU_TENSOR_MAP_INTERLEAVE_NONE, CU_TENSOR_MAP_SWIZZLE_64B,
        CU_TENSOR_MAP_L2_PROMOTION_L2_128B, CU_TENSOR_MAP_FLOAT_OOB_FILL_NONE);
  }
  make_map(enc, &tsp, d_in[7], 2048, 2048, 64, 64, CU_TENSOR_MAP_SWIZZLE_128B);
  make_map(enc, &tout, d_in[9], 512, 688, 64, 64, CU_TENSOR_MAP_SWIZZLE_128B);
  Params prm;
  prm.gate_w = (const __nv_bfloat16*)d_in[10];
  prm.b_sp = (const __nv_bfloat16*)d_in[8];
  prm.w_out = (const __nv_bfloat16*)d_in[9];
  prm.wo = (const __nv_bfloat16*)d_in[4];
  prm.w_in = (const __nv_bfloat16*)d_in[6];
  prm.wq = (const __nv_bfloat16*)d_in[1];
  prm.wk = (const __nv_bfloat16*)d_in[2];
  prm.wv = (const __nv_bfloat16*)d_in[3];
  prm.mlo = 0x007F007Fu;
  prm.mhi = 0xFF80FF80u;
  fused_kernel<<<NCTA, NTHREADS, SMEM_BYTES>>>(tx, tq, tin, tsp, tout, to, ty, prm);
}
```

```cpp
#include <cuda_runtime.h>
#include <cuda.h>
#include <cuda_bf16.h>
#include <cuda_fp16.h>
#include <stdint.h>

namespace {

constexpr int NCTA = 128;
constexpr int NTHREADS = 640;
#define NPOLY 40
constexpr int NP = NPOLY;
constexpr int SPIN_LIMIT = 1 << 18;
#define SBATCH 1

constexpr uint32_t SM_K = 0;
constexpr uint32_t SM_ONES = 131072;
constexpr uint32_t KV_BYTES = 131072;
constexpr uint32_t SM_BAR = 131584;
constexpr uint32_t SM_RING = 132096;
constexpr uint32_t RSTAGE = 27648;
constexpr uint32_t WSLOT = 16384;
constexpr uint32_t SM_WKV = SM_RING + 4 * WSLOT;
constexpr uint32_t SM_GW = SM_WKV + 16384;
constexpr uint32_t SM_Q = 215040;
constexpr uint32_t SM_G = 231424;
constexpr uint32_t SM_MISC = 231936;
constexpr uint32_t SMEM_BYTES = 232448;

constexpr int B_XFULL = 0, B_XEMPTY = 8, B_WFULL = 16, B_WEMPTY = 32, B_RFULL = 44, B_REMPTY = 47, B_KVFULL = 50,
              B_KFB = 51, B_KSTAT = 52, B_DEC = 53, B_ZST0 = 43, B_ZST1 = 63, B_WOFULL = 54, B_EPOCH = 55, B_ZOK = 56, B_Z1OK = 57, B_ATT = 58, B_QRDY = 59, B_LNOK = 60, B_KVB = 61, B_KVC = 62;
constexpr int M_EPOCH = 0, M_KN2 = 1, M_VOK = 2, M_FAST = 3, M_KVR = 4, M_MASK = 8, M_RED = 16;

__device__ uint4 g_kimg[KV_BYTES / 16];
__device__ uint4 g_kbf[65536 / 16];
__device__ unsigned long long g_kvflag[NCTA];
__device__ uint4 g_lnstat[16 * 8 * 128];
__device__ float g_gate[2048];
__device__ uint4 g_z2n[8 * 32 * 11264 / 16];
__device__ uint4 g_z1[16 * 88 * 128];
__device__ uint4 g_u[16 * 11 * 1024];
__device__ uint4 g_o[16 * 8 * 1024];
__device__ float4 g_part[NCTA * 2 * 3 * 128];
__device__ unsigned g_ticket;
__device__ unsigned g_zcnt[16 * 32];
__device__ unsigned g_z1cnt[16 * 32];
__device__ unsigned g_ucnt[16 * 32];
__device__ unsigned g_ocnt[2 * 16 * 32];
#define TS(k) do { } while (0)
#define GTS(k) do { } while (0)

__device__ __forceinline__ void mbar_init(uint32_t a, uint32_t c) { asm volatile("mbarrier.init.shared::cta.b64 [%0], %1;" ::"r"(a), "r"(c) : "memory"); }
__device__ __forceinline__ void mbar_arrive(uint32_t a) { asm volatile("mbarrier.arrive.shared::cta.b64 _, [%0];" ::"r"(a) : "memory"); }
__device__ __forceinline__ void mbar_arrive_both(uint32_t a) {
  asm volatile("{\n.reg .b32 ra;\nmapa.shared::cluster.u32 ra, %0, 0;\nmbarrier.arrive.shared::cluster.b64 _, [ra];\n"
               "mapa.shared::cluster.u32 ra, %0, 1;\nmbarrier.arrive.shared::cluster.b64 _, [ra];\n}" ::"r"(a) : "memory");
}
__device__ __forceinline__ void mbar_wait(uint32_t a, uint32_t ph) {
  uint32_t ok;
#pragma unroll 1
  for (int n = 0; n < SPIN_LIMIT; n++) {
    asm volatile("{\n.reg .pred p;\nmbarrier.try_wait.parity.shared::cta.b64 p, [%1], %2;\nselp.u32 %0, 1, 0, p;\n}" : "=r"(ok) : "r"(a), "r"(ph) : "memory");
    if (ok) break;
  }
}
#define ELECT "{\n.reg .pred p;\nelect.sync _|p, 0xffffffff;\n@p "
__device__ __forceinline__ void e_expect(uint32_t a, uint32_t b) { asm volatile(ELECT "mbarrier.arrive.expect_tx.shared::cta.b64 _, [%0], %1;\n}" ::"r"(a), "r"(b) : "memory"); }
__device__ __forceinline__ void e_arrive(uint32_t a) { asm volatile(ELECT "mbarrier.arrive.shared::cta.b64 _, [%0];\n}" ::"r"(a) : "memory"); }
__device__ __forceinline__ void tma2d(uint32_t dst, const CUtensorMap* tm, int c0, int c1, uint32_t bar) {
  asm volatile(ELECT "cp.async.bulk.tensor.2d.shared::cluster.global.mbarrier::complete_tx::bytes [%0], [%1, {%3, %4}], [%2];\n}"
               ::"r"(dst), "l"(tm), "r"(bar), "r"(c0), "r"(c1) : "memory");
}
__device__ __forceinline__ void tma2d_mc(uint32_t dst, const CUtensorMap* tm, int c0, int c1, uint32_t bar) {
  asm volatile(ELECT "cp.async.bulk.tensor.2d.shared::cluster.global.mbarrier::complete_tx::bytes.multicast::cluster [%0], [%1, {%3, %4}], [%2], %5;\n}"
               ::"r"(dst), "l"(tm), "r"(bar), "r"(c0), "r"(c1), "h"((uint16_t)3) : "memory");
}
__device__ __forceinline__ void tma3d(uint32_t dst, const CUtensorMap* tm, int c0, int c1, int c2, uint32_t bar) {
  asm volatile(ELECT "cp.async.bulk.tensor.3d.shared::cluster.global.mbarrier::complete_tx::bytes [%0], [%1, {%3, %4, %5}], [%2];\n}"
               ::"r"(dst), "l"(tm), "r"(bar), "r"(c0), "r"(c1), "r"(c2) : "memory");
}
__device__ __forceinline__ void tma3d_mc(uint32_t dst, const CUtensorMap* tm, int c0, int c1, int c2, uint32_t bar) {
  asm volatile(ELECT "cp.async.bulk.tensor.3d.shared::cluster.global.mbarrier::complete_tx::bytes.multicast::cluster [%0], [%1, {%3, %4, %5}], [%2], %6;\n}"
               ::"r"(dst), "l"(tm), "r"(bar), "r"(c0), "r"(c1), "r"(c2), "h"((uint16_t)3) : "memory");
}
__device__ __forceinline__ void tma2d_pf(const CUtensorMap* tm, int c0, int c1) {
  asm volatile(ELECT "cp.async.bulk.prefetch.tensor.2d.L2.global [%0, {%1, %2}];\n}" ::"l"(tm), "r"(c0), "r"(c1) : "memory");
}
__device__ __forceinline__ void tm_prefetch(const CUtensorMap* tm) { asm volatile(ELECT "prefetch.tensormap [%0];\n}" ::"l"(tm) : "memory"); }
__device__ __forceinline__ void bulk(uint32_t dst, const void* src, uint32_t bytes, uint32_t bar) {
  asm volatile(ELECT "cp.async.bulk.shared::cluster.global.mbarrier::complete_tx::bytes [%0], [%1], %2, [%3];\n}"
               ::"r"(dst), "l"(src), "r"(bytes), "r"(bar) : "memory");
}
__device__ __forceinline__ void bulk_mc(uint32_t dst, const void* src, uint32_t bytes, uint32_t bar) {
  asm volatile(ELECT "cp.async.bulk.shared::cluster.global.mbarrier::complete_tx::bytes.multicast::cluster [%0], [%1], %2, [%3], %4;\n}"
               ::"r"(dst), "l"(src), "r"(bytes), "r"(bar), "h"((uint16_t)3) : "memory");
}
__device__ __forceinline__ void l2_prefetch(const void* src, uint32_t bytes) { asm volatile(ELECT "cp.async.bulk.prefetch.L2.global [%0], %1;\n}" ::"l"(src), "r"(bytes) : "memory"); }
__device__ __forceinline__ void fence_async() { asm volatile("fence.proxy.async.global;" ::: "memory"); }
__device__ __forceinline__ void fence_async_smem() { asm volatile("fence.proxy.async.shared::cta;" ::: "memory"); }
__device__ __forceinline__ void bar_sync(int id, int n) { asm volatile("bar.sync %0, %1;" ::"r"(id), "r"(n) : "memory"); }
__device__ __forceinline__ void bar_arrive(int id, int n) { asm volatile("bar.arrive %0, %1;" ::"r"(id), "r"(n) : "memory"); }
__device__ __forceinline__ void red_release(unsigned* p) { asm volatile("red.release.gpu.global.add.u32 [%0], 1;" ::"l"(p) : "memory"); }
__device__ __forceinline__ void red_relaxed(unsigned* p) { asm volatile("red.relaxed.gpu.global.add.u32 [%0], 1;" ::"l"(p) : "memory"); }
__device__ __forceinline__ uint32_t ld_back(const void* p) { uint32_t v; asm volatile("ld.relaxed.gpu.global.u32 %0, [%1];" : "=r"(v) : "l"(p) : "memory"); return v; }
__device__ __forceinline__ void consume(uint32_t v, uint32_t sb) { if (v == 0xDEADBEEFu) asm volatile("st.shared.u32 [%0], %1;" ::"r"(sb + SM_MISC + 60), "r"(v) : "memory"); }
__device__ __forceinline__ unsigned ld_acquire(const unsigned* p) { unsigned v; asm volatile("ld.acquire.gpu.global.u32 %0, [%1];" : "=r"(v) : "l"(p) : "memory"); return v; }
__device__ __forceinline__ void wait_ge(const unsigned* p, unsigned target) {
#pragma unroll 1
  for (int n = 0; n < SPIN_LIMIT; n++) {
    if ((int)(ld_acquire(p) - target) >= 0) break;
    __nanosleep(100);
  }
}
__device__ __forceinline__ void wg_fence() { asm volatile("wgmma.fence.sync.aligned;" ::: "memory"); }
__device__ __forceinline__ void wg_commit() { asm volatile("wgmma.commit_group.sync.aligned;" ::: "memory"); }
template <int N> __device__ __forceinline__ void wg_wait() { asm volatile("wgmma.wait_group.sync.aligned %0;" ::"n"(N) : "memory"); }
template <int n> __device__ __forceinline__ void regfence(float (&d)[n]) {
#pragma unroll
  for (int i = 0; i < n; i++) asm volatile("" : "+f"(d[i])::"memory");
}
__device__ __forceinline__ uint64_t mkdesc(uint32_t addr, uint32_t lbo, uint32_t sbo, int swz) {
  return (uint64_t)((addr & 0x3FFFF) >> 4) | ((uint64_t)(lbo >> 4) << 16) | ((uint64_t)(sbo >> 4) << 32) | ((uint64_t)swz << 62);
}
__device__ __forceinline__ uint32_t pack_bf16(float lo, float hi) { uint32_t r; asm("cvt.rn.bf16x2.f32 %0, %1, %2;" : "=r"(r) : "f"(hi), "f"(lo)); return r; }
__device__ __forceinline__ uint32_t pack_f16(float lo, float hi) { uint32_t r; asm("cvt.rn.f16x2.f32 %0, %1, %2;" : "=r"(r) : "f"(hi), "f"(lo)); return r; }
__device__ __forceinline__ float bf_lo(uint32_t v) { return __uint_as_float(v << 16); }
__device__ __forceinline__ float bf_hi(uint32_t v) { return __uint_as_float(v & 0xFFFF0000u); }
__device__ __forceinline__ float ex2(float x) { float r; asm("ex2.approx.ftz.f32 %0, %1;" : "=f"(r) : "f"(x)); return r; }
__device__ __forceinline__ float gelu2_tanh(float x) {
  float u = x * fmaf(x * x, 0.0356774081f, 0.7978845608f), t;
  asm("tanh.approx.f32 %0, %1;" : "=f"(t) : "f"(u));
  return fmaf(x, t, x);
}
__device__ __forceinline__ void sts32(uint32_t a, uint32_t v) { asm volatile("st.shared.u32 [%0], %1;" ::"r"(a), "r"(v) : "memory"); }
__device__ __forceinline__ void sts16(uint32_t a, uint16_t v) { asm volatile("st.shared.u16 [%0], %1;" ::"r"(a), "h"(v) : "memory"); }
__device__ __forceinline__ void sts128(uint32_t a, uint32_t x, uint32_t y, uint32_t z, uint32_t w) { asm volatile("st.shared.v4.u32 [%0], {%1,%2,%3,%4};" ::"r"(a), "r"(x), "r"(y), "r"(z), "r"(w) : "memory"); }
__device__ __forceinline__ uint32_t lds32(uint32_t a) { uint32_t v; asm volatile("ld.shared.u32 %0, [%1];" : "=r"(v) : "r"(a) : "memory"); return v; }
__device__ __forceinline__ float ldsf(uint32_t a) { return __uint_as_float(lds32(a)); }
__device__ __forceinline__ uint4 lds128(uint32_t a) { uint4 v; asm volatile("ld.shared.v4.u32 {%0,%1,%2,%3}, [%4];" : "=r"(v.x), "=r"(v.y), "=r"(v.z), "=r"(v.w) : "r"(a) : "memory"); return v; }

template<int OFF, int TOT> __device__ __forceinline__ void wg_ss_n88(float (&d)[TOT], uint64_t da, uint64_t db) {
  asm volatile("wgmma.mma_async.sync.aligned.m64n88k16.f32.bf16.bf16 {%0, %1, %2, %3, %4, %5, %6, %7, %8, %9, %10, %11, %12, %13, %14, %15, %16, %17, %18, %19, %20, %21, %22, %23, %24, %25, %26, %27, %28, %29, %30, %31, %32, %33, %34, %35, %36, %37, %38, %39, %40, %41, %42, %43}, %44, %45, 1, 1, 1, 0, 1;"
    : "+f"(d[OFF+0]), "+f"(d[OFF+1]), "+f"(d[OFF+2]), "+f"(d[OFF+3]), "+f"(d[OFF+4]), "+f"(d[OFF+5]), "+f"(d[OFF+6]), "+f"(d[OFF+7]),
      "+f"(d[OFF+8]), "+f"(d[OFF+9]), "+f"(d[OFF+10]), "+f"(d[OFF+11]), "+f"(d[OFF+12]), "+f"(d[OFF+13]), "+f"(d[OFF+14]), "+f"(d[OFF+15]),
      "+f"(d[OFF+16]), "+f"(d[OFF+17]), "+f"(d[OFF+18]), "+f"(d[OFF+19]), "+f"(d[OFF+20]), "+f"(d[OFF+21]), "+f"(d[OFF+22]), "+f"(d[OFF+23]),
      "+f"(d[OFF+24]), "+f"(d[OFF+25]), "+f"(d[OFF+26]), "+f"(d[OFF+27]), "+f"(d[OFF+28]), "+f"(d[OFF+29]), "+f"(d[OFF+30]), "+f"(d[OFF+31]),
      "+f"(d[OFF+32]), "+f"(d[OFF+33]), "+f"(d[OFF+34]), "+f"(d[OFF+35]), "+f"(d[OFF+36]), "+f"(d[OFF+37]), "+f"(d[OFF+38]), "+f"(d[OFF+39]),
      "+f"(d[OFF+40]), "+f"(d[OFF+41]), "+f"(d[OFF+42]), "+f"(d[OFF+43])
    : "l"(da), "l"(db));
}
template<int OFF, int TOT> __device__ __forceinline__ void wg_ss_n128(float (&d)[TOT], uint64_t da, uint64_t db) {
  asm volatile("wgmma.mma_async.sync.aligned.m64n128k16.f32.bf16.bf16 {%0, %1, %2, %3, %4, %5, %6, %7, %8, %9, %10, %11, %12, %13, %14, %15, %16, %17, %18, %19, %20, %21, %22, %23, %24, %25, %26, %27, %28, %29, %30, %31, %32, %33, %34, %35, %36, %37, %38, %39, %40, %41, %42, %43, %44, %45, %46, %47, %48, %49, %50, %51, %52, %53, %54, %55, %56, %57, %58, %59, %60, %61, %62, %63}, %64, %65, 1, 1, 1, 0, 1;"
    : "+f"(d[OFF+0]), "+f"(d[OFF+1]), "+f"(d[OFF+2]), "+f"(d[OFF+3]), "+f"(d[OFF+4]), "+f"(d[OFF+5]), "+f"(d[OFF+6]), "+f"(d[OFF+7]),
      "+f"(d[OFF+8]), "+f"(d[OFF+9]), "+f"(d[OFF+10]), "+f"(d[OFF+11]), "+f"(d[OFF+12]), "+f"(d[OFF+13]), "+f"(d[OFF+14]), "+f"(d[OFF+15]),
      "+f"(d[OFF+16]), "+f"(d[OFF+17]), "+f"(d[OFF+18]), "+f"(d[OFF+19]), "+f"(d[OFF+20]), "+f"(d[OFF+21]), "+f"(d[OFF+22]), "+f"(d[OFF+23]),
      "+f"(d[OFF+24]), "+f"(d[OFF+25]), "+f"(d[OFF+26]), "+f"(d[OFF+27]), "+f"(d[OFF+28]), "+f"(d[OFF+29]), "+f"(d[OFF+30]), "+f"(d[OFF+31]),
      "+f"(d[OFF+32]), "+f"(d[OFF+33]), "+f"(d[OFF+34]), "+f"(d[OFF+35]), "+f"(d[OFF+36]), "+f"(d[OFF+37]), "+f"(d[OFF+38]), "+f"(d[OFF+39]),
      "+f"(d[OFF+40]), "+f"(d[OFF+41]), "+f"(d[OFF+42]), "+f"(d[OFF+43]), "+f"(d[OFF+44]), "+f"(d[OFF+45]), "+f"(d[OFF+46]), "+f"(d[OFF+47]),
      "+f"(d[OFF+48]), "+f"(d[OFF+49]), "+f"(d[OFF+50]), "+f"(d[OFF+51]), "+f"(d[OFF+52]), "+f"(d[OFF+53]), "+f"(d[OFF+54]), "+f"(d[OFF+55]),
      "+f"(d[OFF+56]), "+f"(d[OFF+57]), "+f"(d[OFF+58]), "+f"(d[OFF+59]), "+f"(d[OFF+60]), "+f"(d[OFF+61]), "+f"(d[OFF+62]), "+f"(d[OFF+63])
    : "l"(da), "l"(db));
}
template<int OFF, int TOT> __device__ __forceinline__ void wg_ss_n64(float (&d)[TOT], uint64_t da, uint64_t db) {
  asm volatile("wgmma.mma_async.sync.aligned.m64n64k16.f32.bf16.bf16 {%0, %1, %2, %3, %4, %5, %6, %7, %8, %9, %10, %11, %12, %13, %14, %15, %16, %17, %18, %19, %20, %21, %22, %23, %24, %25, %26, %27, %28, %29, %30, %31}, %32, %33, 1, 1, 1, 0, 1;"
    : "+f"(d[OFF+0]), "+f"(d[OFF+1]), "+f"(d[OFF+2]), "+f"(d[OFF+3]), "+f"(d[OFF+4]), "+f"(d[OFF+5]), "+f"(d[OFF+6]), "+f"(d[OFF+7]),
      "+f"(d[OFF+8]), "+f"(d[OFF+9]), "+f"(d[OFF+10]), "+f"(d[OFF+11]), "+f"(d[OFF+12]), "+f"(d[OFF+13]), "+f"(d[OFF+14]), "+f"(d[OFF+15]),
      "+f"(d[OFF+16]), "+f"(d[OFF+17]), "+f"(d[OFF+18]), "+f"(d[OFF+19]), "+f"(d[OFF+20]), "+f"(d[OFF+21]), "+f"(d[OFF+22]), "+f"(d[OFF+23]),
      "+f"(d[OFF+24]), "+f"(d[OFF+25]), "+f"(d[OFF+26]), "+f"(d[OFF+27]), "+f"(d[OFF+28]), "+f"(d[OFF+29]), "+f"(d[OFF+30]), "+f"(d[OFF+31])
    : "l"(da), "l"(db));
}
template<int OFF, int TOT> __device__ __forceinline__ void wg_ss_n32t(float (&d)[TOT], uint64_t da, uint64_t db) {
  asm volatile("wgmma.mma_async.sync.aligned.m64n32k16.f32.bf16.bf16 {%0, %1, %2, %3, %4, %5, %6, %7, %8, %9, %10, %11, %12, %13, %14, %15}, %16, %17, 1, 1, 1, 1, 0;"
    : "+f"(d[OFF+0]), "+f"(d[OFF+1]), "+f"(d[OFF+2]), "+f"(d[OFF+3]), "+f"(d[OFF+4]), "+f"(d[OFF+5]), "+f"(d[OFF+6]), "+f"(d[OFF+7]),
      "+f"(d[OFF+8]), "+f"(d[OFF+9]), "+f"(d[OFF+10]), "+f"(d[OFF+11]), "+f"(d[OFF+12]), "+f"(d[OFF+13]), "+f"(d[OFF+14]), "+f"(d[OFF+15])
    : "l"(da), "l"(db));
}
template<int OFF, int TOT> __device__ __forceinline__ void wg_ss_n8(float (&d)[TOT], uint64_t da, uint64_t db) {
  asm volatile("wgmma.mma_async.sync.aligned.m64n8k16.f32.bf16.bf16 {%0, %1, %2, %3}, %4, %5, 1, 1, 1, 0, 0;"
    : "+f"(d[OFF+0]), "+f"(d[OFF+1]), "+f"(d[OFF+2]), "+f"(d[OFF+3])
    : "l"(da), "l"(db));
}
template<int SCD, int OFF, int TOT> __device__ __forceinline__ void wg_qk_n64(float (&d)[TOT], uint32_t a0, uint32_t a1, uint32_t a2, uint32_t a3, uint64_t db) {
  asm volatile("wgmma.mma_async.sync.aligned.m64n64k16.f32.f16.f16 {%0, %1, %2, %3, %4, %5, %6, %7, %8, %9, %10, %11, %12, %13, %14, %15, %16, %17, %18, %19, %20, %21, %22, %23, %24, %25, %26, %27, %28, %29, %30, %31}, {%32,%33,%34,%35}, %36, %37, 1, 1, 0;"
    : "+f"(d[OFF+0]), "+f"(d[OFF+1]), "+f"(d[OFF+2]), "+f"(d[OFF+3]), "+f"(d[OFF+4]), "+f"(d[OFF+5]), "+f"(d[OFF+6]), "+f"(d[OFF+7]),
      "+f"(d[OFF+8]), "+f"(d[OFF+9]), "+f"(d[OFF+10]), "+f"(d[OFF+11]), "+f"(d[OFF+12]), "+f"(d[OFF+13]), "+f"(d[OFF+14]), "+f"(d[OFF+15]),
      "+f"(d[OFF+16]), "+f"(d[OFF+17]), "+f"(d[OFF+18]), "+f"(d[OFF+19]), "+f"(d[OFF+20]), "+f"(d[OFF+21]), "+f"(d[OFF+22]), "+f"(d[OFF+23]),
      "+f"(d[OFF+24]), "+f"(d[OFF+25]), "+f"(d[OFF+26]), "+f"(d[OFF+27]), "+f"(d[OFF+28]), "+f"(d[OFF+29]), "+f"(d[OFF+30]), "+f"(d[OFF+31])
    : "r"(a0), "r"(a1), "r"(a2), "r"(a3), "l"(db), "n"(SCD));
}
template<int SCD, int OFF, int TOT> __device__ __forceinline__ void wg_pv_n24(float (&d)[TOT], uint32_t a0, uint32_t a1, uint32_t a2, uint32_t a3, uint64_t db) {
  asm volatile("wgmma.mma_async.sync.aligned.m64n24k16.f32.bf16.bf16 {%0, %1, %2, %3, %4, %5, %6, %7, %8, %9, %10, %11}, {%12,%13,%14,%15}, %16, %17, 1, 1, 1;"
    : "+f"(d[OFF+0]), "+f"(d[OFF+1]), "+f"(d[OFF+2]), "+f"(d[OFF+3]), "+f"(d[OFF+4]), "+f"(d[OFF+5]), "+f"(d[OFF+6]), "+f"(d[OFF+7]),
      "+f"(d[OFF+8]), "+f"(d[OFF+9]), "+f"(d[OFF+10]), "+f"(d[OFF+11])
    : "r"(a0), "r"(a1), "r"(a2), "r"(a3), "l"(db), "n"(SCD));
}
template<int SCD, int OFF, int TOT> __device__ __forceinline__ void wg_qkb_n64(float (&d)[TOT], uint32_t a0, uint32_t a1, uint32_t a2, uint32_t a3, uint64_t db) {
  asm volatile("wgmma.mma_async.sync.aligned.m64n64k16.f32.bf16.bf16 {%0, %1, %2, %3, %4, %5, %6, %7, %8, %9, %10, %11, %12, %13, %14, %15, %16, %17, %18, %19, %20, %21, %22, %23, %24, %25, %26, %27, %28, %29, %30, %31}, {%32,%33,%34,%35}, %36, %37, 1, 1, 0;"
    : "+f"(d[OFF+0]), "+f"(d[OFF+1]), "+f"(d[OFF+2]), "+f"(d[OFF+3]), "+f"(d[OFF+4]), "+f"(d[OFF+5]), "+f"(d[OFF+6]), "+f"(d[OFF+7]),
      "+f"(d[OFF+8]), "+f"(d[OFF+9]), "+f"(d[OFF+10]), "+f"(d[OFF+11]), "+f"(d[OFF+12]), "+f"(d[OFF+13]), "+f"(d[OFF+14]), "+f"(d[OFF+15]),
      "+f"(d[OFF+16]), "+f"(d[OFF+17]), "+f"(d[OFF+18]), "+f"(d[OFF+19]), "+f"(d[OFF+20]), "+f"(d[OFF+21]), "+f"(d[OFF+22]), "+f"(d[OFF+23]),
      "+f"(d[OFF+24]), "+f"(d[OFF+25]), "+f"(d[OFF+26]), "+f"(d[OFF+27]), "+f"(d[OFF+28]), "+f"(d[OFF+29]), "+f"(d[OFF+30]), "+f"(d[OFF+31])
    : "r"(a0), "r"(a1), "r"(a2), "r"(a3), "l"(db), "n"(SCD));
}

__device__ __forceinline__ uint32_t exp_mufu(float a, float b) { return pack_bf16(ex2(a), ex2(b)); }
__device__ __forceinline__ uint32_t exp_poly(float a, float b, uint32_t mlo, uint32_t mhi) {
  uint32_t u = __byte_perm(__float_as_uint(a), __float_as_uint(b), 0x6521), mh, e, p;
  asm("lop3.b32 %0, %1, %2, 0x3F003F00, 0xEA;" : "=r"(mh) : "r"(u), "r"(mlo));
  asm("lop3.b32 %0, %1, %2, 0x00020002, 0xEA;" : "=r"(e) : "r"(u), "r"(mhi));
  asm("fma.rn.bf16x2 %0, %1, %2, %3;" : "=r"(p) : "r"(u), "r"(mh), "r"(e));
  return p;
}
constexpr float MAGIC_C = 48948.0625f;
constexpr float QSCALE = 0.25f * 1.4426950408889634f * 8.f;
constexpr float BOUND = 80.f;

__device__ __forceinline__ void softmax_step(const float (&s)[32], uint32_t (&p)[16], uint32_t mlo, uint32_t mhi) {
  constexpr int PP = NP / 4;
  int ip = 0, im = PP;
#pragma unroll
  for (int i = 0; i < 16; i++) {
    if (((i + 1) * PP / 16) > (i * PP / 16)) { p[ip] = exp_poly(s[2 * ip], s[2 * ip + 1], mlo, mhi); ip++; }
    else { p[im] = exp_mufu(s[2 * im], s[2 * im + 1]); im++; }
  }
}
constexpr int64_t VSTEP = 32 - (32 << 16);
constexpr uint64_t VSTEP8 = (uint64_t)(8 * VSTEP);
constexpr uint64_t KOFF = (uint64_t)(-128ll);
__device__ __forceinline__ void issue_qk(float (&s)[32], const uint32_t (&q)[4], uint64_t dk) { wg_qk_n64<1, 0, 32>(s, q[0], q[1], q[2], q[3], dk); }
__device__ __forceinline__ void issue_pv(float (&o)[12], const uint32_t (&p)[16], uint64_t dv) {
#pragma unroll
  for (int c = 0; c < 4; c++) { wg_pv_n24<1, 0, 12>(o, p[4 * c], p[4 * c + 1], p[4 * c + 2], p[4 * c + 3], dv + c * VSTEP); }
}

__device__ __forceinline__ uint32_t wslot(int f) { const int r = f - 5 * ((f * 52) >> 8); return r == 4 ? SM_Q : SM_RING + r * WSLOT; }

struct Params {
  const __nv_bfloat16* gate_w;
  const __nv_bfloat16* b_sp;
  const __nv_bfloat16* w_out;
  const __nv_bfloat16* wo;
  const __nv_bfloat16* w_in;
  const __nv_bfloat16* wq;
  const __nv_bfloat16* wk;
  const __nv_bfloat16* wv;
};

__device__ __forceinline__ float rcp(float x) { float r; asm("rcp.approx.ftz.f32 %0, %1;" : "=f"(r) : "f"(x)); return r; }
__device__ __forceinline__ int tile_of(int tau) { return (0x74632510u >> (4 * tau)) & 7; }
__device__ __forceinline__ uint32_t store_o_tile(const float (&o)[12], uint32_t* obase, uint32_t gbase, int lam, int lane) {
  const float f0 = ldsf(gbase + (lam & 1) * 256) * rcp(o[8]), f1 = ldsf(gbase + (lam & 1) * 256 + 32) * rcp(o[10]);
  uint32_t* dst = obase + lam * 4096;
  dst[0] = pack_bf16(o[0] * f0, o[1] * f0);
  dst[32] = pack_bf16(o[4] * f0, o[5] * f0);
  dst[64] = pack_bf16(o[2] * f1, o[3] * f1);
  dst[96] = pack_bf16(o[6] * f1, o[7] * f1);
  return ld_back(dst + (lane & 15) * 8 - lane);
}

__global__ void __cluster_dims__(2, 1, 1) __launch_bounds__(NTHREADS, 1)
fused_kernel(const __grid_constant__ CUtensorMap tm_x, const __grid_constant__ CUtensorMap tm_wq,
             const __grid_constant__ CUtensorMap tm_win, const __grid_constant__ CUtensorMap tm_wsp,
             const __grid_constant__ CUtensorMap tm_wout, const __grid_constant__ CUtensorMap tm_wo,
             const __grid_constant__ CUtensorMap tm_out, const Params prm) {
  extern __shared__ __align__(1024) uint8_t smem_raw[];
  const uint32_t sb = __shfl_sync(0xffffffffu, (uint32_t)__cvta_generic_to_shared(smem_raw), 0);
  const int warp = __shfl_sync(0xffffffffu, (int)(threadIdx.x >> 5), 0);
  const int wg = warp >> 2;
  const int tid = threadIdx.x & 127;
  const int lane = threadIdx.x & 31;
  const int rank = blockIdx.x & 1;
  const int ai = (blockIdx.x >> 4) * 2 + rank, aj = (blockIdx.x >> 1) & 7;
  const int bi = blockIdx.x >> 3, bj = blockIdx.x & 7;
  auto BAR = [&](int k) { return sb + SM_BAR + 8u * k; };

  if (warp == 16) {
    if (lane == 0) {
      mbar_init(BAR(B_XFULL), 1); mbar_init(BAR(B_XFULL + 1), 1);
      asm volatile("fence.mbarrier_init.release.cluster;" ::: "memory");
    }
    __syncwarp();
    e_expect(BAR(B_XFULL), 16384);
    tma2d(sb + SM_K, &tm_x, 0, ai * 128, BAR(B_XFULL));
    e_expect(BAR(B_XFULL + 1), 16384);
    tma2d(sb + SM_K + 16384, &tm_x, 64, ai * 128, BAR(B_XFULL + 1));
    if (lane == 0) TS(36);
  } else if (warp == 18) {
    if (lane == 0) { mbar_init(BAR(B_WFULL), 1); asm volatile("fence.mbarrier_init.release.cluster;" ::: "memory"); }
    __syncwarp();
    e_expect(BAR(B_WFULL), 16384);
#pragma unroll
    for (int h = 0; h < 2; h++) {
      tma3d(sb + SM_RING + h * 8192, &tm_win, 0, h * 32, aj < 6 ? 21 + 3 * aj : 27 + 2 * aj, BAR(B_WFULL));
      tma2d(sb + SM_RING + h * 8192 + 6144, &tm_wq, 64 * aj, h * 32, BAR(B_WFULL));
    }
  } else if (warp == 19) {
    l2_prefetch(reinterpret_cast<const uint8_t*>(prm.w_in) + blockIdx.x * 11008, 11008);
    l2_prefetch(reinterpret_cast<const uint8_t*>(prm.wq) + blockIdx.x * 4096, 4096);
  } else if (warp < 16 && lane == 0) {
#pragma unroll
    for (int r = 0; r < 4; r++) {
      const int k = warp + 16 * r;
      uint32_t cnt = 1;
      if (k >= B_XEMPTY && k < B_XEMPTY + 8) cnt = 4;
      if (k >= B_WEMPTY && k < B_WEMPTY + 11) cnt = 4;
      if (k == B_ZST0 || k == B_ZST1) cnt = 8;
      if (k >= B_REMPTY && k < B_REMPTY + 3) cnt = 2;
      if (k == B_ATT) cnt = 6;
      if (k == B_QRDY) cnt = 16;
      if (k == B_KSTAT) cnt = 17;
      if (k == B_LNOK) cnt = 8;
      if (k == B_WOFULL) cnt = 3;
      if (k >= 2 && k != B_WFULL) mbar_init(BAR(k), cnt);
    }
    asm volatile("fence.mbarrier_init.release.cluster;" ::: "memory");
  }
  __syncthreads();
  if (threadIdx.x == 0) TS(35);
  asm volatile("barrier.cluster.arrive.relaxed.aligned;" ::: "memory");
  asm volatile("barrier.cluster.wait.acquire.aligned;" ::: "memory");

  if (wg == 4) {
    asm volatile("setmaxnreg.dec.sync.aligned.u32 24;");
    if (warp == 18) {
#pragma unroll 1
      for (int f = 1; f < 16; f++) {
        if (f == 1 && lane == 0) TS(0);
        if (f == 5 && lane == 0) TS(37);
        if (f >= 5) mbar_wait(BAR(B_WEMPTY + f - 5), 0);
        const uint32_t dst = sb + wslot(f) + rank * 8192, bar = BAR(B_WFULL + f);
        const int k0 = (f & 7) * 64 + rank * 32;
        e_expect(bar, 16384);
        tma3d_mc(dst, &tm_win, 0, k0, f < 8 ? (aj < 6 ? 21 + 3 * aj : 27 + 2 * aj) : (aj < 2 ? 2 * aj : 3 * aj - 2), bar);
        tma2d_mc(dst + 6144, &tm_wq, 64 * aj + (f >> 3) * 32, k0, bar);
        if (f < 7) {
          e_expect(BAR(B_XFULL + 1 + f), 16384);
          tma2d(sb + SM_K + (f + 1) * 16384, &tm_x, (f + 1) * 64, ai * 128, BAR(B_XFULL + 1 + f));
        }
      }
      if (lane == 0) TS(1);
    } else if (warp == 19) {
      mbar_wait(BAR(B_ZST0), 0);
      if (lane == 0) { red_release(&g_zcnt[ai * 32]); TS(20); }
      __syncwarp();
      const unsigned ep1 = lds32(sb + SM_MISC + 4 * M_EPOCH) + 1;
      wait_ge(&g_zcnt[(lane & 15) * 32], ep1 * 8);
      __syncwarp();
      e_arrive(BAR(B_ZOK));
      mbar_wait(BAR(B_ZST1), 0);
      if (lane == 0) { red_release(&g_z1cnt[ai * 32]); TS(17); }
      __syncwarp();
      l2_prefetch(reinterpret_cast<const uint8_t*>(prm.w_out) + blockIdx.x * 5504, 5504);
      l2_prefetch(reinterpret_cast<const uint8_t*>(prm.wo) + blockIdx.x * 4096, 4096);
      wait_ge(&g_z1cnt[bi * 32], ep1 * 8);
      e_arrive(BAR(B_Z1OK));
    } else if (warp == 16) {
      tm_prefetch(&tm_wsp);
      tm_prefetch(&tm_wout);
      tm_prefetch(&tm_wo);
      tm_prefetch(&tm_out);
      mbar_wait(BAR(B_XEMPTY), 0);
      tma2d_pf(&tm_wsp, (bj >> 1) * 64, bi * 128 + rank * 64);
      tma2d_pf(&tm_wsp, (bj >> 1) * 64 + 256, bi * 128 + rank * 64);
    } else {
      if (lane == 0) {
        sts32(sb + SM_MISC + 4 * M_EPOCH, atomicAdd(&g_ticket, 1u) / NCTA);
        mbar_arrive(BAR(B_EPOCH));
        TS(71);
      }
      __syncwarp();
      const unsigned ep1 = lds32(sb + SM_MISC + 4 * M_EPOCH) + 1;
      e_expect(BAR(B_KVFULL), 49152);
      e_expect(BAR(B_KVB), 49152);
      e_expect(BAR(B_KVC), 32768);
      mbar_wait(BAR(B_WFULL + 8), 0);
      uint32_t kn = 0, vb = 0;
#pragma unroll 1
      for (int n = 0; n < SPIN_LIMIT; n++) {
        unsigned long long a, b, c, d;
        asm volatile("ld.relaxed.gpu.global.v2.b64 {%0, %1}, [%2];" : "=l"(a), "=l"(b) : "l"(&g_kvflag[2 * lane]) : "memory");
        asm volatile("ld.relaxed.gpu.global.v2.b64 {%0, %1}, [%2];" : "=l"(c), "=l"(d) : "l"(&g_kvflag[64 + 2 * lane]) : "memory");
        kn = max((uint32_t)a, (uint32_t)c); vb = (uint32_t)b | (uint32_t)d;
        if (__all_sync(0xffffffffu, (uint32_t)(a >> 32) == ep1 && (uint32_t)(b >> 32) == ep1 && (uint32_t)(c >> 32) == ep1 && (uint32_t)(d >> 32) == ep1)) break;
        __nanosleep(100);
      }
      asm volatile("fence.acquire.gpu;" ::: "memory");
      kn = __reduce_max_sync(0xffffffffu, kn);
      vb = __reduce_or_sync(0xffffffffu, vb);
      if (lane == 0) {
        TS(6);
        sts32(sb + SM_MISC + 4 * M_KN2, kn);
        sts32(sb + SM_MISC + 4 * M_VOK, vb == 0xFFFFu ? 1u : 0u);
        mbar_arrive(BAR(B_KSTAT));
      }
      __syncwarp();
      fence_async();
      mbar_wait(BAR(B_LNOK), 0);
#pragma unroll 1
      for (int c = 0; c < 8; c++) {
        const uint32_t off = c * 16384 + rank * 8192;
        mbar_wait(BAR(B_XEMPTY + c), 0);
        bulk_mc(sb + SM_K + off, reinterpret_cast<const uint8_t*>(g_kimg) + off, 8192, BAR(c < 3 ? B_KVFULL : (c < 6 ? B_KVB : B_KVC)));
      }
      if (lane == 0) TS(7);
      mbar_wait(BAR(B_DEC), 0);
      if (!lds32(sb + SM_MISC + 4 * M_FAST)) {
        mbar_wait(BAR(B_KVFULL), 0); mbar_wait(BAR(B_KVB), 0); mbar_wait(BAR(B_KVC), 0);
        e_expect(BAR(B_KFB), 65536);
#pragma unroll 1
        for (int j = 0; j < 32; j++) bulk(sb + SM_K + j * 4096, g_kbf + j * 128, 2048, BAR(B_KFB));
      }
    }
    const unsigned ep1 = lds32(sb + SM_MISC + 4 * M_EPOCH) + 1;
    if (warp < 19) {
      const int st = warp - 16, row = bi * 128 + rank * 64;
      const uint32_t stg = sb + SM_RING + st * RSTAGE, full = BAR(B_RFULL + st), empty = BAR(B_REMPTY + st);
      mbar_wait(BAR(B_XEMPTY + 7), 0);
      mbar_wait(BAR(B_ZOK), 0);
      fence_async();
      if (threadIdx.x == 512) TS(2);
      const uint8_t* zsrc = reinterpret_cast<const uint8_t*>(g_z2n) + (bj * 32 + st) * 11264;
      int n = st, ph = 1;
#pragma unroll 1
      for (; n < 32; n += 3, zsrc += 3 * 11264, ph ^= 1) {
        mbar_wait(empty, ph);
        e_expect(full, 16384 + 11264);
        tma2d_mc(stg + rank * 8192, &tm_wsp, n * 64, row, full);
        bulk(stg + 16384, zsrc, 11264, full);
        if ((n & 3) == (bj >> 1) && n < 24) tma2d_pf(&tm_wsp, (n + 8) * 64, row);
      }
      if (n == 32) {
        mbar_wait(empty, ph);
        mbar_wait(BAR(B_Z1OK), 0);
        fence_async();
        e_expect(full, 22528 + 512 + 256);
        bulk(stg, g_z1 + (bi * 88 + bj * 11) * 128, 22528, full);
        bulk(stg + 22528, g_gate + bi * 128, 512, full);
        bulk(stg + 23040, prm.b_sp + bi * 128, 256, full);
        n += 3; ph ^= 1;
      }
      bool first = true;
#pragma unroll 1
      for (; n < 44; n += 3, ph ^= 1) {
        mbar_wait(empty, ph);
        e_expect(full, 16384 + 8192);
        tma2d(stg + 16384, &tm_wout, 64 * bj, (n - 33) * 64, full);
        if (first) { wait_ge(&g_ucnt[bi * 32], ep1 * 8); fence_async(); first = false; if (threadIdx.x == 512) TS(3); }
        bulk_mc(stg + rank * 8192, reinterpret_cast<const uint8_t*>(g_u) + (bi * 11 + n - 33) * 16384 + rank * 8192, 8192, full);
      }
      mbar_wait(empty, ph);
      e_expect(BAR(B_WOFULL), st == 2 ? 16384 : 24576);
#pragma unroll 1
      for (int c = 3 * st; c < 3 * st + 3 && c < 8; c++) tma2d(stg + (c - 3 * st) * 8192, &tm_wo, 64 * bj, c * 64, BAR(B_WOFULL));
      if (threadIdx.x == 512) TS(4);
    }
    const int c0 = warp - 16;
    const uint32_t ooff = c0 * 16384 + rank * 8192;
    const uint8_t* osrc = reinterpret_cast<const uint8_t*>(g_o) + bi * 131072 + ooff;
    e_expect(BAR(B_XFULL + c0), 16384);
    e_expect(BAR(B_XFULL + c0 + 4), 16384);
    wait_ge(&g_ocnt[bi * 32 + 16 * 32], ep1 * 24);
    fence_async();
    mbar_wait(BAR(B_ATT), 0);
    bulk_mc(sb + SM_K + ooff, osrc, 8192, BAR(B_XFULL + c0));
    if (c0) {
#pragma unroll 1
      for (int n = 0; n < SPIN_LIMIT; n++) if ((int)(ld_acquire(&g_ocnt[bi * 32]) - ep1 * 24) >= 0) break;
      fence_async();
      if (threadIdx.x == 544) TS(5);
    }
    bulk_mc(sb + SM_K + ooff + 65536, osrc + 65536, 8192, BAR(B_XFULL + c0 + 4));
  } else {
    asm volatile("setmaxnreg.inc.sync.aligned.u32 112;");
    const int w = tid >> 5, g = lane >> 2, t4 = lane & 3, half = wg & 1;
    {
      float acc[64];
      if (wg == 2) {
        const int slot = ai * 4 + (aj >> 1), isv = aj & 1;
        const uint4* wsrc = reinterpret_cast<const uint4*>(isv ? prm.wv : prm.wk) + tid;
        uint4 wr[8];
#pragma unroll
        for (int r = 0; r < 8; r++) wr[r] = __ldg(wsrc + 128 * r);
#pragma unroll
        for (int r = 0; r < 8; r++) sts128(sb + SM_WKV + r * 2048 + (tid >> 1) * 32 + (((tid ^ (tid >> 3)) & 1) << 4), wr[r].x, wr[r].y, wr[r].z, wr[r].w);
        fence_async_smem();
        bar_sync(3, 128);
        float kv[16];
#pragma unroll
        for (int k = 0; k < 16; k++) kv[k] = 0.f;
        regfence(kv);
#pragma unroll 1
        for (int c = 0; c < 8; c++) {
          mbar_wait(BAR(B_XFULL + c), 0);
          const uint64_t da = mkdesc(sb + SM_WKV + c * 2048, 0, 256, 3);
          const uint64_t db = mkdesc(sb + SM_K + c * 16384 + (aj >> 1) * 4096, 16, 1024, 1);
          wg_fence();
#pragma unroll
          for (int k = 0; k < 4; k++) wg_ss_n32t<0, 16>(kv, da + 32 * k, db + 2 * k);
          wg_commit();
        }
        wg_wait<0>();
        regfence(kv);
        if (tid == 0) TS(22);
        const uint32_t sT = sb + SM_WKV, sH = sb + SM_WKV + 4096;
        bar_sync(3, 128);
        {
          const float a = w & 1 ? kv[4] : kv[0], b = w & 1 ? kv[5] : kv[1], c = w & 1 ? kv[6] : kv[2], d = w & 1 ? kv[7] : kv[3];
          const float e = w & 1 ? kv[12] : kv[8], f = w & 1 ? kv[13] : kv[9], h = w & 1 ? kv[14] : kv[10], i = w & 1 ? kv[15] : kv[11];
          const uint32_t lo = pack_bf16(w & 2 ? e : a, w & 2 ? f : b), hi = pack_bf16(w & 2 ? h : c, w & 2 ? i : d);
          const uint32_t p = sT + ((w * 8 + 2 * t4) * 17 + g) * 4;
          sts32(p, lo << 16); sts32(p + 68, lo & 0xFFFF0000u); sts32(p + 32, hi << 16); sts32(p + 100, hi & 0xFFFF0000u);
        }
        bar_sync(3, 128);
        if (tid == 0) TS(64);
        const int tok = (tid & 63) >> 1, hf = tid & 1;
        float f[8];
#pragma unroll
        for (int e = 0; e < 8; e++) f[e] = ldsf(sT + (tok * 17 + hf * 8 + e) * 4);
        uint4 val = make_uint4(pack_bf16(f[0], f[1]), pack_bf16(f[2], f[3]), pack_bf16(f[4], f[5]), pack_bf16(f[6], f[7]));
        uint32_t stat = 0;
        if (isv) {
#pragma unroll
          for (int e = 0; e < 8; e++) {
            if (fabsf(f[e]) >= 9.5367431640625e-07f) stat |= 1u << e;
            if (!(fabsf(f[e]) <= 1073741824.f)) stat |= 1u << (16 - 8 * hf);
          }
          stat = __reduce_or_sync(0xffffffffu, stat << (8 * hf));
        } else {
          float n2 = 0.f;
#pragma unroll
          for (int e = 0; e < 8; e++) n2 = fmaf(f[e], f[e], n2);
          n2 += __shfl_xor_sync(0xffffffffu, n2, 1);
          if (!(n2 <= 3.0e38f)) n2 = 3.0e38f;
          stat = __reduce_max_sync(0xffffffffu, __float_as_uint(n2));
          if (tid < 48) {
            const int d = tid & 15, sg = tid >> 4, j0 = sg == 0 ? 0 : (sg == 1 ? 10 : 22), j1 = sg == 0 ? 10 : (sg == 1 ? 22 : 32);
            const float sc = slot < NP ? 16.f : 0.125f;
            float kx[12], run = 0.f;
#pragma unroll
            for (int e = 0; e < 12; e++) kx[e] = ldsf(sT + (min(j0 + e, 31) * 17 + d) * 4);
#pragma unroll
            for (int e = 0; e < 12; e++) {
              const __half hv = __float2half_rn(fmaf(kx[e], sc, -run));
              run += __half2float(hv);
              if (j0 + e < j1) sts16(sH + ((j0 + e) * 16 + d) * 2, __half_as_ushort(hv));
            }
          }
        }
        if (lane == 0) sts32(sb + SM_MISC + 4 * (M_KVR + w), stat);
        bar_sync(3, 128);
        const uint32_t off = slot * 2 + (hf ^ ((slot >> 2) & 1));
        uint4* dst = tid < 64 ? g_kimg + tok * 256 + isv * 128 + off : g_kbf + tok * 128 + off;
        if (!isv && tid < 64) val = lds128(sH + tok * 32 + hf * 16);
        uint32_t chk = 0;
        if (tid < 64 || !isv) { *dst = val; chk = ld_back(dst); }
        mbar_wait(BAR(B_EPOCH), 0);
        consume(chk, sb);
        fence_async();
        bar_sync(3, 128);
        if (tid == 0) {
          const uint32_t s0 = lds32(sb + SM_MISC + 4 * M_KVR), s1 = lds32(sb + SM_MISC + 4 * (M_KVR + 1));
          const unsigned long long fl = ((unsigned long long)(lds32(sb + SM_MISC + 4 * M_EPOCH) + 1) << 32) | (isv ? (s0 | s1) : max(s0, s1));
          asm volatile("st.relaxed.gpu.global.b64 [%0], %1;" ::"l"(&g_kvflag[ai * 8 + aj]), "l"(fl) : "memory");
          TS(23);
        }
      } else if (wg == 3) {
        if (tid < 64) { const uint4 gv = __ldg(reinterpret_cast<const uint4*>(prm.gate_w) + tid); sts128(sb + SM_GW + tid * 16, gv.x, gv.y, gv.z, gv.w); }
        sts32(sb + SM_ONES + tid * 4, 0x3F803F80u);
        fence_async_smem();
        bar_sync(4, 128);
        float ga[8];
#pragma unroll
        for (int k = 0; k < 8; k++) ga[k] = 0.f;
        regfence(ga);
#pragma unroll 1
        for (int c = 0; c < 8; c++) {
          mbar_wait(BAR(B_XFULL + c), 0);
          if (tid == 0) TS(40 + c);
          const uint64_t da = mkdesc(sb + SM_K + c * 16384, 16, 1024, 1), db = mkdesc(sb + SM_GW + c * 128, 16, 128, 0);
          wg_fence();
#pragma unroll
          for (int k = 0; k < 4; k++) { wg_ss_n8<0, 8>(ga, da + 2 * k, db + 2 * k); wg_ss_n8<4, 8>(ga, da + 512 + 2 * k, db + 2 * k); }
          wg_commit();
        }
        wg_wait<0>();
        regfence(ga);
        const float g0 = __shfl_sync(0xffffffffu, ga[0], lane & 28), g1 = __shfl_sync(0xffffffffu, ga[2], lane & 28);
        const float g2 = __shfl_sync(0xffffffffu, ga[4], lane & 28), g3 = __shfl_sync(0xffffffffu, ga[6], lane & 28);
        const float gs = t4 & 2 ? (t4 & 1 ? g3 : g2) : (t4 & 1 ? g1 : g0);
        sts32(sb + SM_G + ((t4 >> 1) * 64 + w * 16 + (t4 & 1) * 8 + g) * 4, __float_as_uint(__fdividef(1.f, 1.f + __expf(-gs))));
        bar_sync(4, 128);
        if (aj == 0) g_gate[ai * 128 + tid] = ldsf(sb + SM_G + tid * 4);
        if (tid == 0) TS(8);
      }
#pragma unroll
      for (int k = 0; k < 64; k++) acc[k] = 0.f;
      regfence(acc);
      const int pass = wg >> 1;
#pragma unroll 1
      for (int c = 0; c < 8; c++) {
        mbar_wait(BAR(B_XFULL + c), 0);
        mbar_wait(BAR(B_WFULL + pass * 8 + c), 0);
        if (tid == 0 && half == pass) TS(48 + pass * 8 + c);
        const uint64_t da = mkdesc(sb + SM_K + c * 16384 + half * 8192, 16, 1024, 1);
        const uint64_t db = mkdesc(sb + wslot(pass * 8 + c), 2048, 512, 2);
        wg_fence();
#pragma unroll
        for (int k = 0; k < 4; k++) wg_ss_n128<0, 64>(acc, da + 2 * k, db + (k & 1) * 64 + (k >> 1) * 512);
        wg_commit();
        wg_wait<1>();
        if (tid == 0 && c > 0) {
          if (pass * 8 + c < 12) mbar_arrive_both(BAR(B_WEMPTY + pass * 8 + c - 1));
          if (pass) mbar_arrive_both(BAR(B_XEMPTY + c - 1));
        }
      }
      wg_wait<0>();
      if (tid == 0) mbar_arrive_both(BAR(pass ? B_XEMPTY + 7 : B_WEMPTY + 7));
      regfence(acc);
      if (tid == 0) TS(wg == 0 ? 16 : (wg == 2 ? 24 : (wg == 3 ? 9 : 95)));
      uint32_t qb[8];
      {
        float n2 = 0.f;
#pragma unroll
        for (int k = 0; k < 8; k++) qb[k] = pack_bf16(acc[48 + 2 * k], acc[49 + 2 * k]);
#pragma unroll
        for (int k = 0; k < 4; k++) {
          const uint32_t a = qb[4 * (k >> 1) + (k & 1)], b = qb[4 * (k >> 1) + (k & 1) + 2];
          float s = bf_lo(a) * bf_lo(a);
          s = fmaf(bf_hi(a), bf_hi(a), s); s = fmaf(bf_lo(b), bf_lo(b), s); s = fmaf(bf_hi(b), bf_hi(b), s);
          s += __shfl_xor_sync(0xffffffffu, s, 1); s += __shfl_xor_sync(0xffffffffu, s, 2);
          if (!(s <= 3.0e38f)) s = 3.0e38f;
          n2 = fmaxf(n2, s);
        }
        const uint32_t nmax = __reduce_max_sync(0xffffffffu, __float_as_uint(n2));
        if (lane == 0) { sts32(sb + SM_MISC + 4 * (M_RED + warp), nmax); mbar_arrive(BAR(B_KSTAT)); }
      }
      auto finish_q = [&]() {
        mbar_wait(BAR(B_KSTAT), 0);
        const float qn2 = __uint_as_float(__reduce_max_sync(0xffffffffu, lds32(sb + SM_MISC + 4 * (M_RED + (lane & 15)))));
        const float kn2 = ldsf(sb + SM_MISC + 4 * M_KN2);
        constexpr float SC = QSCALE * 0.125f;
        const bool fast = lds32(sb + SM_MISC + 4 * M_VOK) && qn2 <= 4.0e8f && kn2 <= 4.0e6f && qn2 * kn2 * (SC * SC) <= BOUND * BOUND;
        if (fast) {
#pragma unroll
          for (int k = 0; k < 8; k++) qb[k] = pack_f16(bf_lo(qb[k]) * QSCALE, bf_hi(qb[k]) * QSCALE);
        }
        sts128(sb + SM_Q + wg * 2048 + pass * 4096 + tid * 16, qb[0], qb[1], qb[2], qb[3]);
        sts128(sb + SM_Q + wg * 2048 + pass * 4096 + 4096 + tid * 16, qb[4], qb[5], qb[6], qb[7]);
        if (threadIdx.x == 256) { sts32(sb + SM_MISC + 4 * M_FAST, fast ? 1u : 0u); sts32(sb + SM_MISC + 4 * M_MASK, 0x007F007Fu); mbar_arrive(BAR(B_DEC)); }
        __syncwarp();
        if (lane == 0) mbar_arrive(BAR(B_QRDY));
        if (tid == 0 && pass) TS(75 + wg);
      };
      if (pass) finish_q();
#pragma unroll
      for (int k = 0; k < 48; k++) acc[k] = gelu2_tanh(acc[k]);
      int fb0, c_lo = 0, c_hi = 12;
      if (wg < 2) { fb0 = aj < 6 ? 12 * aj - 2 : 22 + 8 * aj; if (aj == 0) c_lo = 2; if (aj >= 6) c_hi = 8; }
      else { fb0 = aj < 2 ? 8 * aj : 12 * aj - 8; if (aj < 2) c_hi = 8; if (aj == 7) c_hi = 10; }
      if (wg < 2) {
        float s1[2][3], s2[2][3];
#pragma unroll
        for (int k = 0; k < 48; k++) {
          const int r = (k >> 1) & 1, gq = k < 8 ? 0 : (k < 32 ? 1 : 2);
          if (k - 2 * r == (gq == 0 ? 0 : (gq == 1 ? 8 : 32))) { s1[r][gq] = acc[k]; s2[r][gq] = acc[k] * acc[k]; }
          else { s1[r][gq] += acc[k]; s2[r][gq] = fmaf(acc[k], acc[k], s2[r][gq]); }
        }
        const float inv_n = __fdividef(0.125f, (float)(c_hi - c_lo));
        float mm[2], vv[2];
#pragma unroll
        for (int r = 0; r < 2; r++) {
          float a = s1[r][1], b = s2[r][1];
          if (c_lo == 0) { a += s1[r][0]; b += s2[r][0]; }
          if (c_hi == 12) { a += s1[r][2]; b += s2[r][2]; }
          a += __shfl_xor_sync(0xffffffffu, a, 1); b += __shfl_xor_sync(0xffffffffu, b, 1);
          a += __shfl_xor_sync(0xffffffffu, a, 2); b += __shfl_xor_sync(0xffffffffu, b, 2);
          mm[r] = a * inv_n;
          vv[r] = fmaxf(fmaf(-a, mm[r], b), 0.f);
        }
        const int r0 = half * 64 + w * 16 + g;
        mbar_wait(BAR(B_EPOCH), 0);
        const unsigned ep1 = lds32(sb + SM_MISC + 4 * M_EPOCH) + 1;
        if (threadIdx.x == 0) TS(67);
        if (t4 < 2) {
          const float m = t4 ? mm[1] : mm[0], v = t4 ? vv[1] : vv[0];
          asm volatile("st.relaxed.gpu.global.v2.b64 [%0], {%1, %2};" ::"l"(&g_lnstat[(ai * 8 + aj) * 128 + r0 + 8 * t4]),
                       "l"(((unsigned long long)ep1 << 32) | __float_as_uint(m)), "l"(((unsigned long long)ep1 << 32) | __float_as_uint(v)) : "memory");
        }
        float sm[4], sv[4];
        const uint4* lp = &g_lnstat[(ai * 8 + 2 * t4) * 128 + r0];
#pragma unroll 1
        for (int n = 0; n < SPIN_LIMIT; n++) {
          uint32_t tg = ep1;
          if (lane < 8) tg = ld_back(reinterpret_cast<const uint32_t*>(&g_lnstat[(ai * 8 + lane) * 128 + half * 64 + w * 16 + 15]) + 3);
          if (__all_sync(0xffffffffu, tg == ep1)) break;
        }
#pragma unroll 1
        for (int n = 0; n < SPIN_LIMIT; n++) {
          bool ok = true;
#pragma unroll
          for (int e = 0; e < 4; e++) {
            unsigned long long a, b;
            asm volatile("ld.relaxed.gpu.global.v2.b64 {%0, %1}, [%2];" : "=l"(a), "=l"(b) : "l"(lp + (e >> 1) * 128 + (e & 1) * 8) : "memory");
            ok = ok && (uint32_t)(a >> 32) == ep1 && (uint32_t)(b >> 32) == ep1;
            sm[e] = __uint_as_float((uint32_t)a); sv[e] = __uint_as_float((uint32_t)b);
          }
          if (__all_sync(0xffffffffu, ok)) break;
        }
        if (lane == 0) mbar_arrive(BAR(B_LNOK));
        if (threadIdx.x == 0) TS(68);
        const float na = t4 == 0 ? 80.f : (t4 == 3 ? 64.f : 96.f), nb = t4 == 3 ? 64.f : 96.f;
#pragma unroll
        for (int r = 0; r < 2; r++) {
          float t = fmaf(sm[r], na, sm[2 + r] * nb);
          t += __shfl_xor_sync(0xffffffffu, t, 1); t += __shfl_xor_sync(0xffffffffu, t, 2);
          const float mu = t * (1.f / 688.f);
          const float da = sm[r] - mu, db = sm[2 + r] - mu;
          float m2 = sv[r] + sv[2 + r] + na * da * da + nb * db * db;
          m2 += __shfl_xor_sync(0xffffffffu, m2, 1); m2 += __shfl_xor_sync(0xffffffffu, m2, 2);
          const float rs = rsqrtf(fmaf(m2, 1.f / 688.f, 4e-5f)), sh = -mu * rs;
#pragma unroll
          for (int k = 2 * r; k < 48; k += 4) { acc[k] = fmaf(acc[k], rs, sh); acc[k + 1] = fmaf(acc[k + 1], rs, sh); }
        }
        if (aj == 7) {
          c_hi = 10;
#pragma unroll
          for (int k = 32; k < 40; k++) acc[k] = 0.f;
        }
      }
      uint32_t* zp = wg < 2 ? reinterpret_cast<uint32_t*>(g_z2n) + (ai * 2 + half) * 2816 + w * 704
                            : reinterpret_cast<uint32_t*>(g_z1) + (ai * 88 * 16 + half * 8 + w * 2) * 32;
      const int mul = wg < 2 ? 373 : 0, cstr = wg < 2 ? 32 : 512, rstr = wg < 2 ? 352 : 32;
      auto zoff = [&](int c8) { const int fb = fb0 + c8; return ((fb * mul) >> 12) * (32 * 2816 - 352) + fb * cstr; };
#pragma unroll
      for (int c8 = 0; c8 < 12; c8++) {
        uint32_t* p = zp + zoff(c8) + lane;
        if (c8 >= c_lo && c8 < c_hi) { p[0] = pack_bf16(acc[4 * c8], acc[4 * c8 + 1]); p[rstr] = pack_bf16(acc[4 * c8 + 2], acc[4 * c8 + 3]); }
      }
      if (tid == 0) TS(wg == 0 ? 69 : 78 + wg);
      fence_async();
      __syncwarp();
      if (lane == 0) mbar_arrive(BAR(pass ? B_ZST1 : B_ZST0));
      if (!pass) finish_q();
    }
    if (wg == 3) {
      asm volatile("setmaxnreg.inc.sync.aligned.u32 120;");
      int st = 0, ph = 0;
      {
        float acc[88];
#pragma unroll
        for (int k = 0; k < 88; k++) acc[k] = 0.f;
        regfence(acc);
        const uint64_t da0 = mkdesc(sb + SM_RING, 16, 1024, 1), db0 = mkdesc(sb + SM_RING + 16384, 1408, 128, 0);
        uint32_t rel;
        asm("mapa.shared::cluster.u32 %0, %1, %2;" : "=r"(rel) : "r"(BAR(B_REMPTY)), "r"(lane & 1));
        rel -= BAR(B_RFULL);
#pragma unroll 1
        for (int n = 0; n < 11; n++) {
          uint64_t da = da0, db = db0;
          uint32_t fb = BAR(B_RFULL);
          const uint32_t fe = BAR(B_RFULL + (n < 10 ? 3 : 2));
#pragma unroll 1
          do {
            mbar_wait(fb, n & 1);
#pragma unroll
            for (int k = 0; k < 4; k++) {
              if (k % SBATCH == 0) wg_fence();
              wg_ss_n88<0, 88>(acc, da + 2 * k, db + 176 * k);
              wg_ss_n88<44, 88>(acc, da + (512 + 2 * k), db + 176 * k);
              if (k % SBATCH == SBATCH - 1) { wg_commit(); wg_wait<0>(); }
            }
            if (tid < 2) asm volatile("mbarrier.arrive.shared::cluster.b64 _, [%0];" ::"r"(rel + fb) : "memory");
            fb += 8; da += RSTAGE / 16; db += RSTAGE / 16;
          } while (fb != fe);
        }
        st = 2; ph = 0;
        regfence(acc);
        if (tid == 0) TS(11);
        mbar_wait(BAR(B_RFULL + st), ph);
        const uint8_t* zs = smem_raw + SM_RING + st * RSTAGE;
        uint32_t zmask = bj == 7 ? 0u : 0xFFFFFFFFu;
        asm volatile("" : "+r"(zmask));
        uint32_t* up = reinterpret_cast<uint32_t*>(g_u) + bi * 11 * 4096 + w * 512 + lane;
#pragma unroll
        for (int r = 0; r < 4; r++) {
          const int row = (r >> 1) * 64 + w * 16 + (r & 1) * 8 + g;
          const float og = fmaf(reinterpret_cast<const float*>(zs + 22528)[row], -0.5f, 0.5f);
          const float bs = __bfloat162float(reinterpret_cast<const __nv_bfloat16*>(zs + 23040)[row]) * og;
#pragma unroll
          for (int c8 = 0; c8 < 11; c8++) {
            const int k = (r >> 1) * 44 + c8 * 4 + (r & 1) * 2, cb = 11 * bj + c8;
            uint32_t zz = reinterpret_cast<const uint32_t*>(zs)[c8 * 512 + ((r >> 1) * 8 + w * 2 + (r & 1)) * 32 + lane];
            if (c8 >= 9) zz &= zmask;
            uint32_t v = pack_bf16(fmaf(acc[k], og, bs), fmaf(acc[k + 1], og, bs));
            asm("mul.rn.bf16x2 %0, %0, %1;" : "+r"(v) : "r"(zz));
            up[cb * 32 + (cb >> 3) * 3840 + ((r >> 1) * 8 + (r & 1)) * 256] = v;
          }
        }
        fence_async_smem();
        fence_async();
        bar_sync(4, 128);
        if (tid == 0) { mbar_arrive_both(BAR(B_REMPTY + st)); red_release(&g_ucnt[bi * 32]); TS(12); }
        if (++st == 3) { st = 0; ph ^= 1; }
      }
      float oc[64];
#pragma unroll
      for (int k = 0; k < 64; k++) oc[k] = 0.f;
      regfence(oc);
#pragma unroll 1
      for (int n = 0; n < 11; n++) {
        mbar_wait(BAR(B_RFULL + st), ph);
        const uint64_t da = mkdesc(sb + SM_RING + st * RSTAGE, 128, 1024, 0), db = mkdesc(sb + SM_RING + st * RSTAGE + 16384, 8192, 1024, 1);
#pragma unroll
        for (int k = 0; k < 4; k += 2) {
          wg_fence();
          wg_ss_n64<0, 64>(oc, da + 16 * k, db + 128 * k);
          wg_ss_n64<32, 64>(oc, da + 512 + 16 * k, db + 128 * k);
          wg_ss_n64<0, 64>(oc, da + 16 * k + 16, db + 128 * k + 128);
          wg_ss_n64<32, 64>(oc, da + 528 + 16 * k, db + 128 * k + 128);
          wg_commit();
          wg_wait<0>();
        }
        if (tid == 0) mbar_arrive_both(BAR(B_REMPTY + st));
        if (++st == 3) { st = 0; ph ^= 1; }
      }
      if (tid == 0) TS(13);
      mbar_wait(BAR(B_WOFULL), 0);
#pragma unroll 1
      for (int h = 0; h < 4; h++) {
        const uint64_t da = mkdesc(sb + SM_K + h * 32768, 128, 256, 0), db = mkdesc(sb + SM_RING + h * 2048, 8192, 1024, 1);
        mbar_wait(BAR(B_XFULL + 2 * h), 1);
        wg_fence();
#pragma unroll
        for (int c = 0; c < 8; c++) wg_ss_n64<0, 64>(oc, da + 128 * c, db + (c * 8192 + (c / 3) * (RSTAGE - 24576)) / 16);
        wg_commit();
        mbar_wait(BAR(B_XFULL + 2 * h + 1), 1);
#pragma unroll
        for (int c = 0; c < 8; c++) wg_ss_n64<32, 64>(oc, da + 1024 + 128 * c, db + (c * 8192 + (c / 3) * (RSTAGE - 24576)) / 16);
        wg_commit();
      }
      wg_wait<0>();
      regfence(oc);
      if (tid == 0) TS(14);
#pragma unroll
      for (int hf = 0; hf < 2; hf++) {
        const uint32_t rb = sb + SM_Q + (hf * 64 + w * 16) * 128, ra = rb + (lane & 15) * 128;
#pragma unroll
        for (int c = 0; c < 4; c++) {
          const int k = hf * 32 + c * 8;
          asm volatile("stmatrix.sync.aligned.m8n8.x4.shared.b16 [%0], {%1, %2, %3, %4};" ::"r"(ra + (((2 * c + (lane >> 4)) ^ (lane & 7)) << 4)),
                       "r"(pack_bf16(oc[k], oc[k + 1])), "r"(pack_bf16(oc[k + 2], oc[k + 3])), "r"(pack_bf16(oc[k + 4], oc[k + 5])), "r"(pack_bf16(oc[k + 6], oc[k + 7])) : "memory");
        }
        fence_async_smem();
        __syncwarp();
        asm volatile(ELECT "cp.async.bulk.tensor.2d.global.shared::cta.bulk_group [%0, {%2, %3}], [%1];\n}"
                     ::"l"(&tm_out), "r"(rb), "r"(64 * bj), "r"(bi * 128 + hf * 64 + w * 16) : "memory");
      }
      asm volatile("cp.async.bulk.commit_group;" ::: "memory");
      asm volatile("cp.async.bulk.wait_group.read 0;" ::: "memory");
      if (tid == 0) TS(15);
    } else {
      mbar_wait(BAR(B_QRDY), 0);
    if (tid == 0) TS(25 + wg);
    if (tid == 0) TS(28 + wg);
    if (threadIdx.x == 0) GTS(125);
    const uint64_t dv0 = mkdesc(sb + SM_K + 2048, SM_ONES - 2048, 256, 3);
    const int aw = wg == 0 ? 0 : 3 - wg;
    uint32_t chk = 0, pend = 0;
    uint32_t* const obase = reinterpret_cast<uint32_t*>(g_o) + ai * 32768 + aj * 512 + w * 128 + lane;
    const uint32_t gbase = sb + SM_G + (w * 16 + g) * 4;
    auto flush = [&](const float (&o)[12], int tau) {
      chk ^= pend; pend = store_o_tile(o, obase, gbase, tile_of(tau), lane);
      if ((0x52 >> tau) & 1) {
        consume(chk ^ pend, sb);
        fence_async();
        bar_sync(1 + wg, 128);
        if (tid == 0) red_relaxed(&g_ocnt[ai * 32 + 16 * 32]);
      }
    };
    float o[12], s[32];
    uint32_t q[4], p0[16], p1[16];
    if (lds32(sb + SM_MISC + 4 * M_FAST)) {
      const uint32_t mlo = lds32(sb + SM_MISC + 4 * M_MASK), mhi = ~mlo;
      uint64_t dv = dv0;
#define STEP(PIN, POUT) { wg_fence(); issue_qk(s, q, dv + (VSTEP8 + KOFF)); wg_commit(); issue_pv(o, PIN, dv); dv += VSTEP8; wg_commit(); \
                          wg_wait<1>(); regfence(s); softmax_step(s, POUT, mlo, mhi); wg_wait<0>(); }
      int tau = aw * 3 - (aw > 0), seg = (3 - aw) % 3;
      float4* part = g_part + blockIdx.x * 768 + tid;
#pragma unroll 1
      for (int it = 0; it < 8; it++) {
        int n2 = seg == 1 ? 6 : 5;
        if (it < 3) {
          mbar_wait(BAR(seg ? B_KVB : B_KVFULL), 0);
          mbar_wait(BAR(seg == 2 ? B_KVC : B_KVFULL), 0);
        }
#pragma unroll
        for (int k = 0; k < 32; k++) s[k] = k < NP / 2 ? MAGIC_C : 0.f;
        if (it == 0 || seg == 0) {
          const int j0 = seg == 0 ? 0 : (seg == 1 ? 10 : 22);
          dv = dv0 + VSTEP8 * j0;
          const uint4 qv = lds128(sb + SM_Q + tile_of(tau) * 2048 + tid * 16);
          q[0] = qv.x; q[1] = qv.y; q[2] = qv.z; q[3] = qv.w;
          if (it + aw > 5 && aw < 2 && tau == aw * 3 + 2) {
            bar_sync(6 + aw, 256);
            const float4 a = part[aw * 384], b = part[aw * 384 + 128], c = part[aw * 384 + 256];
            o[0] = a.x; o[1] = a.y; o[2] = a.z; o[3] = a.w; o[4] = b.x; o[5] = b.y; o[6] = b.z; o[7] = b.w; o[8] = c.x; o[9] = c.y; o[10] = c.z; o[11] = c.w;
          } else {
#pragma unroll
            for (int k = 0; k < 12; k++) o[k] = 0.f;
          }
          regfence(s);
          wg_fence(); issue_qk(s, q, dv + KOFF); wg_commit();
          wg_wait<0>(); regfence(s);
          softmax_step(s, p0, mlo, mhi);
          regfence(o);
          STEP(p0, p1);
          n2--;
        }
        regfence(s);
#pragma unroll 1
        for (; n2 > 0; n2--) { STEP(p1, p0); STEP(p0, p1); }
        if (it == 7 || seg == 2) {
          wg_fence(); issue_pv(o, p1, dv); wg_commit();
          wg_wait<0>(); regfence(o);
          if (it < aw) {
            float4* pp = part + (aw - 1) * 384;
            pp[0] = make_float4(o[0], o[1], o[2], o[3]); pp[128] = make_float4(o[4], o[5], o[6], o[7]); pp[256] = make_float4(o[8], o[9], o[10], o[11]);
            __threadfence_block();
            bar_arrive(5 + aw, 256);
          } else {
            flush(o, tau);
          }
        }
        if (++seg == 3) { seg = 0; tau++; }
      }
#undef STEP
    } else {
      mbar_wait(BAR(B_KFB), 0);
      constexpr float SC = 0.25f * 1.4426950408889634f;
#pragma unroll 1
      for (int tau = wg * 3; tau < wg * 3 + 3 && tau < 8; tau++) {
        const uint4 qv = lds128(sb + SM_Q + tile_of(tau) * 2048 + tid * 16);
        float m0 = -INFINITY, m1 = -INFINITY;
#pragma unroll
        for (int k = 0; k < 12; k++) o[k] = 0.f;
        uint64_t dv = dv0;
#pragma unroll 1
        for (int j = 0; j < 32; j++) {
          regfence(s);
          wg_fence(); wg_qkb_n64<0, 0, 32>(s, qv.x, qv.y, qv.z, qv.w, dv + KOFF); wg_commit();
          wg_wait<0>(); regfence(s);
          float x0 = m0, x1 = m1;
#pragma unroll
          for (int k = 0; k < 32; k++) { s[k] *= SC; if (k & 2) x1 = fmaxf(x1, s[k]); else x0 = fmaxf(x0, s[k]); }
          x0 = fmaxf(x0, __shfl_xor_sync(0xffffffffu, x0, 1)); x0 = fmaxf(x0, __shfl_xor_sync(0xffffffffu, x0, 2));
          x1 = fmaxf(x1, __shfl_xor_sync(0xffffffffu, x1, 1)); x1 = fmaxf(x1, __shfl_xor_sync(0xffffffffu, x1, 2));
          const float c0 = ex2(m0 - x0), c1 = ex2(m1 - x1);
          m0 = x0; m1 = x1;
#pragma unroll
          for (int k = 0; k < 12; k++) o[k] *= (k & 2) ? c1 : c0;
#pragma unroll
          for (int k = 0; k < 16; k++) { const float m = (k & 1) ? m1 : m0; p0[k] = exp_mufu(s[2 * k] - m, s[2 * k + 1] - m); }
          regfence(o);
          wg_fence(); issue_pv(o, p0, dv); dv += VSTEP8; wg_commit();
          wg_wait<0>(); regfence(o);
        }
        flush(o, tau);
      }
    }
    consume(chk ^ pend, sb);
    fence_async();
    bar_sync(1 + wg, 128);
    if (tid == 0) { red_relaxed(&g_ocnt[ai * 32]); mbar_arrive_both(BAR(B_ATT)); TS(31 + wg); if (wg == 0) GTS(124); }
    }
  }
  __syncwarp();
  asm volatile("barrier.cluster.arrive.relaxed;" ::: "memory");
  asm volatile("barrier.cluster.wait;" ::: "memory");
}

typedef CUresult (*EncodeFn)(CUtensorMap*, CUtensorMapDataType, cuuint32_t, void*, const cuuint64_t*, const cuuint64_t*,
                             const cuuint32_t*, const cuuint32_t*, CUtensorMapInterleave, CUtensorMapSwizzle,
                             CUtensorMapL2promotion, CUtensorMapFloatOOBfill);

void make_map(EncodeFn enc, CUtensorMap* tm, const void* base, uint64_t cols, uint64_t rows, uint32_t bc, uint32_t br, CUtensorMapSwizzle sw) {
  cuuint64_t gd[2] = {cols, rows};
  cuuint64_t gs[1] = {cols * 2};
  cuuint32_t bd[2] = {bc, br};
  cuuint32_t es[2] = {1, 1};
  enc(tm, CU_TENSOR_MAP_DATA_TYPE_BFLOAT16, 2, const_cast<void*>(base), gd, gs, bd, es, CU_TENSOR_MAP_INTERLEAVE_NONE, sw,
      CU_TENSOR_MAP_L2_PROMOTION_L2_128B, CU_TENSOR_MAP_FLOAT_OOB_FILL_NONE);
}

}

extern "C" void kernel_launch(void* const* d_in, const int* in_sizes, int n_in, void* d_out, int out_size) {
  (void)in_sizes; (void)n_in; (void)out_size;
  static EncodeFn enc = nullptr;
  if (!enc) {
    void* fn = nullptr;
    cudaDriverEntryPointQueryResult qr;
    cudaGetDriverEntryPoint("cuTensorMapEncodeTiled", &fn, cudaEnableDefault, &qr);
    enc = (EncodeFn)fn;
    cudaFuncSetAttribute(fused_kernel, cudaFuncAttributeMaxDynamicSharedMemorySize, SMEM_BYTES);
  }
  CUtensorMap tx, tq, tin, tsp, tout, to, ty;
  make_map(enc, &ty, d_out, 512, 2048, 64, 16, CU_TENSOR_MAP_SWIZZLE_128B);
  make_map(enc, &tx, d_in[0], 512, 2048, 64, 128, CU_TENSOR_MAP_SWIZZLE_128B);
  make_map(enc, &tq, d_in[1], 512, 512, 32, 32, CU_TENSOR_MAP_SWIZZLE_64B);
  make_map(enc, &to, d_in[4], 512, 512, 64, 64, CU_TENSOR_MAP_SWIZZLE_128B);
  {
    cuuint64_t gd[3] = {32, 512, 43};
    cuuint64_t gs[2] = {1376 * 2, 64};
    cuuint32_t bd[3] = {32, 32, 3};
    cuuint32_t es[3] = {1, 1, 1};
    enc(&tin, CU_TENSOR_MAP_DATA_TYPE_BFLOAT16, 3, d_in[6], gd, gs, bd, es, CU_TENSOR_MAP_INTERLEAVE_NONE, CU_TENSOR_MAP_SWIZZLE_64B,
        CU_TENSOR_MAP_L2_PROMOTION_L2_128B, CU_TENSOR_MAP_FLOAT_OOB_FILL_NONE);
  }
  make_map(enc, &tsp, d_in[7], 2048, 2048, 64, 64, CU_TENSOR_MAP_SWIZZLE_128B);
  make_map(enc, &tout, d_in[9], 512, 688, 64, 64, CU_TENSOR_MAP_SWIZZLE_128B);
  Params prm;
  prm.gate_w = (const __nv_bfloat16*)d_in[10];
  prm.b_sp = (const __nv_bfloat16*)d_in[8];
  prm.w_out = (const __nv_bfloat16*)d_in[9];
  prm.wo = (const __nv_bfloat16*)d_in[4];
  prm.w_in = (const __nv_bfloat16*)d_in[6];
  prm.wq = (const __nv_bfloat16*)d_in[1];
  prm.wk = (const __nv_bfloat16*)d_in[2];
  prm.wv = (const __nv_bfloat16*)d_in[3];
  fused_kernel<<<NCTA, NTHREADS, SMEM_BYTES>>>(tx, tq, tin, tsp, tout, to, ty, prm);
}
```

```cpp
#include <cuda_runtime.h>
#include <cuda.h>
#include <cuda_bf16.h>
#include <cuda_fp16.h>
#include <stdint.h>

namespace {

constexpr int NCTA = 128;
constexpr int NTHREADS = 640;
#define NPOLY 40
constexpr int NP = NPOLY;
constexpr int SPIN_LIMIT = 1 << 18;
#define LNSLEEP 200
#define SBATCH 1

constexpr uint32_t SM_K = 0;
constexpr uint32_t SM_ONES = 131072;
constexpr uint32_t KV_BYTES = 131072;
constexpr uint32_t SM_BAR = 131584;
constexpr uint32_t SM_RING = 132096;
constexpr uint32_t RSTAGE = 27648;
constexpr uint32_t WSLOT = 16384;
constexpr uint32_t SM_WKV = SM_RING + 4 * WSLOT;
constexpr uint32_t SM_GW = SM_WKV + 16384;
constexpr uint32_t SM_Q = 215040;
constexpr uint32_t SM_G = 231424;
constexpr uint32_t SM_MISC = 231936;
constexpr uint32_t SMEM_BYTES = 232448;

constexpr int B_XFULL = 0, B_XEMPTY = 8, B_WFULL = 16, B_WEMPTY = 32, B_RFULL = 44, B_REMPTY = 47, B_KVFULL = 50,
              B_KFB = 51, B_KSTAT = 52, B_DEC = 53, B_ZST0 = 43, B_ZST1 = 63, B_WOFULL = 54, B_EPOCH = 55, B_ZOK = 56, B_Z1OK = 57, B_ATT = 58, B_QRDY = 59, B_LNOK = 60, B_KVB = 61, B_KVC = 62;
constexpr int M_EPOCH = 0, M_KN2 = 1, M_VOK = 2, M_FAST = 3, M_KVR = 4, M_MASK = 8, M_RED = 16;

__device__ uint4 g_kimg[KV_BYTES / 16];
__device__ uint4 g_kbf[65536 / 16];
__device__ unsigned long long g_kvflag[NCTA];
__device__ unsigned long long g_lnstat[16 * 8 * 128];
__device__ float g_gate[2048];
__device__ uint4 g_z2n[8 * 32 * 11264 / 16];
__device__ uint4 g_z1[16 * 88 * 128];
__device__ uint4 g_u[16 * 11 * 1024];
__device__ uint4 g_o[16 * 8 * 1024];
__device__ float4 g_part[NCTA * 2 * 3 * 128];
__device__ unsigned g_ticket;
__device__ unsigned g_zcnt[16 * 32];
__device__ unsigned g_z1cnt[16 * 32];
__device__ unsigned g_ucnt[16 * 32];
__device__ unsigned g_ocnt[2 * 16 * 32];
#define TS(k) do { } while (0)
#define GTS(k) do { } while (0)

__device__ __forceinline__ void mbar_init(uint32_t a, uint32_t c) { asm volatile("mbarrier.init.shared::cta.b64 [%0], %1;" ::"r"(a), "r"(c) : "memory"); }
__device__ __forceinline__ void mbar_arrive(uint32_t a) { asm volatile("mbarrier.arrive.shared::cta.b64 _, [%0];" ::"r"(a) : "memory"); }
__device__ __forceinline__ void mbar_arrive_both(uint32_t a) {
  asm volatile("{\n.reg .b32 ra;\nmapa.shared::cluster.u32 ra, %0, 0;\nmbarrier.arrive.shared::cluster.b64 _, [ra];\n"
               "mapa.shared::cluster.u32 ra, %0, 1;\nmbarrier.arrive.shared::cluster.b64 _, [ra];\n}" ::"r"(a) : "memory");
}
__device__ __forceinline__ void mbar_wait(uint32_t a, uint32_t ph) {
  uint32_t ok;
#pragma unroll 1
  for (int n = 0; n < SPIN_LIMIT; n++) {
    asm volatile("{\n.reg .pred p;\nmbarrier.try_wait.parity.shared::cta.b64 p, [%1], %2;\nselp.u32 %0, 1, 0, p;\n}" : "=r"(ok) : "r"(a), "r"(ph) : "memory");
    if (ok) break;
  }
}
#define ELECT "{\n.reg .pred p;\nelect.sync _|p, 0xffffffff;\n@p "
__device__ __forceinline__ void e_expect(uint32_t a, uint32_t b) { asm volatile(ELECT "mbarrier.arrive.expect_tx.shared::cta.b64 _, [%0], %1;\n}" ::"r"(a), "r"(b) : "memory"); }
__device__ __forceinline__ void e_arrive(uint32_t a) { asm volatile(ELECT "mbarrier.arrive.shared::cta.b64 _, [%0];\n}" ::"r"(a) : "memory"); }
__device__ __forceinline__ void tma2d(uint32_t dst, const CUtensorMap* tm, int c0, int c1, uint32_t bar) {
  asm volatile(ELECT "cp.async.bulk.tensor.2d.shared::cluster.global.mbarrier::complete_tx::bytes [%0], [%1, {%3, %4}], [%2];\n}"
               ::"r"(dst), "l"(tm), "r"(bar), "r"(c0), "r"(c1) : "memory");
}
__device__ __forceinline__ void tma2d_mc(uint32_t dst, const CUtensorMap* tm, int c0, int c1, uint32_t bar) {
  asm volatile(ELECT "cp.async.bulk.tensor.2d.shared::cluster.global.mbarrier::complete_tx::bytes.multicast::cluster [%0], [%1, {%3, %4}], [%2], %5;\n}"
               ::"r"(dst), "l"(tm), "r"(bar), "r"(c0), "r"(c1), "h"((uint16_t)3) : "memory");
}
__device__ __forceinline__ void tma3d(uint32_t dst, const CUtensorMap* tm, int c0, int c1, int c2, uint32_t bar) {
  asm volatile(ELECT "cp.async.bulk.tensor.3d.shared::cluster.global.mbarrier::complete_tx::bytes [%0], [%1, {%3, %4, %5}], [%2];\n}"
               ::"r"(dst), "l"(tm), "r"(bar), "r"(c0), "r"(c1), "r"(c2) : "memory");
}
__device__ __forceinline__ void tma3d_mc(uint32_t dst, const CUtensorMap* tm, int c0, int c1, int c2, uint32_t bar) {
  asm volatile(ELECT "cp.async.bulk.tensor.3d.shared::cluster.global.mbarrier::complete_tx::bytes.multicast::cluster [%0], [%1, {%3, %4, %5}], [%2], %6;\n}"
               ::"r"(dst), "l"(tm), "r"(bar), "r"(c0), "r"(c1), "r"(c2), "h"((uint16_t)3) : "memory");
}
__device__ __forceinline__ void tma2d_pf(const CUtensorMap* tm, int c0, int c1) {
  asm volatile(ELECT "cp.async.bulk.prefetch.tensor.2d.L2.global [%0, {%1, %2}];\n}" ::"l"(tm), "r"(c0), "r"(c1) : "memory");
}
__device__ __forceinline__ void tm_prefetch(const CUtensorMap* tm) { asm volatile(ELECT "prefetch.tensormap [%0];\n}" ::"l"(tm) : "memory"); }
__device__ __forceinline__ void bulk(uint32_t dst, const void* src, uint32_t bytes, uint32_t bar) {
  asm volatile(ELECT "cp.async.bulk.shared::cluster.global.mbarrier::complete_tx::bytes [%0], [%1], %2, [%3];\n}"
               ::"r"(dst), "l"(src), "r"(bytes), "r"(bar) : "memory");
}
__device__ __forceinline__ void bulk_mc(uint32_t dst, const void* src, uint32_t bytes, uint32_t bar) {
  asm volatile(ELECT "cp.async.bulk.shared::cluster.global.mbarrier::complete_tx::bytes.multicast::cluster [%0], [%1], %2, [%3], %4;\n}"
               ::"r"(dst), "l"(src), "r"(bytes), "r"(bar), "h"((uint16_t)3) : "memory");
}
__device__ __forceinline__ void l2_prefetch(const void* src, uint32_t bytes) { asm volatile(ELECT "cp.async.bulk.prefetch.L2.global [%0], %1;\n}" ::"l"(src), "r"(bytes) : "memory"); }
__device__ __forceinline__ void fence_async() { asm volatile("fence.proxy.async.global;" ::: "memory"); }
__device__ __forceinline__ void fence_async_smem() { asm volatile("fence.proxy.async.shared::cta;" ::: "memory"); }
__device__ __forceinline__ void bar_sync(int id, int n) { asm volatile("bar.sync %0, %1;" ::"r"(id), "r"(n) : "memory"); }
__device__ __forceinline__ void bar_arrive(int id, int n) { asm volatile("bar.arrive %0, %1;" ::"r"(id), "r"(n) : "memory"); }
__device__ __forceinline__ void red_release(unsigned* p) { asm volatile("red.release.gpu.global.add.u32 [%0], 1;" ::"l"(p) : "memory"); }
__device__ __forceinline__ void red_relaxed(unsigned* p) { asm volatile("red.relaxed.gpu.global.add.u32 [%0], 1;" ::"l"(p) : "memory"); }
__device__ __forceinline__ uint32_t ld_back(const void* p) { uint32_t v; asm volatile("ld.relaxed.gpu.global.u32 %0, [%1];" : "=r"(v) : "l"(p) : "memory"); return v; }
__device__ __forceinline__ void consume(uint32_t v, uint32_t sb) { if (v == 0xDEADBEEFu) asm volatile("st.shared.u32 [%0], %1;" ::"r"(sb + SM_MISC + 60), "r"(v) : "memory"); }
__device__ __forceinline__ unsigned ld_acquire(const unsigned* p) { unsigned v; asm volatile("ld.acquire.gpu.global.u32 %0, [%1];" : "=r"(v) : "l"(p) : "memory"); return v; }
__device__ __forceinline__ void wait_ge(const unsigned* p, unsigned target) {
#pragma unroll 1
  for (int n = 0; n < SPIN_LIMIT; n++) {
    if ((int)(ld_acquire(p) - target) >= 0) break;
    __nanosleep(100);
  }
}
__device__ __forceinline__ void wg_fence() { asm volatile("wgmma.fence.sync.aligned;" ::: "memory"); }
__device__ __forceinline__ void wg_commit() { asm volatile("wgmma.commit_group.sync.aligned;" ::: "memory"); }
template <int N> __device__ __forceinline__ void wg_wait() { asm volatile("wgmma.wait_group.sync.aligned %0;" ::"n"(N) : "memory"); }
template <int n> __device__ __forceinline__ void regfence(float (&d)[n]) {
#pragma unroll
  for (int i = 0; i < n; i++) asm volatile("" : "+f"(d[i])::"memory");
}
__device__ __forceinline__ uint64_t mkdesc(uint32_t addr, uint32_t lbo, uint32_t sbo, int swz) {
  return (uint64_t)((addr & 0x3FFFF) >> 4) | ((uint64_t)(lbo >> 4) << 16) | ((uint64_t)(sbo >> 4) << 32) | ((uint64_t)swz << 62);
}
__device__ __forceinline__ uint32_t pack_bf16(float lo, float hi) { uint32_t r; asm("cvt.rn.bf16x2.f32 %0, %1, %2;" : "=r"(r) : "f"(hi), "f"(lo)); return r; }
__device__ __forceinline__ uint32_t pack_f16(float lo, float hi) { uint32_t r; asm("cvt.rn.f16x2.f32 %0, %1, %2;" : "=r"(r) : "f"(hi), "f"(lo)); return r; }
__device__ __forceinline__ float bf_lo(uint32_t v) { return __uint_as_float(v << 16); }
__device__ __forceinline__ float bf_hi(uint32_t v) { return __uint_as_float(v & 0xFFFF0000u); }
__device__ __forceinline__ float ex2(float x) { float r; asm("ex2.approx.ftz.f32 %0, %1;" : "=f"(r) : "f"(x)); return r; }
__device__ __forceinline__ float gelu2_tanh(float x) {
  float u = x * fmaf(x * x, 0.0356774081f, 0.7978845608f), t;
  asm("tanh.approx.f32 %0, %1;" : "=f"(t) : "f"(u));
  return fmaf(x, t, x);
}
__device__ __forceinline__ void sts32(uint32_t a, uint32_t v) { asm volatile("st.shared.u32 [%0], %1;" ::"r"(a), "r"(v) : "memory"); }
__device__ __forceinline__ void sts16(uint32_t a, uint16_t v) { asm volatile("st.shared.u16 [%0], %1;" ::"r"(a), "h"(v) : "memory"); }
__device__ __forceinline__ void sts128(uint32_t a, uint32_t x, uint32_t y, uint32_t z, uint32_t w) { asm volatile("st.shared.v4.u32 [%0], {%1,%2,%3,%4};" ::"r"(a), "r"(x), "r"(y), "r"(z), "r"(w) : "memory"); }
__device__ __forceinline__ uint32_t lds32(uint32_t a) { uint32_t v; asm volatile("ld.shared.u32 %0, [%1];" : "=r"(v) : "r"(a) : "memory"); return v; }
__device__ __forceinline__ float ldsf(uint32_t a) { return __uint_as_float(lds32(a)); }
__device__ __forceinline__ uint4 lds128(uint32_t a) { uint4 v; asm volatile("ld.shared.v4.u32 {%0,%1,%2,%3}, [%4];" : "=r"(v.x), "=r"(v.y), "=r"(v.z), "=r"(v.w) : "r"(a) : "memory"); return v; }

template<int OFF, int TOT> __device__ __forceinline__ void wg_ss_n88(float (&d)[TOT], uint64_t da, uint64_t db) {
  asm volatile("wgmma.mma_async.sync.aligned.m64n88k16.f32.bf16.bf16 {%0, %1, %2, %3, %4, %5, %6, %7, %8, %9, %10, %11, %12, %13, %14, %15, %16, %17, %18, %19, %20, %21, %22, %23, %24, %25, %26, %27, %28, %29, %30, %31, %32, %33, %34, %35, %36, %37, %38, %39, %40, %41, %42, %43}, %44, %45, 1, 1, 1, 0, 1;"
    : "+f"(d[OFF+0]), "+f"(d[OFF+1]), "+f"(d[OFF+2]), "+f"(d[OFF+3]), "+f"(d[OFF+4]), "+f"(d[OFF+5]), "+f"(d[OFF+6]), "+f"(d[OFF+7]),
      "+f"(d[OFF+8]), "+f"(d[OFF+9]), "+f"(d[OFF+10]), "+f"(d[OFF+11]), "+f"(d[OFF+12]), "+f"(d[OFF+13]), "+f"(d[OFF+14]), "+f"(d[OFF+15]),
      "+f"(d[OFF+16]), "+f"(d[OFF+17]), "+f"(d[OFF+18]), "+f"(d[OFF+19]), "+f"(d[OFF+20]), "+f"(d[OFF+21]), "+f"(d[OFF+22]), "+f"(d[OFF+23]),
      "+f"(d[OFF+24]), "+f"(d[OFF+25]), "+f"(d[OFF+26]), "+f"(d[OFF+27]), "+f"(d[OFF+28]), "+f"(d[OFF+29]), "+f"(d[OFF+30]), "+f"(d[OFF+31]),
      "+f"(d[OFF+32]), "+f"(d[OFF+33]), "+f"(d[OFF+34]), "+f"(d[OFF+35]), "+f"(d[OFF+36]), "+f"(d[OFF+37]), "+f"(d[OFF+38]), "+f"(d[OFF+39]),
      "+f"(d[OFF+40]), "+f"(d[OFF+41]), "+f"(d[OFF+42]), "+f"(d[OFF+43])
    : "l"(da), "l"(db));
}
template<int OFF, int TOT> __device__ __forceinline__ void wg_ss_n128(float (&d)[TOT], uint64_t da, uint64_t db) {
  asm volatile("wgmma.mma_async.sync.aligned.m64n128k16.f32.bf16.bf16 {%0, %1, %2, %3, %4, %5, %6, %7, %8, %9, %10, %11, %12, %13, %14, %15, %16, %17, %18, %19, %20, %21, %22, %23, %24, %25, %26, %27, %28, %29, %30, %31, %32, %33, %34, %35, %36, %37, %38, %39, %40, %41, %42, %43, %44, %45, %46, %47, %48, %49, %50, %51, %52, %53, %54, %55, %56, %57, %58, %59, %60, %61, %62, %63}, %64, %65, 1, 1, 1, 0, 1;"
    : "+f"(d[OFF+0]), "+f"(d[OFF+1]), "+f"(d[OFF+2]), "+f"(d[OFF+3]), "+f"(d[OFF+4]), "+f"(d[OFF+5]), "+f"(d[OFF+6]), "+f"(d[OFF+7]),
      "+f"(d[OFF+8]), "+f"(d[OFF+9]), "+f"(d[OFF+10]), "+f"(d[OFF+11]), "+f"(d[OFF+12]), "+f"(d[OFF+13]), "+f"(d[OFF+14]), "+f"(d[OFF+15]),
      "+f"(d[OFF+16]), "+f"(d[OFF+17]), "+f"(d[OFF+18]), "+f"(d[OFF+19]), "+f"(d[OFF+20]), "+f"(d[OFF+21]), "+f"(d[OFF+22]), "+f"(d[OFF+23]),
      "+f"(d[OFF+24]), "+f"(d[OFF+25]), "+f"(d[OFF+26]), "+f"(d[OFF+27]), "+f"(d[OFF+28]), "+f"(d[OFF+29]), "+f"(d[OFF+30]), "+f"(d[OFF+31]),
      "+f"(d[OFF+32]), "+f"(d[OFF+33]), "+f"(d[OFF+34]), "+f"(d[OFF+35]), "+f"(d[OFF+36]), "+f"(d[OFF+37]), "+f"(d[OFF+38]), "+f"(d[OFF+39]),
      "+f"(d[OFF+40]), "+f"(d[OFF+41]), "+f"(d[OFF+42]), "+f"(d[OFF+43]), "+f"(d[OFF+44]), "+f"(d[OFF+45]), "+f"(d[OFF+46]), "+f"(d[OFF+47]),
      "+f"(d[OFF+48]), "+f"(d[OFF+49]), "+f"(d[OFF+50]), "+f"(d[OFF+51]), "+f"(d[OFF+52]), "+f"(d[OFF+53]), "+f"(d[OFF+54]), "+f"(d[OFF+55]),
      "+f"(d[OFF+56]), "+f"(d[OFF+57]), "+f"(d[OFF+58]), "+f"(d[OFF+59]), "+f"(d[OFF+60]), "+f"(d[OFF+61]), "+f"(d[OFF+62]), "+f"(d[OFF+63])
    : "l"(da), "l"(db));
}
template<int OFF, int TOT> __device__ __forceinline__ void wg_ss_n64(float (&d)[TOT], uint64_t da, uint64_t db) {
  asm volatile("wgmma.mma_async.sync.aligned.m64n64k16.f32.bf16.bf16 {%0, %1, %2, %3, %4, %5, %6, %7, %8, %9, %10, %11, %12, %13, %14, %15, %16, %17, %18, %19, %20, %21, %22, %23, %24, %25, %26, %27, %28, %29, %30, %31}, %32, %33, 1, 1, 1, 0, 1;"
    : "+f"(d[OFF+0]), "+f"(d[OFF+1]), "+f"(d[OFF+2]), "+f"(d[OFF+3]), "+f"(d[OFF+4]), "+f"(d[OFF+5]), "+f"(d[OFF+6]), "+f"(d[OFF+7]),
      "+f"(d[OFF+8]), "+f"(d[OFF+9]), "+f"(d[OFF+10]), "+f"(d[OFF+11]), "+f"(d[OFF+12]), "+f"(d[OFF+13]), "+f"(d[OFF+14]), "+f"(d[OFF+15]),
      "+f"(d[OFF+16]), "+f"(d[OFF+17]), "+f"(d[OFF+18]), "+f"(d[OFF+19]), "+f"(d[OFF+20]), "+f"(d[OFF+21]), "+f"(d[OFF+22]), "+f"(d[OFF+23]),
      "+f"(d[OFF+24]), "+f"(d[OFF+25]), "+f"(d[OFF+26]), "+f"(d[OFF+27]), "+f"(d[OFF+28]), "+f"(d[OFF+29]), "+f"(d[OFF+30]), "+f"(d[OFF+31])
    : "l"(da), "l"(db));
}
template<int OFF, int TOT> __device__ __forceinline__ void wg_ss_n32t(float (&d)[TOT], uint64_t da, uint64_t db) {
  asm volatile("wgmma.mma_async.sync.aligned.m64n32k16.f32.bf16.bf16 {%0, %1, %2, %3, %4, %5, %6, %7, %8, %9, %10, %11, %12, %13, %14, %15}, %16, %17, 1, 1, 1, 1, 0;"
    : "+f"(d[OFF+0]), "+f"(d[OFF+1]), "+f"(d[OFF+2]), "+f"(d[OFF+3]), "+f"(d[OFF+4]), "+f"(d[OFF+5]), "+f"(d[OFF+6]), "+f"(d[OFF+7]),
      "+f"(d[OFF+8]), "+f"(d[OFF+9]), "+f"(d[OFF+10]), "+f"(d[OFF+11]), "+f"(d[OFF+12]), "+f"(d[OFF+13]), "+f"(d[OFF+14]), "+f"(d[OFF+15])
    : "l"(da), "l"(db));
}
template<int OFF, int TOT> __device__ __forceinline__ void wg_ss_n8(float (&d)[TOT], uint64_t da, uint64_t db) {
  asm volatile("wgmma.mma_async.sync.aligned.m64n8k16.f32.bf16.bf16 {%0, %1, %2, %3}, %4, %5, 1, 1, 1, 0, 0;"
    : "+f"(d[OFF+0]), "+f"(d[OFF+1]), "+f"(d[OFF+2]), "+f"(d[OFF+3])
    : "l"(da), "l"(db));
}
template<int SCD, int OFF, int TOT> __device__ __forceinline__ void wg_qk_n64(float (&d)[TOT], uint32_t a0, uint32_t a1, uint32_t a2, uint32_t a3, uint64_t db) {
  asm volatile("wgmma.mma_async.sync.aligned.m64n64k16.f32.f16.f16 {%0, %1, %2, %3, %4, %5, %6, %7, %8, %9, %10, %11, %12, %13, %14, %15, %16, %17, %18, %19, %20, %21, %22, %23, %24, %25, %26, %27, %28, %29, %30, %31}, {%32,%33,%34,%35}, %36, %37, 1, 1, 0;"
    : "+f"(d[OFF+0]), "+f"(d[OFF+1]), "+f"(d[OFF+2]), "+f"(d[OFF+3]), "+f"(d[OFF+4]), "+f"(d[OFF+5]), "+f"(d[OFF+6]), "+f"(d[OFF+7]),
      "+f"(d[OFF+8]), "+f"(d[OFF+9]), "+f"(d[OFF+10]), "+f"(d[OFF+11]), "+f"(d[OFF+12]), "+f"(d[OFF+13]), "+f"(d[OFF+14]), "+f"(d[OFF+15]),
      "+f"(d[OFF+16]), "+f"(d[OFF+17]), "+f"(d[OFF+18]), "+f"(d[OFF+19]), "+f"(d[OFF+20]), "+f"(d[OFF+21]), "+f"(d[OFF+22]), "+f"(d[OFF+23]),
      "+f"(d[OFF+24]), "+f"(d[OFF+25]), "+f"(d[OFF+26]), "+f"(d[OFF+27]), "+f"(d[OFF+28]), "+f"(d[OFF+29]), "+f"(d[OFF+30]), "+f"(d[OFF+31])
    : "r"(a0), "r"(a1), "r"(a2), "r"(a3), "l"(db), "n"(SCD));
}
template<int SCD, int OFF, int TOT> __device__ __forceinline__ void wg_pv_n24(float (&d)[TOT], uint32_t a0, uint32_t a1, uint32_t a2, uint32_t a3, uint64_t db) {
  asm volatile("wgmma.mma_async.sync.aligned.m64n24k16.f32.bf16.bf16 {%0, %1, %2, %3, %4, %5, %6, %7, %8, %9, %10, %11}, {%12,%13,%14,%15}, %16, %17, 1, 1, 1;"
    : "+f"(d[OFF+0]), "+f"(d[OFF+1]), "+f"(d[OFF+2]), "+f"(d[OFF+3]), "+f"(d[OFF+4]), "+f"(d[OFF+5]), "+f"(d[OFF+6]), "+f"(d[OFF+7]),
      "+f"(d[OFF+8]), "+f"(d[OFF+9]), "+f"(d[OFF+10]), "+f"(d[OFF+11])
    : "r"(a0), "r"(a1), "r"(a2), "r"(a3), "l"(db), "n"(SCD));
}
template<int SCD, int OFF, int TOT> __device__ __forceinline__ void wg_qkb_n64(float (&d)[TOT], uint32_t a0, uint32_t a1, uint32_t a2, uint32_t a3, uint64_t db) {
  asm volatile("wgmma.mma_async.sync.aligned.m64n64k16.f32.bf16.bf16 {%0, %1, %2, %3, %4, %5, %6, %7, %8, %9, %10, %11, %12, %13, %14, %15, %16, %17, %18, %19, %20, %21, %22, %23, %24, %25, %26, %27, %28, %29, %30, %31}, {%32,%33,%34,%35}, %36, %37, 1, 1, 0;"
    : "+f"(d[OFF+0]), "+f"(d[OFF+1]), "+f"(d[OFF+2]), "+f"(d[OFF+3]), "+f"(d[OFF+4]), "+f"(d[OFF+5]), "+f"(d[OFF+6]), "+f"(d[OFF+7]),
      "+f"(d[OFF+8]), "+f"(d[OFF+9]), "+f"(d[OFF+10]), "+f"(d[OFF+11]), "+f"(d[OFF+12]), "+f"(d[OFF+13]), "+f"(d[OFF+14]), "+f"(d[OFF+15]),
      "+f"(d[OFF+16]), "+f"(d[OFF+17]), "+f"(d[OFF+18]), "+f"(d[OFF+19]), "+f"(d[OFF+20]), "+f"(d[OFF+21]), "+f"(d[OFF+22]), "+f"(d[OFF+23]),
      "+f"(d[OFF+24]), "+f"(d[OFF+25]), "+f"(d[OFF+26]), "+f"(d[OFF+27]), "+f"(d[OFF+28]), "+f"(d[OFF+29]), "+f"(d[OFF+30]), "+f"(d[OFF+31])
    : "r"(a0), "r"(a1), "r"(a2), "r"(a3), "l"(db), "n"(SCD));
}

__device__ __forceinline__ uint32_t exp_mufu(float a, float b) { return pack_bf16(ex2(a), ex2(b)); }
__device__ __forceinline__ uint32_t exp_poly(float a, float b, uint32_t mlo, uint32_t mhi) {
  uint32_t u = __byte_perm(__float_as_uint(a), __float_as_uint(b), 0x6521), mh, e, p;
  asm("lop3.b32 %0, %1, %2, 0x3F003F00, 0xEA;" : "=r"(mh) : "r"(u), "r"(mlo));
  asm("lop3.b32 %0, %1, %2, 0x00020002, 0xEA;" : "=r"(e) : "r"(u), "r"(mhi));
  asm("fma.rn.bf16x2 %0, %1, %2, %3;" : "=r"(p) : "r"(u), "r"(mh), "r"(e));
  return p;
}
constexpr float MAGIC_C = 48948.0625f;
constexpr float QSCALE = 0.25f * 1.4426950408889634f * 8.f;
constexpr float BOUND = 80.f;

__device__ __forceinline__ void softmax_step(const float (&s)[32], uint32_t (&p)[16], uint32_t mlo, uint32_t mhi) {
  constexpr int PP = NP / 4;
  int ip = 0, im = PP;
#pragma unroll
  for (int i = 0; i < 16; i++) {
    if (((i + 1) * PP / 16) > (i * PP / 16)) { p[ip] = exp_poly(s[2 * ip], s[2 * ip + 1], mlo, mhi); ip++; }
    else { p[im] = exp_mufu(s[2 * im], s[2 * im + 1]); im++; }
  }
}
constexpr int64_t VSTEP = 32 - (32 << 16);
constexpr uint64_t VSTEP8 = (uint64_t)(8 * VSTEP);
constexpr uint64_t KOFF = (uint64_t)(-128ll);
__device__ __forceinline__ void issue_qk(float (&s)[32], const uint32_t (&q)[4], uint64_t dk) { wg_qk_n64<1, 0, 32>(s, q[0], q[1], q[2], q[3], dk); }
__device__ __forceinline__ void issue_pv(float (&o)[12], const uint32_t (&p)[16], uint64_t dv) {
#pragma unroll
  for (int c = 0; c < 4; c++) { wg_pv_n24<1, 0, 12>(o, p[4 * c], p[4 * c + 1], p[4 * c + 2], p[4 * c + 3], dv + c * VSTEP); }
}

__device__ __forceinline__ uint32_t wslot(int f) { const int r = f - 5 * ((f * 52) >> 8); return r == 4 ? SM_Q : SM_RING + r * WSLOT; }

struct Params {
  const __nv_bfloat16* gate_w;
  const __nv_bfloat16* b_sp;
  const __nv_bfloat16* w_out;
  const __nv_bfloat16* wo;
  const __nv_bfloat16* w_in;
  const __nv_bfloat16* wq;
  const __nv_bfloat16* wk;
  const __nv_bfloat16* wv;
};

__device__ __forceinline__ float rcp(float x) { float r; asm("rcp.approx.ftz.f32 %0, %1;" : "=f"(r) : "f"(x)); return r; }
__device__ __forceinline__ int tile_of(int tau) { return (0x74632510u >> (4 * tau)) & 7; }
__device__ __forceinline__ uint32_t store_o_tile(const float (&o)[12], uint32_t* obase, uint32_t gbase, int lam, int lane) {
  const float f0 = ldsf(gbase + (lam & 1) * 256) * rcp(o[8]), f1 = ldsf(gbase + (lam & 1) * 256 + 32) * rcp(o[10]);
  uint32_t* dst = obase + lam * 4096;
  dst[0] = pack_bf16(o[0] * f0, o[1] * f0);
  dst[32] = pack_bf16(o[4] * f0, o[5] * f0);
  dst[64] = pack_bf16(o[2] * f1, o[3] * f1);
  dst[96] = pack_bf16(o[6] * f1, o[7] * f1);
  return ld_back(dst + (lane & 15) * 8 - lane);
}

__global__ void __cluster_dims__(2, 1, 1) __launch_bounds__(NTHREADS, 1)
fused_kernel(const __grid_constant__ CUtensorMap tm_x, const __grid_constant__ CUtensorMap tm_wq,
             const __grid_constant__ CUtensorMap tm_win, const __grid_constant__ CUtensorMap tm_wsp,
             const __grid_constant__ CUtensorMap tm_wout, const __grid_constant__ CUtensorMap tm_wo,
             const __grid_constant__ CUtensorMap tm_out, const Params prm) {
  extern __shared__ __align__(1024) uint8_t smem_raw[];
  const uint32_t sb = __shfl_sync(0xffffffffu, (uint32_t)__cvta_generic_to_shared(smem_raw), 0);
  const int warp = __shfl_sync(0xffffffffu, (int)(threadIdx.x >> 5), 0);
  const int wg = warp >> 2;
  const int tid = threadIdx.x & 127;
  const int lane = threadIdx.x & 31;
  const int rank = blockIdx.x & 1;
  const int ai = (blockIdx.x >> 4) * 2 + rank, aj = (blockIdx.x >> 1) & 7;
  const int bi = blockIdx.x >> 3, bj = blockIdx.x & 7;
  auto BAR = [&](int k) { return sb + SM_BAR + 8u * k; };

  if (warp == 16) {
    if (lane == 0) {
      mbar_init(BAR(B_XFULL), 1); mbar_init(BAR(B_XFULL + 1), 1);
      asm volatile("fence.mbarrier_init.release.cluster;" ::: "memory");
    }
    __syncwarp();
    e_expect(BAR(B_XFULL), 16384);
    tma2d(sb + SM_K, &tm_x, 0, ai * 128, BAR(B_XFULL));
    e_expect(BAR(B_XFULL + 1), 16384);
    tma2d(sb + SM_K + 16384, &tm_x, 64, ai * 128, BAR(B_XFULL + 1));
    if (lane == 0) TS(36);
  } else if (warp == 18) {
    if (lane == 0) { mbar_init(BAR(B_WFULL), 1); asm volatile("fence.mbarrier_init.release.cluster;" ::: "memory"); }
    __syncwarp();
    e_expect(BAR(B_WFULL), 16384);
#pragma unroll
    for (int h = 0; h < 2; h++) {
      tma3d(sb + SM_RING + h * 8192, &tm_win, 0, h * 32, aj < 6 ? 21 + 3 * aj : 27 + 2 * aj, BAR(B_WFULL));
      tma2d(sb + SM_RING + h * 8192 + 6144, &tm_wq, 64 * aj, h * 32, BAR(B_WFULL));
    }
  } else if (warp == 19) {
    l2_prefetch(reinterpret_cast<const uint8_t*>(prm.w_in) + blockIdx.x * 11008, 11008);
    l2_prefetch(reinterpret_cast<const uint8_t*>(prm.wq) + blockIdx.x * 4096, 4096);
  } else if (warp < 16 && lane == 0) {
#pragma unroll
    for (int r = 0; r < 4; r++) {
      const int k = warp + 16 * r;
      uint32_t cnt = 1;
      if (k >= B_XEMPTY && k < B_XEMPTY + 8) cnt = 4;
      if (k >= B_WEMPTY && k < B_WEMPTY + 11) cnt = 4;
      if (k == B_ZST0 || k == B_ZST1) cnt = 8;
      if (k >= B_REMPTY && k < B_REMPTY + 3) cnt = 2;
      if (k == B_ATT) cnt = 6;
      if (k == B_QRDY) cnt = 16;
      if (k == B_KSTAT) cnt = 17;
      if (k == B_LNOK) cnt = 8;
      if (k == B_WOFULL) cnt = 3;
      if (k >= 2 && k != B_WFULL) mbar_init(BAR(k), cnt);
    }
    asm volatile("fence.mbarrier_init.release.cluster;" ::: "memory");
  }
  __syncthreads();
  if (threadIdx.x == 0) TS(35);
  asm volatile("barrier.cluster.arrive.relaxed.aligned;" ::: "memory");
  asm volatile("barrier.cluster.wait.acquire.aligned;" ::: "memory");

  if (wg == 4) {
    asm volatile("setmaxnreg.dec.sync.aligned.u32 24;");
    if (warp == 16 || warp == 19) {
      const int t = (warp == 19) * 32 + lane, tok = t >> 1, hf = t & 1;
      const int slot = ai * 4 + (aj >> 1), isv = aj & 1;
      const uint32_t sB = sb + SM_WKV, sH = sb + SM_WKV + 1024;
      bar_sync(11, 192);
      uint4 val = lds128(sB + t * 16);
      uint32_t stat = 0;
      if (isv) {
        const uint32_t vv[4] = {val.x, val.y, val.z, val.w};
#pragma unroll
        for (int e = 0; e < 4; e++) {
          const uint32_t a = vv[e] & 0x7FFFu, b = (vv[e] >> 16) & 0x7FFFu;
          if (a >= 0x3580u) stat |= 1u << (2 * e);
          if (b >= 0x3580u) stat |= 2u << (2 * e);
          if (max(a, b) > 0x4E80u) stat |= 1u << (16 - 8 * hf);
        }
        stat = __reduce_or_sync(0xffffffffu, stat << (8 * hf));
      } else {
        float n2 = bf_lo(val.x) * bf_lo(val.x);
        n2 = fmaf(bf_hi(val.x), bf_hi(val.x), n2); n2 = fmaf(bf_lo(val.y), bf_lo(val.y), n2); n2 = fmaf(bf_hi(val.y), bf_hi(val.y), n2);
        n2 = fmaf(bf_lo(val.z), bf_lo(val.z), n2); n2 = fmaf(bf_hi(val.z), bf_hi(val.z), n2);
        n2 = fmaf(bf_lo(val.w), bf_lo(val.w), n2); n2 = fmaf(bf_hi(val.w), bf_hi(val.w), n2);
        n2 += __shfl_xor_sync(0xffffffffu, n2, 1);
        if (!(n2 <= 3.0e38f)) n2 = 3.0e38f;
        stat = __reduce_max_sync(0xffffffffu, __float_as_uint(n2));
      }
      if (lane == 0) sts32(sb + SM_MISC + 4 * (M_KVR + (t >> 5)), stat);
      const uint32_t off = slot * 2 + (hf ^ ((slot >> 2) & 1));
      uint32_t chk = 0;
      if (!isv) {
        g_kbf[tok * 128 + off] = val;
        chk = ld_back(&g_kbf[tok * 128 + off]);
        if (t < 48) {
          const int sg = t >> 4, j1 = sg == 0 ? 10 : (sg == 1 ? 22 : 32);
          const float sc = slot < NP ? 16.f : 0.125f;
          uint32_t a = sB + (sg == 0 ? 0 : (sg == 1 ? 10 : 22)) * 32 + (t & 15) * 2;
          const uint32_t ae = sB + j1 * 32;
          float run = 0.f;
#pragma unroll 2
          for (; a < ae; a += 32) {
            uint16_t kx;
            asm volatile("ld.shared.u16 %0, [%1];" : "=h"(kx) : "r"(a));
            const __half hv = __float2half_rn(fmaf(__uint_as_float((uint32_t)kx << 16), sc, -run));
            run += __half2float(hv);
            sts16(a + 1024, __half_as_ushort(hv));
          }
        }
        bar_sync(10, 64);
        val = lds128(sH + t * 16);
      }
      g_kimg[tok * 256 + isv * 128 + off] = val;
      chk ^= ld_back(&g_kimg[tok * 256 + isv * 128 + off]);
      mbar_wait(BAR(B_EPOCH), 0);
      consume(chk, sb);
      fence_async();
      bar_sync(10, 64);
      if (t == 0) {
        const uint32_t s0 = lds32(sb + SM_MISC + 4 * M_KVR), s1 = lds32(sb + SM_MISC + 4 * (M_KVR + 1));
        const unsigned long long fl = ((unsigned long long)(lds32(sb + SM_MISC + 4 * M_EPOCH) + 1) << 32) | (isv ? (s0 | s1) : max(s0, s1));
        asm volatile("st.relaxed.gpu.global.b64 [%0], %1;" ::"l"(&g_kvflag[ai * 8 + aj]), "l"(fl) : "memory");
        TS(23);
      }
      __syncwarp();
    }
    if (warp == 18) {
#pragma unroll 1
      for (int f = 1; f < 16; f++) {
        if (f == 1 && lane == 0) TS(0);
        if (f == 5 && lane == 0) TS(37);
        if (f >= 5) mbar_wait(BAR(B_WEMPTY + f - 5), 0);
        const uint32_t dst = sb + wslot(f) + rank * 8192, bar = BAR(B_WFULL + f);
        const int k0 = (f & 7) * 64 + rank * 32;
        e_expect(bar, 16384);
        tma3d_mc(dst, &tm_win, 0, k0, f < 8 ? (aj < 6 ? 21 + 3 * aj : 27 + 2 * aj) : (aj < 2 ? 2 * aj : 3 * aj - 2), bar);
        tma2d_mc(dst + 6144, &tm_wq, 64 * aj + (f >> 3) * 32, k0, bar);
        if (f < 7) {
          e_expect(BAR(B_XFULL + 1 + f), 16384);
          tma2d(sb + SM_K + (f + 1) * 16384, &tm_x, (f + 1) * 64, ai * 128, BAR(B_XFULL + 1 + f));
        }
      }
      if (lane == 0) TS(1);
    } else if (warp == 19) {
      mbar_wait(BAR(B_ZST0), 0);
      if (lane == 0) { red_release(&g_zcnt[ai * 32]); TS(20); }
      __syncwarp();
      const unsigned ep1 = lds32(sb + SM_MISC + 4 * M_EPOCH) + 1;
      wait_ge(&g_zcnt[(lane & 15) * 32], ep1 * 8);
      __syncwarp();
      e_arrive(BAR(B_ZOK));
      mbar_wait(BAR(B_ZST1), 0);
      if (lane == 0) { red_release(&g_z1cnt[ai * 32]); TS(17); }
      __syncwarp();
      l2_prefetch(reinterpret_cast<const uint8_t*>(prm.w_out) + blockIdx.x * 5504, 5504);
      l2_prefetch(reinterpret_cast<const uint8_t*>(prm.wo) + blockIdx.x * 4096, 4096);
      wait_ge(&g_z1cnt[bi * 32], ep1 * 8);
      e_arrive(BAR(B_Z1OK));
    } else if (warp == 16) {
      tm_prefetch(&tm_wsp);
      tm_prefetch(&tm_wout);
      tm_prefetch(&tm_wo);
      tm_prefetch(&tm_out);
      mbar_wait(BAR(B_XEMPTY), 0);
      tma2d_pf(&tm_wsp, (bj >> 1) * 64, bi * 128 + rank * 64);
      tma2d_pf(&tm_wsp, (bj >> 1) * 64 + 256, bi * 128 + rank * 64);
    } else {
      if (lane == 0) {
        sts32(sb + SM_MISC + 4 * M_EPOCH, atomicAdd(&g_ticket, 1u) / NCTA);
        mbar_arrive(BAR(B_EPOCH));
        TS(71);
      }
      __syncwarp();
      const unsigned ep1 = lds32(sb + SM_MISC + 4 * M_EPOCH) + 1;
      e_expect(BAR(B_KVFULL), 49152);
      e_expect(BAR(B_KVB), 49152);
      e_expect(BAR(B_KVC), 32768);
      mbar_wait(BAR(B_WFULL + 8), 0);
      uint32_t kn = 0, vb = 0;
#pragma unroll 1
      for (int n = 0; n < SPIN_LIMIT; n++) {
        unsigned long long a, b, c, d;
        asm volatile("ld.relaxed.gpu.global.v2.b64 {%0, %1}, [%2];" : "=l"(a), "=l"(b) : "l"(&g_kvflag[2 * lane]) : "memory");
        asm volatile("ld.relaxed.gpu.global.v2.b64 {%0, %1}, [%2];" : "=l"(c), "=l"(d) : "l"(&g_kvflag[64 + 2 * lane]) : "memory");
        kn = max((uint32_t)a, (uint32_t)c); vb = (uint32_t)b | (uint32_t)d;
        if (__all_sync(0xffffffffu, (uint32_t)(a >> 32) == ep1 && (uint32_t)(b >> 32) == ep1 && (uint32_t)(c >> 32) == ep1 && (uint32_t)(d >> 32) == ep1)) break;
        __nanosleep(100);
      }
      asm volatile("fence.acquire.gpu;" ::: "memory");
      kn = __reduce_max_sync(0xffffffffu, kn);
      vb = __reduce_or_sync(0xffffffffu, vb);
      if (lane == 0) {
        TS(6);
        sts32(sb + SM_MISC + 4 * M_KN2, kn);
        sts32(sb + SM_MISC + 4 * M_VOK, vb == 0xFFFFu ? 1u : 0u);
        mbar_arrive(BAR(B_KSTAT));
      }
      __syncwarp();
      fence_async();
      mbar_wait(BAR(B_LNOK), 0);
#pragma unroll 1
      for (int c = 0; c < 8; c++) {
        const uint32_t off = c * 16384 + rank * 8192;
        mbar_wait(BAR(B_XEMPTY + c), 0);
        bulk_mc(sb + SM_K + off, reinterpret_cast<const uint8_t*>(g_kimg) + off, 8192, BAR(c < 3 ? B_KVFULL : (c < 6 ? B_KVB : B_KVC)));
      }
      if (lane == 0) TS(7);
      mbar_wait(BAR(B_DEC), 0);
      if (!lds32(sb + SM_MISC + 4 * M_FAST)) {
        mbar_wait(BAR(B_KVFULL), 0); mbar_wait(BAR(B_KVB), 0); mbar_wait(BAR(B_KVC), 0);
        e_expect(BAR(B_KFB), 65536);
#pragma unroll 1
        for (int j = 0; j < 32; j++) bulk(sb + SM_K + j * 4096, g_kbf + j * 128, 2048, BAR(B_KFB));
      }
    }
    const unsigned ep1 = lds32(sb + SM_MISC + 4 * M_EPOCH) + 1;
    if (warp < 19) {
      const int st = warp - 16, row = bi * 128 + rank * 64;
      const uint32_t stg = sb + SM_RING + st * RSTAGE, full = BAR(B_RFULL + st), empty = BAR(B_REMPTY + st);
      mbar_wait(BAR(B_XEMPTY + 7), 0);
      mbar_wait(BAR(B_ZOK), 0);
      fence_async();
      if (threadIdx.x == 512) TS(2);
      const uint8_t* zsrc = reinterpret_cast<const uint8_t*>(g_z2n) + (bj * 32 + st) * 11264;
      int n = st, ph = 1;
#pragma unroll 1
      for (; n < 32; n += 3, zsrc += 3 * 11264, ph ^= 1) {
        mbar_wait(empty, ph);
        e_expect(full, 16384 + 11264);
        tma2d_mc(stg + rank * 8192, &tm_wsp, n * 64, row, full);
        bulk(stg + 16384, zsrc, 11264, full);
        if ((n & 3) == (bj >> 1) && n < 24) tma2d_pf(&tm_wsp, (n + 8) * 64, row);
      }
      if (n == 32) {
        mbar_wait(empty, ph);
        mbar_wait(BAR(B_Z1OK), 0);
        fence_async();
        e_expect(full, 22528 + 512 + 256);
        bulk(stg, g_z1 + (bi * 88 + bj * 11) * 128, 22528, full);
        bulk(stg + 22528, g_gate + bi * 128, 512, full);
        bulk(stg + 23040, prm.b_sp + bi * 128, 256, full);
        n += 3; ph ^= 1;
      }
      bool first = true;
#pragma unroll 1
      for (; n < 44; n += 3, ph ^= 1) {
        mbar_wait(empty, ph);
        e_expect(full, 16384 + 8192);
        tma2d(stg + 16384, &tm_wout, 64 * bj, (n - 33) * 64, full);
        if (first) { wait_ge(&g_ucnt[bi * 32], ep1 * 8); fence_async(); first = false; if (threadIdx.x == 512) TS(3); }
        bulk_mc(stg + rank * 8192, reinterpret_cast<const uint8_t*>(g_u) + (bi * 11 + n - 33) * 16384 + rank * 8192, 8192, full);
      }
      mbar_wait(empty, ph);
      e_expect(BAR(B_WOFULL), st == 2 ? 16384 : 24576);
#pragma unroll 1
      for (int c = 3 * st; c < 3 * st + 3 && c < 8; c++) tma2d(stg + (c - 3 * st) * 8192, &tm_wo, 64 * bj, c * 64, BAR(B_WOFULL));
      if (threadIdx.x == 512) TS(4);
    }
    const int c0 = warp - 16;
    const uint32_t ooff = c0 * 16384 + rank * 8192;
    const uint8_t* osrc = reinterpret_cast<const uint8_t*>(g_o) + bi * 131072 + ooff;
    e_expect(BAR(B_XFULL + c0), 16384);
    e_expect(BAR(B_XFULL + c0 + 4), 16384);
    wait_ge(&g_ocnt[bi * 32 + 16 * 32], ep1 * 24);
    fence_async();
    mbar_wait(BAR(B_ATT), 0);
    bulk_mc(sb + SM_K + ooff, osrc, 8192, BAR(B_XFULL + c0));
    if (c0) {
#pragma unroll 1
      for (int n = 0; n < SPIN_LIMIT; n++) if ((int)(ld_acquire(&g_ocnt[bi * 32]) - ep1 * 24) >= 0) break;
      fence_async();
      if (threadIdx.x == 544) TS(5);
    }
    bulk_mc(sb + SM_K + ooff + 65536, osrc + 65536, 8192, BAR(B_XFULL + c0 + 4));
  } else {
    asm volatile("setmaxnreg.inc.sync.aligned.u32 112;");
    const int w = tid >> 5, g = lane >> 2, t4 = lane & 3, half = wg & 1;
    {
      float acc[64];
      if (wg == 2) {
        const uint4* wsrc = reinterpret_cast<const uint4*>(aj & 1 ? prm.wv : prm.wk) + tid;
        uint4 wr[8];
#pragma unroll
        for (int r = 0; r < 8; r++) wr[r] = __ldg(wsrc + 128 * r);
#pragma unroll
        for (int r = 0; r < 8; r++) sts128(sb + SM_WKV + r * 2048 + (tid >> 1) * 32 + (((tid ^ (tid >> 3)) & 1) << 4), wr[r].x, wr[r].y, wr[r].z, wr[r].w);
        fence_async_smem();
        bar_sync(3, 128);
        float kv[16];
#pragma unroll
        for (int k = 0; k < 16; k++) kv[k] = 0.f;
        regfence(kv);
#pragma unroll 1
        for (int c = 0; c < 8; c++) {
          mbar_wait(BAR(B_XFULL + c), 0);
          const uint64_t da = mkdesc(sb + SM_WKV + c * 2048, 0, 256, 3);
          const uint64_t db = mkdesc(sb + SM_K + c * 16384 + (aj >> 1) * 4096, 16, 1024, 1);
          wg_fence();
#pragma unroll
          for (int k = 0; k < 4; k++) wg_ss_n32t<0, 16>(kv, da + 32 * k, db + 2 * k);
          wg_commit();
        }
        wg_wait<0>();
        regfence(kv);
        if (tid == 0) TS(22);
        bar_sync(3, 128);
        {
          const float a = w & 1 ? kv[4] : kv[0], b = w & 1 ? kv[5] : kv[1], c = w & 1 ? kv[6] : kv[2], d = w & 1 ? kv[7] : kv[3];
          const float e = w & 1 ? kv[12] : kv[8], f = w & 1 ? kv[13] : kv[9], h = w & 1 ? kv[14] : kv[10], i = w & 1 ? kv[15] : kv[11];
          const uint32_t lo = pack_bf16(w & 2 ? e : a, w & 2 ? f : b), hi = pack_bf16(w & 2 ? h : c, w & 2 ? i : d);
          const uint32_t p = sb + SM_WKV + (w * 8 + 2 * t4) * 32 + g * 2;
          sts16(p, (uint16_t)lo); sts16(p + 32, (uint16_t)(lo >> 16)); sts16(p + 16, (uint16_t)hi); sts16(p + 48, (uint16_t)(hi >> 16));
        }
        bar_arrive(11, 192);
        if (tid == 0) TS(64);
      } else if (wg == 3) {
        if (tid < 64) { const uint4 gv = __ldg(reinterpret_cast<const uint4*>(prm.gate_w) + tid); sts128(sb + SM_GW + tid * 16, gv.x, gv.y, gv.z, gv.w); }
        sts32(sb + SM_ONES + tid * 4, 0x3F803F80u);
        fence_async_smem();
        bar_sync(4, 128);
        float ga[8];
#pragma unroll
        for (int k = 0; k < 8; k++) ga[k] = 0.f;
        regfence(ga);
#pragma unroll 1
        for (int c = 0; c < 8; c++) {
          mbar_wait(BAR(B_XFULL + c), 0);
          if (tid == 0) TS(40 + c);
          const uint64_t da = mkdesc(sb + SM_K + c * 16384, 16, 1024, 1), db = mkdesc(sb + SM_GW + c * 128, 16, 128, 0);
          wg_fence();
#pragma unroll
          for (int k = 0; k < 4; k++) { wg_ss_n8<0, 8>(ga, da + 2 * k, db + 2 * k); wg_ss_n8<4, 8>(ga, da + 512 + 2 * k, db + 2 * k); }
          wg_commit();
        }
        wg_wait<0>();
        regfence(ga);
        const float g0 = __shfl_sync(0xffffffffu, ga[0], lane & 28), g1 = __shfl_sync(0xffffffffu, ga[2], lane & 28);
        const float g2 = __shfl_sync(0xffffffffu, ga[4], lane & 28), g3 = __shfl_sync(0xffffffffu, ga[6], lane & 28);
        const float gs = t4 & 2 ? (t4 & 1 ? g3 : g2) : (t4 & 1 ? g1 : g0);
        sts32(sb + SM_G + ((t4 >> 1) * 64 + w * 16 + (t4 & 1) * 8 + g) * 4, __float_as_uint(__fdividef(1.f, 1.f + __expf(-gs))));
        bar_sync(4, 128);
        if (aj == 0) g_gate[ai * 128 + tid] = ldsf(sb + SM_G + tid * 4);
        if (tid == 0) TS(8);
      }
#pragma unroll
      for (int k = 0; k < 64; k++) acc[k] = 0.f;
      regfence(acc);
      const int pass = wg >> 1;
#pragma unroll 1
      for (int c = 0; c < 8; c++) {
        mbar_wait(BAR(B_XFULL + c), 0);
        mbar_wait(BAR(B_WFULL + pass * 8 + c), 0);
        if (tid == 0 && half == pass) TS(48 + pass * 8 + c);
        const uint64_t da = mkdesc(sb + SM_K + c * 16384 + half * 8192, 16, 1024, 1);
        const uint64_t db = mkdesc(sb + wslot(pass * 8 + c), 2048, 512, 2);
        wg_fence();
#pragma unroll
        for (int k = 0; k < 4; k++) wg_ss_n128<0, 64>(acc, da + 2 * k, db + (k & 1) * 64 + (k >> 1) * 512);
        wg_commit();
        wg_wait<1>();
        if (tid == 0 && c > 0) {
          if (pass * 8 + c < 12) mbar_arrive_both(BAR(B_WEMPTY + pass * 8 + c - 1));
          if (pass) mbar_arrive_both(BAR(B_XEMPTY + c - 1));
        }
      }
      wg_wait<0>();
      if (tid == 0) mbar_arrive_both(BAR(pass ? B_XEMPTY + 7 : B_WEMPTY + 7));
      regfence(acc);
      if (tid == 0) TS(wg == 0 ? 16 : (wg == 2 ? 24 : (wg == 3 ? 9 : 95)));
      uint32_t qb[8];
      {
        float n2 = 0.f;
#pragma unroll
        for (int k = 0; k < 8; k++) qb[k] = pack_bf16(acc[48 + 2 * k], acc[49 + 2 * k]);
#pragma unroll
        for (int k = 0; k < 4; k++) {
          const uint32_t a = qb[4 * (k >> 1) + (k & 1)], b = qb[4 * (k >> 1) + (k & 1) + 2];
          float s = bf_lo(a) * bf_lo(a);
          s = fmaf(bf_hi(a), bf_hi(a), s); s = fmaf(bf_lo(b), bf_lo(b), s); s = fmaf(bf_hi(b), bf_hi(b), s);
          s += __shfl_xor_sync(0xffffffffu, s, 1); s += __shfl_xor_sync(0xffffffffu, s, 2);
          if (!(s <= 3.0e38f)) s = 3.0e38f;
          n2 = fmaxf(n2, s);
        }
        const uint32_t nmax = __reduce_max_sync(0xffffffffu, __float_as_uint(n2));
        if (lane == 0) { sts32(sb + SM_MISC + 4 * (M_RED + warp), nmax); mbar_arrive(BAR(B_KSTAT)); }
      }
      auto finish_q = [&]() {
        mbar_wait(BAR(B_KSTAT), 0);
        const float qn2 = __uint_as_float(__reduce_max_sync(0xffffffffu, lds32(sb + SM_MISC + 4 * (M_RED + (lane & 15)))));
        const float kn2 = ldsf(sb + SM_MISC + 4 * M_KN2);
        constexpr float SC = QSCALE * 0.125f;
        const bool fast = lds32(sb + SM_MISC + 4 * M_VOK) && qn2 <= 4.0e8f && kn2 <= 4.0e6f && qn2 * kn2 * (SC * SC) <= BOUND * BOUND;
        if (fast) {
#pragma unroll
          for (int k = 0; k < 8; k++) qb[k] = pack_f16(bf_lo(qb[k]) * QSCALE, bf_hi(qb[k]) * QSCALE);
        }
        sts128(sb + SM_Q + wg * 2048 + pass * 4096 + tid * 16, qb[0], qb[1], qb[2], qb[3]);
        sts128(sb + SM_Q + wg * 2048 + pass * 4096 + 4096 + tid * 16, qb[4], qb[5], qb[6], qb[7]);
        if (threadIdx.x == 256) { sts32(sb + SM_MISC + 4 * M_FAST, fast ? 1u : 0u); sts32(sb + SM_MISC + 4 * M_MASK, 0x007F007Fu); mbar_arrive(BAR(B_DEC)); }
        __syncwarp();
        if (lane == 0) mbar_arrive(BAR(B_QRDY));
        if (tid == 0 && pass) TS(75 + wg);
      };
      if (pass) finish_q();
#pragma unroll
      for (int k = 0; k < 48; k++) acc[k] = gelu2_tanh(acc[k]);
      int fb0, c_lo = 0, c_hi = 12;
      if (wg < 2) { fb0 = aj < 6 ? 12 * aj - 2 : 22 + 8 * aj; if (aj == 0) c_lo = 2; if (aj >= 6) c_hi = 8; }
      else { fb0 = aj < 2 ? 8 * aj : 12 * aj - 8; if (aj < 2) c_hi = 8; if (aj == 7) c_hi = 10; }
      if (wg < 2) {
        float s1[2][3], s2[2][3];
#pragma unroll
        for (int k = 0; k < 48; k++) {
          const int r = (k >> 1) & 1, gq = k < 8 ? 0 : (k < 32 ? 1 : 2);
          if (k - 2 * r == (gq == 0 ? 0 : (gq == 1 ? 8 : 32))) { s1[r][gq] = acc[k]; s2[r][gq] = acc[k] * acc[k]; }
          else { s1[r][gq] += acc[k]; s2[r][gq] = fmaf(acc[k], acc[k], s2[r][gq]); }
        }
        const float inv_n = __fdividef(0.125f, (float)(c_hi - c_lo));
        float mm[2], vv[2];
#pragma unroll
        for (int r = 0; r < 2; r++) {
          float a = s1[r][1], b = s2[r][1];
          if (c_lo == 0) { a += s1[r][0]; b += s2[r][0]; }
          if (c_hi == 12) { a += s1[r][2]; b += s2[r][2]; }
          a += __shfl_xor_sync(0xffffffffu, a, 1); b += __shfl_xor_sync(0xffffffffu, b, 1);
          a += __shfl_xor_sync(0xffffffffu, a, 2); b += __shfl_xor_sync(0xffffffffu, b, 2);
          mm[r] = a * inv_n;
          vv[r] = fmaxf(fmaf(-a, mm[r], b), 0.f);
        }
        const int r0 = half * 64 + w * 16 + g;
        mbar_wait(BAR(B_EPOCH), 0);
        const unsigned ep1 = lds32(sb + SM_MISC + 4 * M_EPOCH) + 1;
        if (threadIdx.x == 0) TS(67);
        const uint32_t tag = ep1 & 15;
        if (t4 < 2) {
          const float m = t4 ? mm[1] : mm[0], v = t4 ? vv[1] : vv[0];
          asm volatile("st.relaxed.gpu.global.b64 [%0], %1;" ::"l"(&g_lnstat[(ai * 8 + aj) * 128 + r0 + 8 * t4]),
                       "l"(((unsigned long long)((__float_as_uint(v) & ~15u) | tag) << 32) | __float_as_uint(m)) : "memory");
        }
        float sm[4], sv[4];
        const unsigned long long* lp = &g_lnstat[(ai * 8 + 2 * t4) * 128 + r0];
#pragma unroll 1
        for (int n = 0; n < SPIN_LIMIT; n++) {
          __nanosleep(LNSLEEP);
          uint32_t bad = 0;
#pragma unroll
          for (int e = 0; e < 4; e++) {
            unsigned long long a;
            asm volatile("ld.relaxed.gpu.global.b64 %0, [%1];" : "=l"(a) : "l"(lp + (e >> 1) * 128 + (e & 1) * 8) : "memory");
            bad |= (uint32_t)(a >> 32) ^ tag;
            sm[e] = __uint_as_float((uint32_t)a); sv[e] = __uint_as_float((uint32_t)(a >> 32));
          }
          if (__all_sync(0xffffffffu, (bad & 15) == 0)) break;
        }
        if (lane == 0) mbar_arrive(BAR(B_LNOK));
        if (threadIdx.x == 0) TS(68);
        const float na = t4 == 0 ? 80.f : (t4 == 3 ? 64.f : 96.f), nb = t4 == 3 ? 64.f : 96.f;
#pragma unroll
        for (int r = 0; r < 2; r++) {
          float t = fmaf(sm[r], na, sm[2 + r] * nb);
          t += __shfl_xor_sync(0xffffffffu, t, 1); t += __shfl_xor_sync(0xffffffffu, t, 2);
          const float mu = t * (1.f / 688.f);
          const float da = sm[r] - mu, db = sm[2 + r] - mu;
          float m2 = sv[r] + sv[2 + r] + na * da * da + nb * db * db;
          m2 += __shfl_xor_sync(0xffffffffu, m2, 1); m2 += __shfl_xor_sync(0xffffffffu, m2, 2);
          const float rs = rsqrtf(fmaf(m2, 1.f / 688.f, 4e-5f)), sh = -mu * rs;
#pragma unroll
          for (int k = 2 * r; k < 48; k += 4) { acc[k] = fmaf(acc[k], rs, sh); acc[k + 1] = fmaf(acc[k + 1], rs, sh); }
        }
        if (aj == 7) {
          c_hi = 10;
#pragma unroll
          for (int k = 32; k < 40; k++) acc[k] = 0.f;
        }
      }
      uint32_t* zp = wg < 2 ? reinterpret_cast<uint32_t*>(g_z2n) + (ai * 2 + half) * 2816 + w * 704
                            : reinterpret_cast<uint32_t*>(g_z1) + (ai * 88 * 16 + half * 8 + w * 2) * 32;
      const int mul = wg < 2 ? 373 : 0, cstr = wg < 2 ? 32 : 512, rstr = wg < 2 ? 352 : 32;
      auto zoff = [&](int c8) { const int fb = fb0 + c8; return ((fb * mul) >> 12) * (32 * 2816 - 352) + fb * cstr; };
#pragma unroll
      for (int c8 = 0; c8 < 12; c8++) {
        uint32_t* p = zp + zoff(c8) + lane;
        if (c8 >= c_lo && c8 < c_hi) { p[0] = pack_bf16(acc[4 * c8], acc[4 * c8 + 1]); p[rstr] = pack_bf16(acc[4 * c8 + 2], acc[4 * c8 + 3]); }
      }
      if (tid == 0) TS(wg == 0 ? 69 : 78 + wg);
      fence_async();
      __syncwarp();
      if (lane == 0) mbar_arrive(BAR(pass ? B_ZST1 : B_ZST0));
      if (!pass) finish_q();
    }
    if (wg == 3) {
      asm volatile("setmaxnreg.inc.sync.aligned.u32 120;");
      int st = 0, ph = 0;
      {
        float acc[88];
#pragma unroll
        for (int k = 0; k < 88; k++) acc[k] = 0.f;
        regfence(acc);
        const uint64_t da0 = mkdesc(sb + SM_RING, 16, 1024, 1), db0 = mkdesc(sb + SM_RING + 16384, 1408, 128, 0);
        uint32_t rel;
        asm("mapa.shared::cluster.u32 %0, %1, %2;" : "=r"(rel) : "r"(BAR(B_REMPTY)), "r"(lane & 1));
        rel -= BAR(B_RFULL);
#pragma unroll 1
        for (int n = 0; n < 11; n++) {
          uint64_t da = da0, db = db0;
          uint32_t fb = BAR(B_RFULL);
          const uint32_t fe = BAR(B_RFULL + (n < 10 ? 3 : 2));
#pragma unroll 1
          do {
            mbar_wait(fb, n & 1);
#pragma unroll
            for (int k = 0; k < 4; k++) {
              if (k % SBATCH == 0) wg_fence();
              wg_ss_n88<0, 88>(acc, da + 2 * k, db + 176 * k);
              wg_ss_n88<44, 88>(acc, da + (512 + 2 * k), db + 176 * k);
              if (k % SBATCH == SBATCH - 1) { wg_commit(); wg_wait<0>(); }
            }
            if (tid < 2) asm volatile("mbarrier.arrive.shared::cluster.b64 _, [%0];" ::"r"(rel + fb) : "memory");
            fb += 8; da += RSTAGE / 16; db += RSTAGE / 16;
          } while (fb != fe);
        }
        st = 2; ph = 0;
        regfence(acc);
        if (tid == 0) TS(11);
        mbar_wait(BAR(B_RFULL + st), ph);
        const uint8_t* zs = smem_raw + SM_RING + st * RSTAGE;
        uint32_t zmask = bj == 7 ? 0u : 0xFFFFFFFFu;
        asm volatile("" : "+r"(zmask));
        uint32_t* up = reinterpret_cast<uint32_t*>(g_u) + bi * 11 * 4096 + w * 512 + lane;
#pragma unroll
        for (int r = 0; r < 4; r++) {
          const int row = (r >> 1) * 64 + w * 16 + (r & 1) * 8 + g;
          const float og = fmaf(reinterpret_cast<const float*>(zs + 22528)[row], -0.5f, 0.5f);
          const float bs = __bfloat162float(reinterpret_cast<const __nv_bfloat16*>(zs + 23040)[row]) * og;
#pragma unroll
          for (int c8 = 0; c8 < 11; c8++) {
            const int k = (r >> 1) * 44 + c8 * 4 + (r & 1) * 2, cb = 11 * bj + c8;
            uint32_t zz = reinterpret_cast<const uint32_t*>(zs)[c8 * 512 + ((r >> 1) * 8 + w * 2 + (r & 1)) * 32 + lane];
            if (c8 >= 9) zz &= zmask;
            uint32_t v = pack_bf16(fmaf(acc[k], og, bs), fmaf(acc[k + 1], og, bs));
            asm("mul.rn.bf16x2 %0, %0, %1;" : "+r"(v) : "r"(zz));
            up[cb * 32 + (cb >> 3) * 3840 + ((r >> 1) * 8 + (r & 1)) * 256] = v;
          }
        }
        fence_async_smem();
        fence_async();
        bar_sync(4, 128);
        if (tid == 0) { mbar_arrive_both(BAR(B_REMPTY + st)); red_release(&g_ucnt[bi * 32]); TS(12); }
        if (++st == 3) { st = 0; ph ^= 1; }
      }
      float oc[64];
#pragma unroll
      for (int k = 0; k < 64; k++) oc[k] = 0.f;
      regfence(oc);
#pragma unroll 1
      for (int n = 0; n < 11; n++) {
        mbar_wait(BAR(B_RFULL + st), ph);
        const uint64_t da = mkdesc(sb + SM_RING + st * RSTAGE, 128, 1024, 0), db = mkdesc(sb + SM_RING + st * RSTAGE + 16384, 8192, 1024, 1);
#pragma unroll
        for (int k = 0; k < 4; k += 2) {
          wg_fence();
          wg_ss_n64<0, 64>(oc, da + 16 * k, db + 128 * k);
          wg_ss_n64<32, 64>(oc, da + 512 + 16 * k, db + 128 * k);
          wg_ss_n64<0, 64>(oc, da + 16 * k + 16, db + 128 * k + 128);
          wg_ss_n64<32, 64>(oc, da + 528 + 16 * k, db + 128 * k + 128);
          wg_commit();
          wg_wait<0>();
        }
        if (tid == 0) mbar_arrive_both(BAR(B_REMPTY + st));
        if (++st == 3) { st = 0; ph ^= 1; }
      }
      if (tid == 0) TS(13);
      mbar_wait(BAR(B_WOFULL), 0);
#pragma unroll 1
      for (int h = 0; h < 4; h++) {
        const uint64_t da = mkdesc(sb + SM_K + h * 32768, 128, 256, 0), db = mkdesc(sb + SM_RING + h * 2048, 8192, 1024, 1);
        mbar_wait(BAR(B_XFULL + 2 * h), 1);
        wg_fence();
#pragma unroll
        for (int c = 0; c < 8; c++) wg_ss_n64<0, 64>(oc, da + 128 * c, db + (c * 8192 + (c / 3) * (RSTAGE - 24576)) / 16);
        wg_commit();
        mbar_wait(BAR(B_XFULL + 2 * h + 1), 1);
#pragma unroll
        for (int c = 0; c < 8; c++) wg_ss_n64<32, 64>(oc, da + 1024 + 128 * c, db + (c * 8192 + (c / 3) * (RSTAGE - 24576)) / 16);
        wg_commit();
      }
      wg_wait<0>();
      regfence(oc);
      if (tid == 0) TS(14);
#pragma unroll
      for (int hf = 0; hf < 2; hf++) {
        const uint32_t rb = sb + SM_Q + (hf * 64 + w * 16) * 128, ra = rb + (lane & 15) * 128;
#pragma unroll
        for (int c = 0; c < 4; c++) {
          const int k = hf * 32 + c * 8;
          asm volatile("stmatrix.sync.aligned.m8n8.x4.shared.b16 [%0], {%1, %2, %3, %4};" ::"r"(ra + (((2 * c + (lane >> 4)) ^ (lane & 7)) << 4)),
                       "r"(pack_bf16(oc[k], oc[k + 1])), "r"(pack_bf16(oc[k + 2], oc[k + 3])), "r"(pack_bf16(oc[k + 4], oc[k + 5])), "r"(pack_bf16(oc[k + 6], oc[k + 7])) : "memory");
        }
        fence_async_smem();
        __syncwarp();
        asm volatile(ELECT "cp.async.bulk.tensor.2d.global.shared::cta.bulk_group [%0, {%2, %3}], [%1];\n}"
                     ::"l"(&tm_out), "r"(rb), "r"(64 * bj), "r"(bi * 128 + hf * 64 + w * 16) : "memory");
      }
      asm volatile("cp.async.bulk.commit_group;" ::: "memory");
      asm volatile("cp.async.bulk.wait_group.read 0;" ::: "memory");
      if (tid == 0) TS(15);
    } else {
      mbar_wait(BAR(B_QRDY), 0);
    if (tid == 0) TS(25 + wg);
    if (tid == 0) TS(28 + wg);
    if (threadIdx.x == 0) GTS(125);
    const uint64_t dv0 = mkdesc(sb + SM_K + 2048, SM_ONES - 2048, 256, 3);
    const int aw = wg == 0 ? 0 : 3 - wg;
    uint32_t chk = 0, pend = 0;
    uint32_t* const obase = reinterpret_cast<uint32_t*>(g_o) + ai * 32768 + aj * 512 + w * 128 + lane;
    const uint32_t gbase = sb + SM_G + (w * 16 + g) * 4;
    auto flush = [&](const float (&o)[12], int tau) {
      chk ^= pend; pend = store_o_tile(o, obase, gbase, tile_of(tau), lane);
      if ((0x52 >> tau) & 1) {
        consume(chk ^ pend, sb);
        fence_async();
        bar_sync(1 + wg, 128);
        if (tid == 0) red_relaxed(&g_ocnt[ai * 32 + 16 * 32]);
      }
    };
    float o[12], s[32];
    uint32_t q[4], p0[16], p1[16];
    if (lds32(sb + SM_MISC + 4 * M_FAST)) {
      const uint32_t mlo = lds32(sb + SM_MISC + 4 * M_MASK), mhi = ~mlo;
      uint64_t dv = dv0;
#define STEP(PIN, POUT) { wg_fence(); issue_qk(s, q, dv + (VSTEP8 + KOFF)); wg_commit(); issue_pv(o, PIN, dv); dv += VSTEP8; wg_commit(); \
                          wg_wait<1>(); regfence(s); softmax_step(s, POUT, mlo, mhi); wg_wait<0>(); }
      int tau = aw * 3 - (aw > 0), seg = (3 - aw) % 3;
      float4* part = g_part + blockIdx.x * 768 + tid;
#pragma unroll 1
      for (int it = 0; it < 8; it++) {
        int n2 = seg == 1 ? 6 : 5;
        if (it < 3) {
          mbar_wait(BAR(seg ? B_KVB : B_KVFULL), 0);
          mbar_wait(BAR(seg == 2 ? B_KVC : B_KVFULL), 0);
        }
#pragma unroll
        for (int k = 0; k < 32; k++) s[k] = k < NP / 2 ? MAGIC_C : 0.f;
        if (it == 0 || seg == 0) {
          const int j0 = seg == 0 ? 0 : (seg == 1 ? 10 : 22);
          dv = dv0 + VSTEP8 * j0;
          const uint4 qv = lds128(sb + SM_Q + tile_of(tau) * 2048 + tid * 16);
          q[0] = qv.x; q[1] = qv.y; q[2] = qv.z; q[3] = qv.w;
          if (it + aw > 5 && aw < 2 && tau == aw * 3 + 2) {
            bar_sync(6 + aw, 256);
            const float4 a = part[aw * 384], b = part[aw * 384 + 128], c = part[aw * 384 + 256];
            o[0] = a.x; o[1] = a.y; o[2] = a.z; o[3] = a.w; o[4] = b.x; o[5] = b.y; o[6] = b.z; o[7] = b.w; o[8] = c.x; o[9] = c.y; o[10] = c.z; o[11] = c.w;
          } else {
#pragma unroll
            for (int k = 0; k < 12; k++) o[k] = 0.f;
          }
          regfence(s);
          wg_fence(); issue_qk(s, q, dv + KOFF); wg_commit();
          wg_wait<0>(); regfence(s);
          softmax_step(s, p0, mlo, mhi);
          regfence(o);
          STEP(p0, p1);
          n2--;
        }
        regfence(s);
#pragma unroll 1
        for (; n2 > 0; n2--) { STEP(p1, p0); STEP(p0, p1); }
        if (it == 7 || seg == 2) {
          wg_fence(); issue_pv(o, p1, dv); wg_commit();
          wg_wait<0>(); regfence(o);
          if (it < aw) {
            float4* pp = part + (aw - 1) * 384;
            pp[0] = make_float4(o[0], o[1], o[2], o[3]); pp[128] = make_float4(o[4], o[5], o[6], o[7]); pp[256] = make_float4(o[8], o[9], o[10], o[11]);
            __threadfence_block();
            bar_arrive(5 + aw, 256);
          } else {
            flush(o, tau);
          }
        }
        if (++seg == 3) { seg = 0; tau++; }
      }
#undef STEP
    } else {
      mbar_wait(BAR(B_KFB), 0);
      constexpr float SC = 0.25f * 1.4426950408889634f;
#pragma unroll 1
      for (int tau = wg * 3; tau < wg * 3 + 3 && tau < 8; tau++) {
        const uint4 qv = lds128(sb + SM_Q + tile_of(tau) * 2048 + tid * 16);
        float m0 = -INFINITY, m1 = -INFINITY;
#pragma unroll
        for (int k = 0; k < 12; k++) o[k] = 0.f;
        uint64_t dv = dv0;
#pragma unroll 1
        for (int j = 0; j < 32; j++) {
          regfence(s);
          wg_fence(); wg_qkb_n64<0, 0, 32>(s, qv.x, qv.y, qv.z, qv.w, dv + KOFF); wg_commit();
          wg_wait<0>(); regfence(s);
          float x0 = m0, x1 = m1;
#pragma unroll
          for (int k = 0; k < 32; k++) { s[k] *= SC; if (k & 2) x1 = fmaxf(x1, s[k]); else x0 = fmaxf(x0, s[k]); }
          x0 = fmaxf(x0, __shfl_xor_sync(0xffffffffu, x0, 1)); x0 = fmaxf(x0, __shfl_xor_sync(0xffffffffu, x0, 2));
          x1 = fmaxf(x1, __shfl_xor_sync(0xffffffffu, x1, 1)); x1 = fmaxf(x1, __shfl_xor_sync(0xffffffffu, x1, 2));
          const float c0 = ex2(m0 - x0), c1 = ex2(m1 - x1);
          m0 = x0; m1 = x1;
#pragma unroll
          for (int k = 0; k < 12; k++) o[k] *= (k & 2) ? c1 : c0;
#pragma unroll
          for (int k = 0; k < 16; k++) { const float m = (k & 1) ? m1 : m0; p0[k] = exp_mufu(s[2 * k] - m, s[2 * k + 1] - m); }
          regfence(o);
          wg_fence(); issue_pv(o, p0, dv); dv += VSTEP8; wg_commit();
          wg_wait<0>(); regfence(o);
        }
        flush(o, tau);
      }
    }
    consume(chk ^ pend, sb);
    fence_async();
    bar_sync(1 + wg, 128);
    if (tid == 0) { red_relaxed(&g_ocnt[ai * 32]); mbar_arrive_both(BAR(B_ATT)); TS(31 + wg); if (wg == 0) GTS(124); }
    }
  }
  __syncwarp();
  asm volatile("barrier.cluster.arrive.relaxed;" ::: "memory");
  asm volatile("barrier.cluster.wait;" ::: "memory");
}

typedef CUresult (*EncodeFn)(CUtensorMap*, CUtensorMapDataType, cuuint32_t, void*, const cuuint64_t*, const cuuint64_t*,
                             const cuuint32_t*, const cuuint32_t*, CUtensorMapInterleave, CUtensorMapSwizzle,
                             CUtensorMapL2promotion, CUtensorMapFloatOOBfill);

void make_map(EncodeFn enc, CUtensorMap* tm, const void* base, uint64_t cols, uint64_t rows, uint32_t bc, uint32_t br, CUtensorMapSwizzle sw) {
  cuuint64_t gd[2] = {cols, rows};
  cuuint64_t gs[1] = {cols * 2};
  cuuint32_t bd[2] = {bc, br};
  cuuint32_t es[2] = {1, 1};
  enc(tm, CU_TENSOR_MAP_DATA_TYPE_BFLOAT16, 2, const_cast<void*>(base), gd, gs, bd, es, CU_TENSOR_MAP_INTERLEAVE_NONE, sw,
      CU_TENSOR_MAP_L2_PROMOTION_L2_128B, CU_TENSOR_MAP_FLOAT_OOB_FILL_NONE);
}

}

extern "C" void kernel_launch(void* const* d_in, const int* in_sizes, int n_in, void* d_out, int out_size) {
  (void)in_sizes; (void)n_in; (void)out_size;
  static EncodeFn enc = nullptr;
  if (!enc) {
    void* fn = nullptr;
    cudaDriverEntryPointQueryResult qr;
    cudaGetDriverEntryPoint("cuTensorMapEncodeTiled", &fn, cudaEnableDefault, &qr);
    enc = (EncodeFn)fn;
    cudaFuncSetAttribute(fused_kernel, cudaFuncAttributeMaxDynamicSharedMemorySize, SMEM_BYTES);
  }
  CUtensorMap tx, tq, tin, tsp, tout, to, ty;
  make_map(enc, &ty, d_out, 512, 2048, 64, 16, CU_TENSOR_MAP_SWIZZLE_128B);
  make_map(enc, &tx, d_in[0], 512, 2048, 64, 128, CU_TENSOR_MAP_SWIZZLE_128B);
  make_map(enc, &tq, d_in[1], 512, 512, 32, 32, CU_TENSOR_MAP_SWIZZLE_64B);
  make_map(enc, &to, d_in[4], 512, 512, 64, 64, CU_TENSOR_MAP_SWIZZLE_128B);
  {
    cuuint64_t gd[3] = {32, 512, 43};
    cuuint64_t gs[2] = {1376 * 2, 64};
    cuuint32_t bd[3] = {32, 32, 3};
    cuuint32_t es[3] = {1, 1, 1};
    enc(&tin, CU_TENSOR_MAP_DATA_TYPE_BFLOAT16, 3, d_in[6], gd, gs, bd, es, CU_TENSOR_MAP_INTERLEAVE_NONE, CU_TENSOR_MAP_SWIZZLE_64B,
        CU_TENSOR_MAP_L2_PROMOTION_L2_128B, CU_TENSOR_MAP_FLOAT_OOB_FILL_NONE);
  }
  make_map(enc, &tsp, d_in[7], 2048, 2048, 64, 64, CU_TENSOR_MAP_SWIZZLE_128B);
  make_map(enc, &tout, d_in[9], 512, 688, 64, 64, CU_TENSOR_MAP_SWIZZLE_128B);
  Params prm;
  prm.gate_w = (const __nv_bfloat16*)d_in[10];
  prm.b_sp = (const __nv_bfloat16*)d_in[8];
  prm.w_out = (const __nv_bfloat16*)d_in[9];
  prm.wo = (const __nv_bfloat16*)d_in[4];
  prm.w_in = (const __nv_bfloat16*)d_in[6];
  prm.wq = (const __nv_bfloat16*)d_in[1];
  prm.wk = (const __nv_bfloat16*)d_in[2];
  prm.wv = (const __nv_bfloat16*)d_in[3];
  fused_kernel<<<NCTA, NTHREADS, SMEM_BYTES>>>(tx, tq, tin, tsp, tout, to, ty, prm);
}
```
